```python
import torch

def _softmax(x, axis=-1):
    return torch.softmax(x, dim=axis)

def _gelu(x):
    return torch.nn.functional.gelu(x, approximate='tanh')

def _silu(x):
    return torch.nn.functional.silu(x)

def _sigmoid(x):
    return torch.sigmoid(x)

def _layernorm(x, axis=-1, eps=1e-05):
    m = x.mean(dim=axis, keepdim=True)
    v = x.var(dim=axis, keepdim=True, unbiased=False)
    return (x - m) / torch.sqrt(v + eps)

def _scatter_add(tgt, idx, src, axis=0):
    return tgt.clone().index_add_(axis, idx, src)

def _segment_sum(src, seg, n):
    out = torch.zeros((n,) + src.shape[1:], dtype=src.dtype)
    return out.index_add_(0, seg, src)

def _pad(x, pw):
    flat = tuple((v for pair in reversed(pw) for v in pair))
    return torch.nn.functional.pad(x, flat)
kernel_name = 'interleave_layers__memory_aug_recurrent_mem_tr__moe_arch_mod__prompt'

def setup_inputs():

    _w = lambda a: (lambda t: t.to(torch.bfloat16) if t.is_floating_point() else t)(torch.as_tensor(a))

    def _A_setup():
        B, S, Dm = (1, 2048, 512)
        H, Dh = (32, 128)
        M, seg = (8, 32)
        seg = min(seg, S)
        S = S // seg * seg
        return {'x': _w((lambda *s: torch.randn(*s, dtype=torch.bfloat16) * 0.05)(B, S, Dm)), 'mem0': _w((lambda *s: torch.randn(*s, dtype=torch.bfloat16) * 0.8)(B, M, Dm)), 'Wq': _w((lambda *s: torch.randn(*s, dtype=torch.bfloat16) * 0.8)(Dm, H, Dh) * Dm ** (-0.5)), 'Wk': _w((lambda *s: torch.randn(*s, dtype=torch.bfloat16) * 0.8)(Dm, H, Dh) * Dm ** (-0.5)), 'Wv': _w((lambda *s: torch.randn(*s, dtype=torch.bfloat16) * 0.8)(Dm, H, Dh) * Dm ** (-0.5)), 'Wo': _w((lambda *s: torch.randn(*s, dtype=torch.bfloat16) * 0.8)(H, Dh, Dm) * (H * Dh) ** (-0.5)), 'seg_len': seg}
    _A_in = _A_setup()

    def _B_setup():
        B, S, D, F, C = (1, 2048, 512, 1792, 1)
        return {'x': _w((lambda *s: torch.randn(*s, dtype=torch.bfloat16) * 0.05)(B, S, D)), 'w_r': _w((lambda *s: torch.randn(*s, dtype=torch.bfloat16) * 0.05)(D)), 'w_gate': _w((lambda *s: torch.randn(*s, dtype=torch.bfloat16) * 0.05)(D, F)), 'w_up': _w((lambda *s: torch.randn(*s, dtype=torch.bfloat16) * 0.05)(D, F)), 'w_down': _w((lambda *s: torch.randn(*s, dtype=torch.bfloat16) * 0.05)(F, D))}
    _B_in = _B_setup()
    return {'A_x': _A_in['x'], 'A_mem0': _A_in['mem0'], 'A_Wq': _A_in['Wq'], 'A_Wk': _A_in['Wk'], 'A_Wv': _A_in['Wv'], 'A_Wo': _A_in['Wo'], 'A_seg_len': _A_in['seg_len'], 'B_x': _B_in['x'], 'B_w_r': _B_in['w_r'], 'B_w_gate': _B_in['w_gate'], 'B_w_up': _B_in['w_up'], 'B_w_down': _B_in['w_down']}

def reference(A_x, A_mem0, A_Wq, A_Wk, A_Wv, A_Wo, A_seg_len, B_x, B_w_r, B_w_gate, B_w_up, B_w_down):

    def _A_ref(x, mem0, Wq, Wk, Wv, Wo, seg_len):
        B, S, Dm = x.shape
        H, Dh = (Wq.shape[1], Wq.shape[2])
        M = mem0.shape[1]
        scale = Dh ** (-0.5)
        n_seg = S // seg_len
        L = M + seg_len
        idx = torch.arange(L)
        mask = (idx[:, None] < M) | (idx[:, None] >= idx[None, :])
        mem = mem0
        outs = []
        for s in range(n_seg):
            xs = x[:, s * seg_len:(s + 1) * seg_len, :].clone()
            h = torch.concatenate([mem, xs], axis=1)
            q = torch.einsum('btd,dhe->bhte', h, Wq)
            k = torch.einsum('btd,dhe->bhte', h, Wk)
            v = torch.einsum('btd,dhe->bhte', h, Wv)
            scores = torch.einsum('bhqe,bhke->bhqk', q, k) * scale
            scores = torch.where(mask[None, None], scores, -1000000000.0)
            p = _softmax(scores, axis=-1)
            o = torch.einsum('bhqk,bhke->bhqe', p, v)
            o = torch.einsum('bhte,hed->btd', o, Wo)
            mem = o[:, :M, :].clone()
            outs.append(o[:, M:, :])
        return torch.concatenate(outs, axis=1)

    def _B_ref(x, w_r, w_gate, w_up, w_down):
        B, S, D = x.shape
        C = 1
        r = x @ w_r
        idx = torch.argsort(-r, axis=-1)[:, :C]
        idx_e = (lambda x, n, axis: torch.repeat_interleave(x, n, dim=axis))(idx.reshape(B, C, 1), D, axis=2)
        x_sel = (lambda x, i, axis: torch.take_along_dim(x, i, dim=axis))(x, idx_e, axis=1)
        g = _silu(x_sel @ w_gate)
        u = x_sel @ w_up
        y = g * u @ w_down
        r_sel = _sigmoid((lambda x, i, axis: torch.take_along_dim(x, i, dim=axis))(r, idx, axis=1))
        y = y * r_sel.reshape(B, C, 1)
        b_off = (torch.arange(B) * S).reshape(B, 1)
        flat_idx = (idx + b_off).reshape(B * C)
        zero = (x * 0.0).reshape(B * S, D)
        upd = _scatter_add(zero, flat_idx, y.reshape(B * C, D), axis=0)
        return x + upd.reshape(B, S, D)
    x = A_x
    x = x + _A_ref(_layernorm(x, axis=-1), A_mem0, A_Wq, A_Wk, A_Wv, A_Wo, A_seg_len)
    x = x + _B_ref(_layernorm(x, axis=-1), B_w_r, B_w_gate, B_w_up, B_w_down)
    x = x + _A_ref(_layernorm(x, axis=-1), A_mem0, A_Wq, A_Wk, A_Wv, A_Wo, A_seg_len)
    x = x + _B_ref(_layernorm(x, axis=-1), B_w_r, B_w_gate, B_w_up, B_w_down)
    return x
```

```cpp
#include <cuda_runtime.h>
#include <cuda_bf16.h>
#include <stdint.h>

namespace {

typedef __nv_bfloat16 bf16;
typedef unsigned long long u64;

constexpr int NTOK = 2048, DM = 512, HD = 4096, NSEG = 64, FF = 1792;
#define DELTA 4
constexpr int NSTEP = NSEG + DELTA;
constexpr int SPIN_LIMIT = 40000;
constexpr int MBAR_LIMIT = 20000;
constexpr int NWORK = 36;
constexpr int OSLOTS = 8;

__device__ __align__(1024) uint8_t g_xs[2][NSEG * 32768];
__device__ __align__(1024) uint8_t g_patch[NSEG * 8192];
__device__ __align__(1024) uint8_t g_O[3][OSLOTS * 32 * 8192];
__device__ __align__(1024) float g_part[3][2 * 32 * 8 * DM];
__device__ __align__(1024) bf16 g_xr[3][NTOK * DM];
__device__ __align__(1024) bf16 g_y[3][NTOK * DM];
__device__ __align__(1024) bf16 g_x2[NTOK * DM];
__device__ __align__(1024) bf16 g_x2p[NSEG * DM];
__device__ __align__(1024) bf16 g_fin[NTOK * DM];
__device__ __align__(65536) uint32_t g_M[4 * 16384];
__device__ __align__(65536) uint32_t g_P[96 * 4096];
struct Flags {
  uint32_t pol[96];
  uint32_t oflag[3][NSEG][8];
  uint32_t ffncnt[NSEG + 1][8];
  uint32_t patch[NSEG][8];
  u64 key[3][NSEG][32];
  float upd[NSEG + 1][DM];
};
__device__ __align__(1024) Flags g_fl;
#define TR(e)
#define TRV(e, v)
#define TG(i)
#define TRDUMP
#define TREXTRA 0

__device__ __forceinline__ uint32_t smem_u32(const void* p) { return (uint32_t)__cvta_generic_to_shared(p); }
__device__ __forceinline__ uint32_t pack_bf16(float lo, float hi) {
  uint32_t r;
  asm("cvt.rn.bf16x2.f32 %0, %1, %2;" : "=r"(r) : "f"(hi), "f"(lo));
  return r;
}
__device__ __forceinline__ float bf_lo(uint32_t v) { return __uint_as_float(v << 16); }
__device__ __forceinline__ float bf_hi(uint32_t v) { return __uint_as_float(v & 0xffff0000u); }
__device__ __forceinline__ float ex2_fast(float x) { float y; asm("ex2.approx.ftz.f32 %0, %1;" : "=f"(y) : "f"(x)); return y; }
__device__ __forceinline__ float rcp_fast(float x) { float y; asm("rcp.approx.ftz.f32 %0, %1;" : "=f"(y) : "f"(x)); return y; }
__device__ __forceinline__ float round_bf16(float x) { return __bfloat162float(__float2bfloat16_rn(x)); }
__device__ __forceinline__ uint32_t clk32() { uint32_t t; asm volatile("mov.u32 %0, %%clock;" : "=r"(t) :: "memory"); return t; }
__device__ __forceinline__ void spin_until(uint32_t t0, uint32_t d) { while (clk32() - t0 < d) {} }

__device__ __forceinline__ void mma16816(float (&d)[4], uint32_t a0, uint32_t a1, uint32_t a2, uint32_t a3,
                                         uint32_t b0, uint32_t b1) {
  asm("mma.sync.aligned.m16n8k16.row.col.f32.bf16.bf16.f32 {%0,%1,%2,%3}, {%4,%5,%6,%7}, {%8,%9}, {%0,%1,%2,%3};"
      : "+f"(d[0]), "+f"(d[1]), "+f"(d[2]), "+f"(d[3])
      : "r"(a0), "r"(a1), "r"(a2), "r"(a3), "r"(b0), "r"(b1));
}
__device__ __forceinline__ void mma1688(float (&d)[4], uint32_t a0, uint32_t a1, uint32_t b0) {
  asm("mma.sync.aligned.m16n8k8.row.col.f32.bf16.bf16.f32 {%0,%1,%2,%3}, {%4,%5}, {%6}, {%0,%1,%2,%3};"
      : "+f"(d[0]), "+f"(d[1]), "+f"(d[2]), "+f"(d[3])
      : "r"(a0), "r"(a1), "r"(b0));
}
__device__ __forceinline__ void ldsm4(uint32_t (&r)[4], uint32_t addr) {
  asm volatile("ldmatrix.sync.aligned.m8n8.x4.shared.b16 {%0,%1,%2,%3}, [%4];"
               : "=r"(r[0]), "=r"(r[1]), "=r"(r[2]), "=r"(r[3]) : "r"(addr) : "memory");
}
__device__ __forceinline__ void ldsm4t(uint32_t (&r)[4], uint32_t addr) {
  asm volatile("ldmatrix.sync.aligned.m8n8.x4.trans.shared.b16 {%0,%1,%2,%3}, [%4];"
               : "=r"(r[0]), "=r"(r[1]), "=r"(r[2]), "=r"(r[3]) : "r"(addr) : "memory");
}
__device__ __forceinline__ void stsm4(uint32_t addr, uint32_t a, uint32_t b, uint32_t c, uint32_t d) {
  asm volatile("stmatrix.sync.aligned.m8n8.x4.shared.b16 [%0], {%1,%2,%3,%4};" ::"r"(addr), "r"(a), "r"(b), "r"(c), "r"(d) : "memory");
}
__device__ __forceinline__ uint4 lds128(uint32_t a) {
  uint4 v; asm volatile("ld.shared.v4.b32 {%0,%1,%2,%3}, [%4];" : "=r"(v.x), "=r"(v.y), "=r"(v.z), "=r"(v.w) : "r"(a) : "memory"); return v;
}
__device__ __forceinline__ uint32_t lds32(uint32_t a) { uint32_t v; asm volatile("ld.shared.b32 %0, [%1];" : "=r"(v) : "r"(a) : "memory"); return v; }
__device__ __forceinline__ void sts32(uint32_t a, uint32_t x) { asm volatile("st.shared.b32 [%0], %1;" ::"r"(a), "r"(x) : "memory"); }
__device__ __forceinline__ void sts128(uint32_t a, uint4 v) {
  asm volatile("st.shared.v4.b32 [%0], {%1,%2,%3,%4};" ::"r"(a), "r"(v.x), "r"(v.y), "r"(v.z), "r"(v.w) : "memory");
}
__device__ __forceinline__ void cp16(uint32_t dst, const void* src) {
  asm volatile("cp.async.cg.shared.global [%0], [%1], 16;" ::"r"(dst), "l"(src) : "memory");
}
__device__ __forceinline__ void mbar_init(uint32_t mbar, uint32_t cnt) {
  asm volatile("mbarrier.init.shared.b64 [%0], %1;" ::"r"(mbar), "r"(cnt) : "memory");
}
__device__ __forceinline__ void mbar_expect_tx(uint32_t mbar, uint32_t bytes) {
  asm volatile("mbarrier.arrive.expect_tx.shared.b64 _, [%0], %1;" ::"r"(mbar), "r"(bytes) : "memory");
}
__device__ __forceinline__ void mbar_arrive(uint32_t mbar) {
  asm volatile("mbarrier.arrive.shared.b64 _, [%0];" ::"r"(mbar) : "memory");
}
__device__ __forceinline__ void mbar_arrive_remote(uint32_t mbar) {
  asm volatile("mbarrier.arrive.shared::cluster.b64 _, [%0];" ::"r"(mbar) : "memory");
}
__device__ __forceinline__ bool mbar_try(uint32_t mbar, uint32_t par) {
  uint32_t ok;
  asm volatile("{ .reg .pred p; mbarrier.try_wait.parity.shared::cta.b64 p, [%1], %2; selp.u32 %0, 1, 0, p; }"
               : "=r"(ok) : "r"(mbar), "r"(par) : "memory");
  return ok;
}
__device__ __forceinline__ void fail(int) { __trap(); }
__device__ __forceinline__ void give_up(int it, int limit, int code) { if (it > limit) fail(code); }
__device__ __forceinline__ void mbar_wait(uint32_t mbar, uint32_t par, int code) {
  int it = 0;
  while (!mbar_try(mbar, par)) give_up(++it, MBAR_LIMIT, code);
}
__device__ __forceinline__ void mbar_gate(uint32_t mbar, uint32_t par) {
  const uint32_t t0 = clk32();
  while (!mbar_try(mbar, par) && clk32() - t0 < 20000) {}
}
__device__ __forceinline__ void bulk_g2s(uint32_t dst, const void* src, uint32_t bytes, uint32_t mbar) {
  asm volatile("cp.async.bulk.shared::cluster.global.mbarrier::complete_tx::bytes [%0], [%1], %2, [%3];"
               ::"r"(dst), "l"(src), "r"(bytes), "r"(mbar) : "memory");
}
__device__ __forceinline__ void bulk_s2r(uint32_t dst, uint32_t src, uint32_t bytes, uint32_t mbar) {
  asm volatile("cp.async.bulk.shared::cluster.shared::cta.mbarrier::complete_tx::bytes [%0], [%1], %2, [%3];"
               ::"r"(dst), "r"(src), "r"(bytes), "r"(mbar) : "memory");
}
__device__ __forceinline__ void bulk_s2g(void* dst, uint32_t src, uint32_t bytes) {
  asm volatile("cp.async.bulk.global.shared::cta.bulk_group [%0], [%1], %2;" ::"l"(dst), "r"(src), "r"(bytes) : "memory");
}
__device__ __forceinline__ void fence_async_smem() { asm volatile("fence.proxy.async.shared::cta;" ::: "memory"); }
__device__ __forceinline__ void fence_async_glb() { asm volatile("fence.proxy.async.global;" ::: "memory"); }
__device__ __forceinline__ void bar_sync(int id, int n) { asm volatile("bar.sync %0, %1;" ::"r"(id), "r"(n) : "memory"); }
__device__ __forceinline__ void bar_arrive(int id, int n) { asm volatile("bar.arrive %0, %1;" ::"r"(id), "r"(n) : "memory"); }
__device__ __forceinline__ void cluster_sync() { asm volatile("barrier.cluster.arrive.release; barrier.cluster.wait.acquire;" ::: "memory"); }
__device__ __forceinline__ uint32_t mapa_u32(uint32_t a, uint32_t r) {
  uint32_t o;
  asm("mapa.shared::cluster.u32 %0, %1, %2;" : "=r"(o) : "r"(a), "r"(r));
  return o;
}
__device__ __forceinline__ void st_async32(uint32_t a, uint32_t x, uint32_t mbar) {
  asm volatile("st.async.weak.shared::cluster.mbarrier::complete_tx::bytes.b32 [%0], %1, [%2];" ::"r"(a), "r"(x), "r"(mbar) : "memory");
}
__device__ __forceinline__ uint4 ld_rlx128(const void* p) {
  uint4 v;
  asm volatile("ld.relaxed.gpu.global.v4.u32 {%0,%1,%2,%3}, [%4];" : "=r"(v.x), "=r"(v.y), "=r"(v.z), "=r"(v.w) : "l"(p) : "memory");
  return v;
}
__device__ __forceinline__ uint2 ld_rlx64(const void* p) {
  uint2 v; asm volatile("ld.relaxed.gpu.global.v2.u32 {%0,%1}, [%2];" : "=r"(v.x), "=r"(v.y) : "l"(p) : "memory"); return v;
}
__device__ __forceinline__ uint32_t ld_rlx32(const void* p) {
  uint32_t v; asm volatile("ld.relaxed.gpu.global.u32 %0, [%1];" : "=r"(v) : "l"(p) : "memory"); return v;
}
__device__ __forceinline__ void st_rlx32(void* p, uint32_t a) { asm volatile("st.relaxed.gpu.global.u32 [%0], %1;" ::"l"(p), "r"(a) : "memory"); }
__device__ __forceinline__ void red_release(uint32_t* p) { asm volatile("red.release.gpu.global.add.u32 [%0], 1;" ::"l"(p) : "memory"); }
__device__ __forceinline__ void st_release32(void* p, uint32_t a) { asm volatile("st.release.gpu.global.u32 [%0], %1;" ::"l"(p), "r"(a) : "memory"); }
__device__ __forceinline__ void st_release_u64(void* p, u64 a) { asm volatile("st.release.gpu.global.u64 [%0], %1;" ::"l"(p), "l"(a) : "memory"); }
__device__ __forceinline__ uint32_t ld_acq32(const void* p) {
  uint32_t v; asm volatile("ld.acquire.gpu.global.u32 %0, [%1];" : "=r"(v) : "l"(p) : "memory"); return v;
}
__device__ __forceinline__ u64 ld_acq_u64(const void* p) {
  u64 v; asm volatile("ld.acquire.gpu.global.u64 %0, [%1];" : "=l"(v) : "l"(p) : "memory"); return v;
}
__device__ __forceinline__ void wait_count(const uint32_t* p, uint32_t val, int code) {
  int it = 0;
  while (ld_acq32(p) < val) {
    give_up(++it, SPIN_LIMIT, code);
    __nanosleep(40);
  }
}
__device__ __forceinline__ u64 wait_keys(const u64* keys, int lane, int code) {
  u64 k;
  int it = 0;
  while (true) {
    k = ld_acq_u64(keys + lane);
    if (__all_sync(~0u, k != 0)) break;
    give_up(++it, SPIN_LIMIT, code);
    __nanosleep(100);
  }
  __syncwarp();
  const uint32_t hi = __reduce_max_sync(~0u, (uint32_t)(k >> 32));
  const uint32_t lo = __reduce_max_sync(~0u, (uint32_t)(k >> 32) == hi ? (uint32_t)k : 0u);
  return (u64)hi << 32 | lo;
}
__device__ __forceinline__ int key_token(u64 k) { return (int)(~(uint32_t)k) & (NTOK - 1); }
__device__ __forceinline__ float key_score(u64 k) {
  const uint32_t ob = (uint32_t)(k >> 32);
  return __uint_as_float((ob & 0x80000000u) ? (ob & 0x7fffffffu) : ~ob);
}

__device__ __forceinline__ uint32_t desc_lo(uint32_t saddr, uint32_t lbo) { return ((saddr & 0x3FFFF) >> 4) | (lbo >> 4) << 16; }
constexpr uint32_t desc_hi(uint32_t sbo, uint32_t sw128) { return (sbo >> 4) | sw128 << 30; }
template <int N> __device__ __forceinline__ void reg_inc() { asm volatile("setmaxnreg.inc.sync.aligned.u32 %0;" ::"n"(N)); }
template <int N> __device__ __forceinline__ void reg_dec() { asm volatile("setmaxnreg.dec.sync.aligned.u32 %0;" ::"n"(N)); }
__device__ __forceinline__ void wg_fence() { asm volatile("wgmma.fence.sync.aligned;" ::: "memory"); }
__device__ __forceinline__ void wg_commit() { asm volatile("wgmma.commit_group.sync.aligned;" ::: "memory"); }
template <int N> __device__ __forceinline__ void wg_wait() { asm volatile("wgmma.wait_group.sync.aligned %0;" ::"n"(N) : "memory"); }
template <int N> __device__ __forceinline__ void acc_fence(float (&d)[N]) {
#pragma unroll
  for (int i = 0; i < N; i++) asm volatile("" : "+f"(d[i]) :: "memory");
}
#define O4(d, i) "+f"(d[i]), "+f"(d[i + 1]), "+f"(d[i + 2]), "+f"(d[i + 3])
template <int TB, int ACC, uint32_t HI>
__device__ __forceinline__ void wg_rs8(float (&d)[4], const uint32_t (&a)[4], uint32_t db) {
  asm volatile("{ .reg .b64 b; mov.b64 b, {%8, %11};\n"
               "wgmma.mma_async.sync.aligned.m64n8k16.f32.bf16.bf16 {%0,%1,%2,%3}, {%4,%5,%6,%7}, b, %9, 1, 1, %10; }"
               : O4(d, 0) : "r"(a[0]), "r"(a[1]), "r"(a[2]), "r"(a[3]), "r"(db), "n"(ACC), "n"(TB), "n"(HI));
}
template <int TB, int ACC, uint32_t HI>
__device__ __forceinline__ void wg_rs24(float (&d)[12], const uint32_t (&a)[4], uint32_t db) {
  asm volatile("{ .reg .b64 b; mov.b64 b, {%16, %19};\n"
               "wgmma.mma_async.sync.aligned.m64n24k16.f32.bf16.bf16 {%0,%1,%2,%3,%4,%5,%6,%7,%8,%9,%10,%11}, {%12,%13,%14,%15}, b, %17, 1, 1, %18; }"
               : O4(d, 0), O4(d, 4), O4(d, 8) : "r"(a[0]), "r"(a[1]), "r"(a[2]), "r"(a[3]), "r"(db), "n"(ACC), "n"(TB), "n"(HI));
}
template <int TB, int ACC, uint32_t HI>
__device__ __forceinline__ void wg_rs32(float (&d)[16], const uint32_t (&a)[4], uint32_t db) {
  asm volatile("{ .reg .b64 b; mov.b64 b, {%20, %23};\n"
               "wgmma.mma_async.sync.aligned.m64n32k16.f32.bf16.bf16 {%0,%1,%2,%3,%4,%5,%6,%7,%8,%9,%10,%11,%12,%13,%14,%15}, {%16,%17,%18,%19}, b, %21, 1, 1, %22; }"
               : O4(d, 0), O4(d, 4), O4(d, 8), O4(d, 12) : "r"(a[0]), "r"(a[1]), "r"(a[2]), "r"(a[3]), "r"(db), "n"(ACC), "n"(TB), "n"(HI));
}
template <int ACC, uint32_t HIA, uint32_t HIB>
__device__ __forceinline__ void wg_ss24(float (&d)[12], uint32_t da, uint32_t db) {
  asm volatile("{ .reg .b64 a, b; mov.b64 a, {%12, %15}; mov.b64 b, {%13, %16};\n"
               "wgmma.mma_async.sync.aligned.m64n24k16.f32.bf16.bf16 {%0,%1,%2,%3,%4,%5,%6,%7,%8,%9,%10,%11}, a, b, %14, 1, 1, 1, 1; }"
               : O4(d, 0), O4(d, 4), O4(d, 8) : "r"(da), "r"(db), "n"(ACC), "n"(HIA), "n"(HIB));
}

__device__ __forceinline__ void warp_ln(const float (&x)[16], float (&y)[16], float& extra) {
  float m = (((x[0] + x[1]) + (x[2] + x[3])) + ((x[4] + x[5]) + (x[6] + x[7]))) + (((x[8] + x[9]) + (x[10] + x[11])) + ((x[12] + x[13]) + (x[14] + x[15])));
  m *= (1.f / 16);
  float v0 = 0.f, v1 = 0.f;
#pragma unroll
  for (int i = 0; i < 16; i += 2) { const float d0 = x[i] - m, d1 = x[i + 1] - m; v0 = fmaf(d0, d0, v0); v1 = fmaf(d1, d1, v1); }
  float v = v0 + v1;
#pragma unroll
  for (int o = 1; o <= 16; o <<= 1) {
    const float mo = __shfl_xor_sync(~0u, m, o), vo = __shfl_xor_sync(~0u, v, o);
    extra += __shfl_xor_sync(~0u, extra, o);
    const float d = mo - m;
    v = fmaf(d * d, 8.f * o, v + vo);
    m = 0.5f * (m + mo);
  }
  const float var = fmaf(v, 1.f / DM, 1e-5f);
  float rs = rsqrtf(var);
  rs = rs * fmaf(-0.5f * var * rs, rs, 1.5f);
#pragma unroll
  for (int i = 0; i < 16; i++) y[i] = round_bf16((x[i] - m) * rs);
}
__device__ __forceinline__ void warp_ln(const float (&x)[16], float (&y)[16]) { float e = 0.f; warp_ln(x, y, e); }
__device__ __forceinline__ void load_row(const bf16* p, int lane, uint2 (&r)[4]) {
#pragma unroll
  for (int q = 0; q < 4; q++) r[q] = ld_rlx64(p + q * 128 + lane * 4);
}
__device__ __forceinline__ void unpack_row(const uint2 (&r)[4], float (&x)[16]) {
#pragma unroll
  for (int q = 0; q < 4; q++) { x[4 * q] = bf_lo(r[q].x); x[4 * q + 1] = bf_hi(r[q].x); x[4 * q + 2] = bf_lo(r[q].y); x[4 * q + 3] = bf_hi(r[q].y); }
}
__device__ __forceinline__ void store_row(bf16* p, int lane, const float (&x)[16]) {
#pragma unroll
  for (int q = 0; q < 4; q++) *(uint2*)(p + q * 128 + lane * 4) = make_uint2(pack_bf16(x[4 * q], x[4 * q + 1]), pack_bf16(x[4 * q + 2], x[4 * q + 3]));
}
__device__ __forceinline__ void store_row_img(uint8_t* grp, int r, int lane, const float (&x)[16]) {
  uint8_t* p = grp + (lane >> 4) * 1024 + r * 128 + ((((lane & 15) >> 1) ^ r) << 4) + (lane & 1) * 8;
#pragma unroll
  for (int q = 0; q < 4; q++) *(uint2*)(p + q * 2048) = make_uint2(pack_bf16(x[4 * q], x[4 * q + 1]), pack_bf16(x[4 * q + 2], x[4 * q + 3]));
}

__global__ void __launch_bounds__(256) prep_kernel(const bf16* __restrict__ x0) {
  const int lane = threadIdx.x & 31, row = blockIdx.x * 8 + (threadIdx.x >> 5);
  uint2 r[4];
  float x[16], y[16];
  load_row(x0 + (size_t)row * DM, lane, r);
  const int gt = blockIdx.x * 256 + threadIdx.x, nt = gridDim.x * 256;
  uint4* M = (uint4*)g_M;
  for (int i = gt; i < 4 * 16384 / 4; i += nt) M[i] = make_uint4(~0u, ~0u, ~0u, ~0u);
  uint4* P = (uint4*)g_P;
  for (int i = gt; i < 96 * 4096 / 4; i += nt) P[i] = make_uint4(0, 0, 0, 0);
  uint4* F = (uint4*)&g_fl;
  for (int i = gt; i < (int)(sizeof(Flags) / 16); i += nt) F[i] = make_uint4(0, 0, 0, 0);
  unpack_row(r, x);
  warp_ln(x, y);
  store_row_img(g_xs[0] + (size_t)blockIdx.x * 8192, row & 7, lane, y);
}

constexpr int W_STRIDE = 272;
constexpr int C_WO = 0;
constexpr int C_X = 49152;
constexpr int C_M = C_X + 9 * 8192;
constexpr int C_Q = C_M + 24576;
constexpr int C_K = C_Q + 10240, C_V = C_K + 10240;
constexpr int C_SA = C_V + 10240, C_SB = C_SA + 8192, C_SP = C_SB + 8192;
constexpr int C_O = C_SP + 2048;
constexpr int C_OT = C_O + 6144;
constexpr int C_SC = C_OT + 8192;
constexpr int C_ST = C_SC + 2048;
constexpr int C_BAR = C_ST + 4096;
constexpr int C_SMEM = C_BAR + 256 + 1024 + TREXTRA;
static_assert(C_X + 512 * W_STRIDE <= C_BAR, "staging");
enum { B_M0 = 0, B_M1, B_M2, B_X, B_O, B_T, B_F, B_XL1, B_XL2, B_XL3, B_P1, B_P2, B_P3, B_OT, B_NUM };
constexpr int C_INFO = C_BAR + 128, C_POL = C_BAR + 160;
enum { NB_ALL = 0, NB_S, NB_TS, NB_PV, NB_W0, NB_TA };
constexpr uint32_t HI_X = desc_hi(8192, 1), HI_M = desc_hi(256, 0), HI_WO = desc_hi(1024, 1), HI_O = desc_hi(2048, 0);
constexpr float SCALE_LOG2E = 0.08838834764831845f * 1.4426950408889634f;
#define N2STEPS 10
#define GATE_P 450
#define GATE_PW 170
#define GATE_M 300

__device__ __forceinline__ uint32_t probe_polarity(uint32_t* p) {
  uint32_t best[2] = {~0u, ~0u};
#pragma unroll 1
  for (int rep = 0; rep < 4; rep++) {
#pragma unroll
    for (int pg = 0; pg < 2; pg++) {
      uint32_t t0, t1, v;
      asm volatile("mov.u32 %0, %%clock;" : "=r"(t0) :: "memory");
      asm volatile("atom.relaxed.gpu.global.add.u32 %0, [%1], 0;" : "=r"(v) : "l"(p + pg * 1024) : "memory");
      asm volatile("{ .reg .pred p; setp.ne.u32 p, %1, 0x13572468; mov.u32 %0, 0; @p mov.u32 %0, %%clock; }" : "=r"(t1) : "r"(v) : "memory");
      if (rep > 0) best[pg] = min(best[pg], t1 - t0);
    }
  }
  return best[1] < best[0] ? 1u : 0u;
}
__device__ __forceinline__ uint32_t ppage(uint32_t lp, uint32_t pol) { return lp ? 3 - pol : pol; }
__device__ __forceinline__ uint32_t and_x(uint32_t a, uint32_t b, uint32_t m) {
  uint32_t d; asm("lop3.b32 %0, %1, %2, %3, 0x42;" : "=r"(d) : "r"(a), "r"(b), "r"(m)); return d;
}
__device__ __forceinline__ uint32_t umax4(uint32_t m, uint4 v) { return __vimax3_u32(__vimax3_u32(m, v.x, v.y), v.z, v.w); }

__device__ __forceinline__ void load_wfrags(uint32_t (&wA)[32][4], uint32_t stage, int w, int lane) {
  const int mi = lane >> 3, r = lane & 7;
#pragma unroll
  for (int ks = 0; ks < 32; ks++) ldsm4t(wA[ks], stage + (ks * 16 + (mi >> 1) * 8 + r) * W_STRIDE + (w * 16 + (mi & 1) * 8) * 2);
}
template <int K0, int K1>
__device__ __forceinline__ void tok_part(float (&d)[16], const uint32_t (&wA)[32][4], uint32_t desc) {
#pragma unroll
  for (int ks = K0; ks < K1; ks++) {
    if (ks == 0) wg_rs32<0, 0, HI_X>(d, wA[ks], desc);
    else wg_rs32<0, 1, HI_X>(d, wA[ks], desc + (ks >> 2) * 64 + (ks & 3) * 2);
  }
}
template <int K0, int K1>
__device__ __forceinline__ void mem_part(float (&d)[12], const uint32_t (&wA)[32][4], uint32_t desc) {
#pragma unroll
  for (int ks = K0; ks < K1; ks++) {
    if (ks == 0) wg_rs24<1, 0, HI_M>(d, wA[ks], desc);
    else wg_rs24<1, 1, HI_M>(d, wA[ks], desc + ks * 48);
  }
}
__device__ __forceinline__ void tok_store(uint32_t dst, const float (&d)[16]) {
  stsm4(dst, pack_bf16(d[0], d[1]), pack_bf16(d[2], d[3]), pack_bf16(d[4], d[5]), pack_bf16(d[6], d[7]));
  stsm4(dst + 4096, pack_bf16(d[8], d[9]), pack_bf16(d[10], d[11]), pack_bf16(d[12], d[13]), pack_bf16(d[14], d[15]));
}

template <int T>
__device__ __forceinline__ void tok_pv(uint32_t sb, int c, int lane) {
  constexpr int NK = T ? 4 : 2;
  float p[NK + 1][4];
  {
    const uint4 v = lds128(sb + C_ST + (2 + T) * 512 + lane * 16);
    p[0][0] = __uint_as_float(v.x); p[0][1] = __uint_as_float(v.y); p[0][2] = __uint_as_float(v.z); p[0][3] = __uint_as_float(v.w);
  }
#pragma unroll
  for (int k = 0; k < NK; k++) {
    const uint4 v = lds128(sb + C_ST + (4 * T + k) * 512 + lane * 16);
    p[k + 1][0] = __uint_as_float(v.x); p[k + 1][1] = __uint_as_float(v.y); p[k + 1][2] = __uint_as_float(v.z); p[k + 1][3] = __uint_as_float(v.w);
  }
  const uint32_t va = sb + C_V + c * 512 + lane * 16;
  uint32_t vm[4], v0[4], v1[4];
  ldsm4(vm, va + 8192); ldsm4(v0, va); ldsm4(v1, va + 2048);
  const int row = lane >> 2, key = (lane & 3) * 2;
  if (key > row) { p[NK - 1][0] = -INFINITY; p[NK][2] = -INFINITY; }
  if (key + 1 > row) { p[NK - 1][1] = -INFINITY; p[NK][3] = -INFINITY; }
  p[NK][0] = p[NK][1] = -INFINITY;
  float mx0 = fmaxf(p[0][0], p[0][1]), mx1 = fmaxf(p[0][2], p[0][3]);
#pragma unroll
  for (int k = 1; k <= NK; k++) { mx0 = fmaxf(mx0, fmaxf(p[k][0], p[k][1])); mx1 = fmaxf(mx1, fmaxf(p[k][2], p[k][3])); }
  mx0 = fmaxf(mx0, __shfl_xor_sync(~0u, mx0, 1)); mx1 = fmaxf(mx1, __shfl_xor_sync(~0u, mx1, 1));
  mx0 = fmaxf(mx0, __shfl_xor_sync(~0u, mx0, 2)); mx1 = fmaxf(mx1, __shfl_xor_sync(~0u, mx1, 2));
  const float nb0 = -mx0 * SCALE_LOG2E, nb1 = -mx1 * SCALE_LOG2E;
  float l0 = 0.f, l1 = 0.f;
  uint32_t pa[NK + 1][2];
#pragma unroll
  for (int k = 0; k <= NK; k++) {
    p[k][0] = ex2_fast(fmaf(p[k][0], SCALE_LOG2E, nb0)); p[k][1] = ex2_fast(fmaf(p[k][1], SCALE_LOG2E, nb0));
    p[k][2] = ex2_fast(fmaf(p[k][2], SCALE_LOG2E, nb1)); p[k][3] = ex2_fast(fmaf(p[k][3], SCALE_LOG2E, nb1));
    l0 += p[k][0] + p[k][1]; l1 += p[k][2] + p[k][3];
    pa[k][0] = pack_bf16(p[k][0], p[k][1]); pa[k][1] = pack_bf16(p[k][2], p[k][3]);
  }
  float o[4][4];
#pragma unroll
  for (int j = 0; j < 4; j++) { o[j][0] = o[j][1] = o[j][2] = o[j][3] = 0.f; mma1688(o[j], pa[0][0], pa[0][1], vm[j]); }
#pragma unroll
  for (int j = 0; j < 4; j++) mma16816(o[j], pa[1][0], pa[1][1], pa[2][0], pa[2][1], v0[j], v1[j]);
  if (T) {
    ldsm4(v0, va + 4096); ldsm4(v1, va + 6144);
#pragma unroll
    for (int j = 0; j < 4; j++) mma16816(o[j], pa[NK - 1][0], pa[NK - 1][1], pa[NK][0], pa[NK][1], v0[j], v1[j]);
  }
  l0 += __shfl_xor_sync(~0u, l0, 1); l1 += __shfl_xor_sync(~0u, l1, 1);
  l0 += __shfl_xor_sync(~0u, l0, 2); l1 += __shfl_xor_sync(~0u, l1, 2);
  const float i0 = rcp_fast(l0), i1 = rcp_fast(l1);
  const uint32_t oa = sb + C_OT + T * 4096 + c * 512 + lane * 16;
  stsm4(oa, pack_bf16(o[0][0] * i0, o[0][1] * i0), pack_bf16(o[1][0] * i0, o[1][1] * i0), pack_bf16(o[2][0] * i0, o[2][1] * i0), pack_bf16(o[3][0] * i0, o[3][1] * i0));
  stsm4(oa + 2048, pack_bf16(o[0][2] * i1, o[0][3] * i1), pack_bf16(o[1][2] * i1, o[1][3] * i1), pack_bf16(o[2][2] * i1, o[2][3] * i1), pack_bf16(o[3][2] * i1, o[3][3] * i1));
}

#define TRC blockIdx.x
#define TRS (C_BAR + 256)
__device__ __forceinline__ void chain_proj(const uint32_t sb, const int w, const int lane, const uint32_t rank) {
  uint32_t wA[32][4];
  load_wfrags(wA, sb + C_X, w, lane);
  bar_sync(NB_ALL, 512);
  bar_sync(NB_ALL, 512);
  cluster_sync();
  const uint32_t bars = sb + C_BAR;
  const int mi = lane >> 3;
  const uint32_t stm = (mi >> 1) * 2048 + (2 * w + (mi & 1)) * 128 + (lane & 7) * 16;
  const uint32_t own = sb + C_Q + rank * 10240;
  const uint32_t dX1 = desc_lo(sb + C_X, 16), dX2 = dX1 + 2048, dX3 = dX1 + 4096;
  const uint32_t dM = desc_lo(sb + C_M, 128);
  const int jt = w >= 3, jk = w >= 4 ? w - 4 : (w >= 2 ? 4 : w);
  uint32_t npatch = 0;
#pragma unroll 1
  for (int st = 0; st < NSTEP; st++) {
    uint32_t info = 0;
    {
      float a2[16], a1[16];
      if (st > 0) bar_sync(NB_PV, 384);
      TR(0)
      if (st >= DELTA) { mbar_wait(bars + B_XL2 * 8, (st - DELTA) & 1, 30); info = lds32(sb + C_INFO + (st & 1) * 4); }
      wg_fence();
      tok_part<0, N2STEPS>(a2, wA, dX2);
      wg_commit();
      TR(1)
      if (st > 0) bar_sync(NB_W0, 384);
      TR(2)
      tok_part<N2STEPS, 32>(a2, wA, dX2);
      wg_commit();
      if (st < NSEG) mbar_wait(bars + B_XL1 * 8, st & 1, 31);
      tok_part<0, 4>(a1, wA, dX1);
      wg_commit();
      wg_wait<1>();
      acc_fence(a2);
      TR(3)
      tok_store((rank == 0 ? sb + C_SA : own) + stm, a2);
      if (rank == 2) tok_store(sb + C_SB + stm, a2);
      fence_async_smem();
      __syncwarp();
      if (lane == 0 && st >= DELTA) mbar_arrive(bars + B_P1 * 8);
      TR(4)
      tok_part<4, 32>(a1, wA, dX1);
      wg_commit();
      wg_wait<0>();
      acc_fence(a1);
      TR(5)
      tok_store((rank == 0 ? own : sb + C_SA) + stm, a1);
      fence_async_smem();
      __syncwarp();
      if (lane == 0 && st < NSEG) mbar_arrive(bars + B_P2 * 8);
    }
    if (info & 4) {
      float a3[4];
      mbar_wait(bars + B_XL3 * 8, npatch & 1, 32);
      npatch++;
      wg_fence();
#pragma unroll
      for (int ks = 0; ks < 32; ks++) {
        if (ks == 0) wg_rs8<0, 0, HI_X>(a3, wA[ks], dX3);
        else wg_rs8<0, 1, HI_X>(a3, wA[ks], dX3 + (ks >> 2) * 64 + (ks & 3) * 2);
      }
      wg_commit();
      wg_wait<0>();
      acc_fence(a3);
      const uint32_t dst = (rank == 2 ? own + (info & 3) * 2048 : sb + C_SP) + w * 256 + lane * 4;
      sts32(dst, pack_bf16(a3[0], a3[1])); sts32(dst + 128, pack_bf16(a3[2], a3[3]));
      fence_async_smem();
      __syncwarp();
      if (lane == 0) mbar_arrive(bars + B_P3 * 8);
    }
    TR(6)
    {
      float am[12];
      mbar_wait(bars + B_M0 * 8, st & 1, 33);
      TR(7)
      fence_async_smem();
      wg_fence();
      mem_part<0, 10>(am, wA, dM);
      wg_commit();
      mbar_wait(bars + B_M1 * 8, st & 1, 34);
      fence_async_smem();
      mem_part<10, 24>(am, wA, dM);
      wg_commit();
      mbar_wait(bars + B_M2 * 8, st & 1, 35);
      fence_async_smem();
      mem_part<24, 32>(am, wA, dM);
      wg_commit();
      wg_wait<0>();
      acc_fence(am);
      TR(8)
      uint32_t x[3][2];
#pragma unroll
      for (int j = 0; j < 3; j++) { x[j][0] = pack_bf16(am[4 * j], am[4 * j + 1]); x[j][1] = pack_bf16(am[4 * j + 2], am[4 * j + 3]); }
      if (info & 4) { x[2][0] = x[1][0]; x[2][1] = x[1][1]; }
      const uint32_t xa = own + 8192 + w * 256 + lane * 4;
#pragma unroll
      for (int j = 0; j < 3; j++) {
        if (rank != j) {
          const uint32_t ra = mapa_u32(xa, j), rb = mapa_u32(bars + B_X * 8, j);
          st_async32(ra, x[j][0], rb); st_async32(ra + 128, x[j][1], rb);
        } else {
          sts32(xa, x[j][0]); sts32(xa + 128, x[j][1]);
        }
      }
      __syncwarp();
      if (lane == 0) mbar_arrive(bars + B_X * 8);
    }
    TR(9)
    {
      bar_sync(NB_TS, 256);
      mbar_wait(bars + B_T * 8, st & 1, 36);
      if (jk == 4) mbar_wait(bars + B_X * 8, st & 1, 37);
      TR(10)
      float s0[4] = {0.f, 0.f, 0.f, 0.f}, s1[4] = {0.f, 0.f, 0.f, 0.f};
      const uint32_t qa = sb + C_Q + (2 * jt + (mi & 1)) * 2048 + (mi >> 1) * 128 + (lane & 7) * 16;
      const uint32_t ka = sb + C_K + jk * 2048 + lane * 16;
#pragma unroll
      for (int i = 0; i < 4; i++) {
        uint32_t q0[4], q1[4], kf[4];
        ldsm4t(q0, qa + i * 512); ldsm4t(kf, ka + i * 512); ldsm4t(q1, qa + i * 512 + 256);
        mma16816(s0, q0[0], q0[1], q0[2], q0[3], kf[0], kf[1]);
        mma16816(s1, q1[0], q1[1], q1[2], q1[3], kf[2], kf[3]);
      }
      sts128(sb + C_ST + w * 512 + lane * 16, make_uint4(__float_as_uint(s0[0] + s1[0]), __float_as_uint(s0[1] + s1[1]),
                                                         __float_as_uint(s0[2] + s1[2]), __float_as_uint(s0[3] + s1[3])));
      if (jk != 4) mbar_wait(bars + B_X * 8, st & 1, 37);
      bar_sync(NB_TS, 256);
      TR(11)
      if (w < 4) tok_pv<0>(sb, w & 3, lane); else tok_pv<1>(sb, w & 3, lane);
      fence_async_smem();
      __syncwarp();
      if (lane == 0) mbar_arrive(bars + B_OT * 8);
      if (st < NSTEP - 1) bar_arrive(NB_TA, 384);
      TR(12)
    }
  }
}

__device__ __forceinline__ void chain_mem(const uint32_t sb, const int w, const int lane, const uint32_t rank, const int h,
                                          const bf16* __restrict__ mem0) {
  const int c = w - 8, t = c * 32 + lane, b = blockIdx.x;
  const uint32_t bars = sb + C_BAR;
  uint32_t pgbits = 0;
  {
    uint32_t pol = 1;
    const int tl = lane / 3, u = ((tl * 3 + rank) * 4 + c) * 3 + (lane - tl * 3);
    if (lane < 9 && u < 96) {
      int it = 0;
      while ((pol = ld_rlx32(&g_fl.pol[u])) == 0) give_up(++it, SPIN_LIMIT, 40);
    }
    pgbits = __reduce_or_sync(~0u, lane < 9 ? ppage(h >> 4, (pol - 1) & 1) << (2 * lane) : 0u);
  }
  const int wi = ((lane >> 4) & 1) * 2 + ((lane >> 3) & 1);
  uint32_t m0word;
  {
    const unsigned short* mp = (const unsigned short*)mem0 + 2 * wi * DM + h * 16 + c * 4 + (lane & 3);
    m0word = (uint32_t)mp[0] | (uint32_t)mp[DM] << 16;
  }
  bar_sync(NB_ALL, 512);
  for (int i = t; i < 2048; i += 128) {
    const unsigned short* mp = (const unsigned short*)mem0 + 2 * (i & 3) * DM + (i >> 2);
    const uint32_t v = (uint32_t)mp[0] | (uint32_t)mp[DM] << 16;
    const uint32_t a = sb + C_M + (i >> 6) * 768 + (i & 63) * 4;
    sts32(a, v); sts32(a + 256, v); sts32(a + 512, v);
  }
  fence_async_smem();
  __syncwarp();
  if (lane == 0) { mbar_arrive(bars + B_M0 * 8); mbar_arrive(bars + B_M1 * 8); mbar_arrive(bars + B_M2 * 8); }
  if (t == 0) { mbar_expect_tx(bars + B_X * 8, 4096); mbar_expect_tx(bars + B_O * 8, 4096); }
  bar_sync(NB_ALL, 512);
  cluster_sync();

  const int mi = lane >> 3;
  const uint32_t l16 = lane * 16;
  const uint32_t kperm = (((mi & 1) << 1) | (mi >> 1)) * 128 + (lane & 7) * 16;
  const uint32_t vq = sb + C_V + (mi >> 1) * 2048 + (4 * c + (mi & 1)) * 128 + (lane & 7) * 16;
  const uint32_t r1 = rank == 2 ? 0 : rank + 1, r2 = rank == 0 ? 2 : rank - 1;
  const uint32_t oa = sb + C_O + rank * 2048 + c * 512 + lane * 4;
  const uint32_t dWo = desc_lo(sb + C_WO, 8192), dO = desc_lo(sb + C_O, 128);
  uint8_t* Pw = (uint8_t*)g_P + (rank * 4 + c) * 3 * 16384 + (h & 15) * 256 + lane * 4;
  const uint32_t polP = lds32(sb + C_POL + 16);
  const uint8_t* Pr0 = (const uint8_t*)g_P + b * 16384 + (lane >> 2) * 256 + c * 64 + (lane & 3) * 16 + ppage(0, polP) * 4096;
  const uint8_t* Pr1 = Pr0 + (3 - 2 * polP) * 4096;
  uint8_t* Mw = (uint8_t*)g_M + (b >> 5) * 16384 + ppage((b >> 4) & 1, (lane >> 2) & 1) * 4096 + (b & 15) * 256 + c * 64 + (lane & 3) * 16 + wi * 4;
  uint32_t mpol = 0;
#pragma unroll
  for (int k = 0; k < 4; k++) mpol |= lds32(sb + C_POL + k * 4) << k;
  const uint32_t wave = h >= 24 ? 2 : h >= 12 ? 1 : 0;

#pragma unroll 1
  for (int st = 0; st < NSTEP - 1; st++) {
    mbar_wait(bars + B_X * 8, st & 1, 41);
    mbar_wait(bars + B_T * 8, st & 1, 42);
    TR(0)
    {
      float sa[2][4], sc[2][4], ma[4], mc[4];
#pragma unroll
      for (int i = 0; i < 4; i++) sa[0][i] = sa[1][i] = sc[0][i] = sc[1][i] = ma[i] = mc[i] = 0.f;
      uint32_t qf[4][4], kf[4][4], km[4];
#pragma unroll
      for (int i = 0; i < 4; i++) {
        const uint32_t o = ((i + c) & 3) * 512;
        ldsm4t(qf[i], sb + C_Q + 8192 + o + l16);
        ldsm4t(kf[i], sb + C_K + c * 2048 + o + kperm);
        if (i == 0) ldsm4t(km, sb + C_K + 8192 + o + kperm);
      }
      mma16816(ma, qf[0][0], qf[0][1], qf[0][2], qf[0][3], km[0], km[1]);
      mma16816(mc, qf[0][0], qf[0][1], qf[0][2], qf[0][3], km[2], km[3]);
#pragma unroll
      for (int i = 0; i < 4; i++) {
        mma16816(sa[i & 1], qf[i][0], qf[i][1], qf[i][2], qf[i][3], kf[i][0], kf[i][1]);
        mma16816(sc[i & 1], qf[i][0], qf[i][1], qf[i][2], qf[i][3], kf[i][2], kf[i][3]);
      }
      sts128(sb + C_SC + c * 512 + l16,
             make_uint4(__float_as_uint((sa[0][0] + sa[1][0]) + (sc[0][2] + sc[1][2])), __float_as_uint((sa[0][1] + sa[1][1]) + (sc[0][3] + sc[1][3])),
                        __float_as_uint(ma[0] + mc[2]), __float_as_uint(ma[1] + mc[3])));
    }
    uint32_t vm[4], vx[4][4];
    ldsm4(vm, sb + C_V + 8192 + c * 512 + l16);
#pragma unroll
    for (int i = 0; i < 4; i++) ldsm4(vx[i], vq + (i >> 1) * 4096 + (i & 1) * 256);
    bar_sync(NB_S, 128);
    TR(1)
    {
      float p[10];
      const uint4 s0 = lds128(sb + C_SC + l16), s1 = lds128(sb + C_SC + 512 + l16), s2 = lds128(sb + C_SC + 1024 + l16), s3 = lds128(sb + C_SC + 1536 + l16);
      p[0] = (__uint_as_float(s0.z) + __uint_as_float(s1.z)) + (__uint_as_float(s2.z) + __uint_as_float(s3.z));
      p[1] = (__uint_as_float(s0.w) + __uint_as_float(s1.w)) + (__uint_as_float(s2.w) + __uint_as_float(s3.w));
      p[2] = __uint_as_float(s0.x); p[3] = __uint_as_float(s0.y); p[4] = __uint_as_float(s1.x); p[5] = __uint_as_float(s1.y);
      p[6] = __uint_as_float(s2.x); p[7] = __uint_as_float(s2.y); p[8] = __uint_as_float(s3.x); p[9] = __uint_as_float(s3.y);
      float mx = fmaxf(fmaxf(fmaxf(p[2], p[3]), fmaxf(p[4], p[5])), fmaxf(fmaxf(p[6], p[7]), fmaxf(p[8], p[9])));
      mx = fmaxf(mx, fmaxf(p[0], p[1]));
      mx = fmaxf(mx, __shfl_xor_sync(~0u, mx, 1));
      mx = fmaxf(mx, __shfl_xor_sync(~0u, mx, 2));
      const float nb = -mx * SCALE_LOG2E;
#pragma unroll
      for (int k = 0; k < 10; k++) p[k] = ex2_fast(fmaf(p[k], SCALE_LOG2E, nb));
      const uint32_t pm = pack_bf16(p[0], p[1]), p0 = pack_bf16(p[2], p[3]), p1 = pack_bf16(p[4], p[5]),
                     p2 = pack_bf16(p[6], p[7]), p3 = pack_bf16(p[8], p[9]);
      float o0[4] = {0.f, 0.f, 0.f, 0.f}, o1[4] = {0.f, 0.f, 0.f, 0.f}, o2[4] = {0.f, 0.f, 0.f, 0.f}, o3[4] = {0.f, 0.f, 0.f, 0.f};
      float la[4] = {0.f, 0.f, 0.f, 0.f}, lb[4] = {0.f, 0.f, 0.f, 0.f};
      const uint32_t one = 0x3f803f80u;
      mma16816(la, one, one, one, one, p0, p1);
      mma16816(lb, one, one, one, one, p2, p3);
      mma16816(o0, vx[0][0], vx[0][1], vx[0][2], vx[0][3], p0, p1);
      mma16816(o1, vx[1][0], vx[1][1], vx[1][2], vx[1][3], p0, p1);
      mma16816(o2, vx[2][0], vx[2][1], vx[2][2], vx[2][3], p2, p3);
      mma16816(o3, vx[3][0], vx[3][1], vx[3][2], vx[3][3], p2, p3);
      mma1688(la, one, one, pm);
      mma1688(o0, vm[0], vm[1], pm);
      mma1688(o1, vm[2], vm[3], pm);
      const float i0 = rcp_fast(la[0] + lb[0]), i1 = rcp_fast(la[1] + lb[1]);
      const uint32_t e0 = pack_bf16((o0[0] + o2[0]) * i0, (o0[1] + o2[1]) * i1), e1 = pack_bf16((o0[2] + o2[2]) * i0, (o0[3] + o2[3]) * i1);
      const uint32_t e2 = pack_bf16((o1[0] + o3[0]) * i0, (o1[1] + o3[1]) * i1), e3 = pack_bf16((o1[2] + o3[2]) * i0, (o1[3] + o3[3]) * i1);
      const uint32_t a1 = mapa_u32(oa, r1), b1 = mapa_u32(bars + B_O * 8, r1), a2 = mapa_u32(oa, r2), b2 = mapa_u32(bars + B_O * 8, r2);
      st_async32(a1, e0, b1); st_async32(a2, e0, b2); st_async32(a1 + 128, e1, b1); st_async32(a2 + 128, e1, b2);
      st_async32(a1 + 256, e2, b1); st_async32(a2 + 256, e2, b2); st_async32(a1 + 384, e3, b1); st_async32(a2 + 384, e3, b2);
      bar_arrive(NB_PV, 384);
      sts32(oa, e0); sts32(oa + 128, e1); sts32(oa + 256, e2); sts32(oa + 384, e3);
      __syncwarp();
      if (lane == 0) mbar_arrive(bars + B_O * 8);
      if (t == 0) mbar_expect_tx(bars + B_X * 8, 4096);
    }
    TR(2)
    uint32_t tp;
    {
      const uint32_t tag = (st & 1) ^ 1;
      float oc0[12], oc1[12], oc2[12];
      mbar_wait(bars + B_O * 8, st & 1, 43);
      fence_async_smem();
      TR(3)
      wg_fence();
#pragma unroll
      for (int i = 0; i < 8; i++) { if (i == 0) wg_ss24<0, HI_WO, HI_O>(oc0, dWo, dO); else wg_ss24<1, HI_WO, HI_O>(oc0, dWo + i * 128, dO + i * 16); }
      wg_commit();
#pragma unroll
      for (int i = 0; i < 8; i++) { if (i == 0) wg_ss24<0, HI_WO, HI_O>(oc1, dWo + 1024, dO); else wg_ss24<1, HI_WO, HI_O>(oc1, dWo + 1024 + i * 128, dO + i * 16); }
      wg_commit();
      auto put = [&](const float (&oc)[12], int tl) {
#pragma unroll
        for (int j = 0; j < 3; j++) {
          uint8_t* p = Pw + (tl * 36 + j) * 16384 + ((pgbits >> (2 * (tl * 3 + j))) & 3) * 4096;
          st_rlx32(p, (pack_bf16(oc[4 * j], oc[4 * j + 1]) & ~1u) | tag);
          st_rlx32(p + 128, (pack_bf16(oc[4 * j + 2], oc[4 * j + 3]) & ~1u) | tag);
        }
      };
      wg_wait<1>();
      acc_fence(oc0);
      put(oc0, 0);
      tp = clk32();
      bar_arrive(NB_W0, 384);
      TR(4)
#pragma unroll
      for (int i = 0; i < 8; i++) { if (i == 0) wg_ss24<0, HI_WO, HI_O>(oc2, dWo + 2048, dO); else wg_ss24<1, HI_WO, HI_O>(oc2, dWo + 2048 + i * 128, dO + i * 16); }
      wg_commit();
      wg_wait<1>();
      acc_fence(oc1);
      put(oc1, 1);
      TR(5)
      wg_wait<0>();
      acc_fence(oc2);
      if (rank != 2) put(oc2, 2);
      TR(6)
    }
    bar_sync(NB_TA, 384);
    if (t == 0) {
      mbar_arrive_remote(mapa_u32(bars + B_F * 8, r1)); mbar_arrive_remote(mapa_u32(bars + B_F * 8, r2));
      mbar_expect_tx(bars + B_O * 8, 4096);
    }
    const int sn = (st + 1) & 3;
    {
      const uint32_t flip = (st & 1) ? ~0u : 0u;
      spin_until(tp, GATE_P + wave * GATE_PW);
      TR(7)
      uint4 q0, q1, q2, q3;
      int it = 0;
      while (true) {
        q0 = ld_rlx128(Pr0); q1 = ld_rlx128(Pr0 + 2048); q2 = ld_rlx128(Pr1); q3 = ld_rlx128(Pr1 + 2048);
        const uint32_t ok = and_x(q0.x, q0.y, flip) & and_x(q0.z, q0.w, flip) & and_x(q1.x, q1.y, flip) & and_x(q1.z, q1.w, flip) &
                            and_x(q2.x, q2.y, flip) & and_x(q2.z, q2.w, flip) & and_x(q3.x, q3.y, flip) & and_x(q3.z, q3.w, flip) & 1u;
        if (__all_sync(~0u, ok != 0)) break;
        give_up(++it, SPIN_LIMIT, 44);
      }
      TR(8)
      TRV(14, it)
      float r[8];
      r[0] = (bf_lo(q0.x) + bf_lo(q1.x)) + (bf_lo(q2.x) + bf_lo(q3.x)); r[1] = (bf_hi(q0.x) + bf_hi(q1.x)) + (bf_hi(q2.x) + bf_hi(q3.x));
      r[2] = (bf_lo(q0.y) + bf_lo(q1.y)) + (bf_lo(q2.y) + bf_lo(q3.y)); r[3] = (bf_hi(q0.y) + bf_hi(q1.y)) + (bf_hi(q2.y) + bf_hi(q3.y));
      r[4] = (bf_lo(q0.z) + bf_lo(q1.z)) + (bf_lo(q2.z) + bf_lo(q3.z)); r[5] = (bf_hi(q0.z) + bf_hi(q1.z)) + (bf_hi(q2.z) + bf_hi(q3.z));
      r[6] = (bf_lo(q0.w) + bf_lo(q1.w)) + (bf_lo(q2.w) + bf_lo(q3.w)); r[7] = (bf_hi(q0.w) + bf_hi(q1.w)) + (bf_hi(q2.w) + bf_hi(q3.w));
      const bool u16 = lane & 16, u8 = lane & 8;
      float k4[4], k2[2];
#pragma unroll
      for (int i = 0; i < 4; i++) k4[i] = (u16 ? r[4 + i] : r[i]) + __shfl_xor_sync(~0u, u16 ? r[i] : r[4 + i], 16);
#pragma unroll
      for (int i = 0; i < 2; i++) k2[i] = (u8 ? k4[2 + i] : k4[i]) + __shfl_xor_sync(~0u, u8 ? k4[i] : k4[2 + i], 8);
      k2[0] += __shfl_xor_sync(~0u, k2[0], 4); k2[1] += __shfl_xor_sync(~0u, k2[1], 4);
      uint32_t mword = pack_bf16(k2[0], k2[1]);
      if (rank != 0 && st < DELTA) mword = m0word;
      st_rlx32(Mw + sn * 65536, mword);
    }
    TR(9)
    {
      const uint32_t tm = clk32();
      const uint32_t pol = (mpol >> sn) & 1;
      const uint8_t* M0 = (const uint8_t*)g_M + sn * 65536 + t * 16 + pol * 4096;
      const uint8_t* M1 = M0 + (3 - 2 * pol) * 4096;
      const uint32_t ms = sb + C_M + t * 16;
      if (GATE_M > (int)(wave * GATE_PW)) spin_until(tm, GATE_M - wave * GATE_PW);
      TR(10)
      uint4 v0, v1, v2, v3, v4;
      int it = 0;
      while (true) {
        v0 = ld_rlx128(M0); v1 = ld_rlx128(M0 + 2048); v2 = ld_rlx128(M1); v3 = ld_rlx128(M1 + 2048);
        if (__all_sync(~0u, umax4(umax4(umax4(umax4(0, v0), v1), v2), v3) != ~0u)) break;
        give_up(++it, SPIN_LIMIT, 45);
      }
      uint4 u0 = ld_rlx128(M0 + 16384), u1 = ld_rlx128(M0 + 18432), u2 = ld_rlx128(M1 + 16384), u3 = ld_rlx128(M1 + 18432), u4 = ld_rlx128(M0 + 32768);
      sts128(ms, v0); sts128(ms + 2048, v1); sts128(ms + 4096, v2); sts128(ms + 6144, v3);
      __syncwarp();
      if (lane == 0) mbar_arrive(bars + B_M0 * 8);
      TR(11)
      v0 = ld_rlx128(M0 + 34816); v1 = ld_rlx128(M1 + 32768); v2 = ld_rlx128(M1 + 34816);
      while (!__all_sync(~0u, umax4(umax4(umax4(umax4(umax4(0, u0), u1), u2), u3), u4) != ~0u)) {
        give_up(++it, SPIN_LIMIT, 46);
        u0 = ld_rlx128(M0 + 16384); u1 = ld_rlx128(M0 + 18432); u2 = ld_rlx128(M1 + 16384); u3 = ld_rlx128(M1 + 18432); u4 = ld_rlx128(M0 + 32768);
      }
      sts128(ms + 8192, u0); sts128(ms + 10240, u1); sts128(ms + 12288, u2); sts128(ms + 14336, u3); sts128(ms + 16384, u4);
      __syncwarp();
      if (lane == 0) mbar_arrive(bars + B_M1 * 8);
      TR(12)
      while (!__all_sync(~0u, umax4(umax4(umax4(0, v0), v1), v2) != ~0u)) {
        give_up(++it, SPIN_LIMIT, 47);
        v0 = ld_rlx128(M0 + 34816); v1 = ld_rlx128(M1 + 32768); v2 = ld_rlx128(M1 + 34816);
      }
      sts128(ms + 18432, v0); sts128(ms + 20480, v1); sts128(ms + 22528, v2);
      __syncwarp();
      if (lane == 0) mbar_arrive(bars + B_M2 * 8);
      (void)v4;
      TR(13)
      TRV(15, it)
      st_rlx32(Mw + (st & 3) * 65536, ~0u);
    }
  }
}

__device__ __forceinline__ void chain_dma(const uint32_t sb, const int w, const int lane, const uint32_t rank, const int h) {
  const uint32_t bars = sb + C_BAR;
  bar_sync(NB_ALL, 512);
  bar_sync(NB_ALL, 512);
  cluster_sync();
  if (w == 12) {
    u64 best = 0;
    uint32_t npatch = 0;
#pragma unroll 1
    for (int st = 0; st < NSTEP; st++) {
      bool rec = false;
      if (st >= DELTA) {
        const int sg = st - DELTA;
        mbar_gate(bars + B_M2 * 8, (st - 1) & 1);
        const u64 k = wait_keys(g_fl.key[0][sg], lane, 50);
        rec = k > best;
        if (rec) best = k;
        TR(0)
        if (sg > 0) mbar_wait(bars + B_P1 * 8, (sg - 1) & 1, 51);
        if (lane == 0) {
          sts32(sb + C_INFO + (st & 1) * 4, rec ? 4 | ((key_token(k) >> 3) & 3) : 0);
          fence_async_glb();
          mbar_expect_tx(bars + B_XL2 * 8, 32768);
          bulk_g2s(sb + C_X + 32768, g_xs[1] + (size_t)sg * 32768, 32768, bars + B_XL2 * 8);
        }
        __syncwarp();
        TR(1)
      }
      if (st < NSEG) {
        if (st > 0) { mbar_wait(bars + B_P2 * 8, (st - 1) & 1, 53); mbar_wait(bars + B_O * 8, (st - 1) & 1, 54); }
        if (lane == 0) {
          mbar_expect_tx(bars + B_XL1 * 8, 32768);
          bulk_g2s(sb + C_X, g_xs[0] + (size_t)st * 32768, 32768, bars + B_XL1 * 8);
        }
        __syncwarp();
      }
      if (rec) {
        if (npatch > 0) mbar_wait(bars + B_P3 * 8, (npatch - 1) & 1, 55);
        npatch++;
        wait_count(g_fl.patch[st - DELTA], 1, 56);
        if (lane == 0) {
          fence_async_glb();
          mbar_expect_tx(bars + B_XL3 * 8, 8192);
          bulk_g2s(sb + C_X + 65536, g_patch + (size_t)(st - DELTA) * 8192, 8192, bars + B_XL3 * 8);
        }
        __syncwarp();
      }
    }
  } else if (w == 13) {
    const uint32_t own = sb + C_Q + rank * 10240, bt = bars + B_T * 8;
    uint32_t npatch = 0;
#pragma unroll 1
    for (int st = 0; st < NSTEP; st++) {
      if (st > 0) mbar_wait(bars + B_F * 8, (st - 1) & 1, 60);
      uint32_t info = 0;
      if (st >= DELTA) {
        mbar_wait(bars + B_P1 * 8, (st - DELTA) & 1, 61);
        info = lds32(sb + C_INFO + (st & 1) * 4);
        TR(0)
        const uint32_t src = rank == 0 ? sb + C_SA : rank == 1 ? own : sb + C_SB;
        if (lane == 0) {
#pragma unroll 1
          for (uint32_t g = 0; g < 4; g++) {
            if (rank != 1) bulk_s2r(mapa_u32(own + g * 2048, 1), src + g * 2048, 2048, mapa_u32(bt, 1));
            if (rank != 2 && info != (4 | g)) bulk_s2r(mapa_u32(own + g * 2048, 2), src + g * 2048, 2048, mapa_u32(bt, 2));
          }
        }
        __syncwarp();
        TR(1)
      }
      if (st < NSEG) {
        mbar_wait(bars + B_P2 * 8, st & 1, 62);
        TR(2)
        if (rank != 0 && lane == 0) {
#pragma unroll 1
          for (uint32_t g = 0; g < 4; g++) bulk_s2r(mapa_u32(own + g * 2048, 0), sb + C_SA + g * 2048, 2048, mapa_u32(bt, 0));
        }
        __syncwarp();
        TR(3)
      }
      if (info & 4) {
        mbar_wait(bars + B_P3 * 8, npatch & 1, 63);
        npatch++;
        if (rank != 2 && lane == 0) bulk_s2r(mapa_u32(own + (info & 3) * 2048, 2), sb + C_SP, 2048, mapa_u32(bt, 2));
        __syncwarp();
      }
    }
  } else if (w == 14) {
    const int s0 = rank == 0 ? 0 : DELTA;
    if (lane == 0) mbar_expect_tx(bars + B_T * 8, s0 == 0 ? 16384 : 0);
    __syncwarp();
#pragma unroll 1
    for (int st = 0; st < NSTEP; st++) {
      const int sg = st - s0;
      mbar_wait(bars + B_OT * 8, st & 1, 70);
      if (st < NSTEP - 1) mbar_wait(bars + B_F * 8, st & 1, 71);
      TR(0)
      if (lane == 0) {
        if ((unsigned)sg < (unsigned)NSEG) {
          uint8_t* dst = g_O[rank] + ((size_t)(sg & (OSLOTS - 1)) * 32 + h) * 8192;
#pragma unroll 1
          for (int g = 0; g < 4; g++) bulk_s2g(dst + g * 2048, sb + C_OT + g * 2048, 2048);
          asm volatile("cp.async.bulk.commit_group;" ::: "memory");
          asm volatile("cp.async.bulk.wait_group 0;" ::: "memory");
        }
        mbar_expect_tx(bars + B_T * 8, (unsigned)(sg + 1) < (unsigned)NSEG ? 16384 : 0);
        if ((unsigned)sg < (unsigned)NSEG) red_release(&g_fl.oflag[rank][sg][h >> 2]);
      }
      __syncwarp();
      TR(1)
    }
  }
}

__global__ void __cluster_dims__(3, 1, 1) __launch_bounds__(512, 1)
chain_kernel(const bf16* __restrict__ Wq, const bf16* __restrict__ Wk, const bf16* __restrict__ Wv,
             const bf16* __restrict__ Wo, const bf16* __restrict__ mem0) {
  extern __shared__ __align__(1024) uint8_t smem_raw[];
  const uint32_t sb = (smem_u32(smem_raw) + 1023) & ~1023u;
  const int tid = threadIdx.x, lane = tid & 31;
  const int w = __shfl_sync(~0u, tid >> 5, 0);
  uint32_t rank;
  asm volatile("mov.u32 %0, %%cluster_ctarank;" : "=r"(rank));
  const int h = blockIdx.x / 3;
  asm volatile("griddepcontrol.launch_dependents;" ::: "memory");
  TG(0)
  if (tid == 0) {
    const uint32_t bars = sb + C_BAR;
    mbar_init(bars + B_M0 * 8, 4); mbar_init(bars + B_M1 * 8, 4); mbar_init(bars + B_M2 * 8, 4);
    mbar_init(bars + B_X * 8, 9); mbar_init(bars + B_O * 8, 5); mbar_init(bars + B_T * 8, 1); mbar_init(bars + B_F * 8, 2);
    mbar_init(bars + B_XL1 * 8, 1); mbar_init(bars + B_XL2 * 8, 1); mbar_init(bars + B_XL3 * 8, 1);
    mbar_init(bars + B_P1 * 8, 8); mbar_init(bars + B_P2 * 8, 8); mbar_init(bars + B_P3 * 8, 8); mbar_init(bars + B_OT * 8, 8);
    asm volatile("fence.mbarrier_init.release.cluster;" ::: "memory");
  }
  {
    const bf16* W1 = (rank == 0 ? Wq : rank == 1 ? Wk : Wv) + h * 128;
#pragma unroll 4
    for (int cidx = tid; cidx < 512 * 16; cidx += 512) {
      const int d = cidx >> 4, q = cidx & 15;
      cp16(sb + C_X + d * W_STRIDE + q * 16, W1 + (size_t)d * HD + q * 8);
    }
    const int nt = rank == 2 ? 2 : 3;
    for (int cidx = tid; cidx < nt * 1024; cidx += 512) {
      const int tl = cidx >> 10, e = (cidx >> 3) & 127, q = cidx & 7;
      cp16(sb + C_WO + tl * 16384 + e * 128 + ((q ^ (e & 7)) << 4), Wo + (size_t)(h * 128 + e) * DM + (tl * 3 + rank) * 64 + q * 8);
    }
    asm volatile("cp.async.commit_group;" ::: "memory");
    if (lane == 0) {
      if (w < 4) sts32(sb + C_POL + w * 4, probe_polarity(g_M + w * 16384 + 3 * 4096 + (blockIdx.x & 31) * 32));
      else if (w == 4) {
        const uint32_t pol = probe_polarity(g_P + blockIdx.x * 4096);
        sts32(sb + C_POL + 16, pol);
        st_rlx32(&g_fl.pol[blockIdx.x], pol + 1);
      }
    }
    asm volatile("cp.async.wait_group 0;" ::: "memory");
    fence_async_smem();
    __syncthreads();
  }
  if (w < 8) {
    reg_inc<192>();
    chain_proj(sb, w, lane, rank);
    TG(1)
    TRDUMP
    cluster_sync();
  } else if (w < 12) {
    reg_dec<104>();
    chain_mem(sb, w, lane, rank, h, mem0);
    TRDUMP
    cluster_sync();
  } else {
    reg_dec<24>();
    chain_dma(sb, w, lane, rank, h);
    TRDUMP
    if (w != 15) cluster_sync();
  }
}
#undef TRC
#undef TRS

constexpr int K_O = 0;
constexpr int K_IN = 98304;
constexpr int K_FFN = K_IN + 49152;
constexpr int K_BAR = K_FFN + 8192;
constexpr int K_SMEM = K_BAR + 256 + 1024 + TREXTRA;
static_assert(512 * W_STRIDE <= K_FFN, "staging");
enum { KB_FULL = 0, KB_EMPTY = 3, KB_IN = 6, KB_OK = 9 };
#define GATE_R 300
struct WorkerParams {
  const bf16 *x0, *Wo, *w_r, *w_gate, *w_up, *w_down;
  bf16* out;
};
#define TRC (96 + blockIdx.x)
#define TRS (K_BAR + 256)

template <int N> __device__ __forceinline__ void halve(float (&g)[16], int lane) {
  const bool up = lane & (2 * N);
#pragma unroll
  for (int i = 0; i < N; i++) g[i] = (up ? g[N + i] : g[i]) + __shfl_xor_sync(~0u, up ? g[i] : g[N + i], 2 * N);
}
__device__ __forceinline__ void ffn_slice(const WorkerParams& prm, uint32_t sf, int t, const bf16* yrow, int ev) {
  const int lane = t & 31, c = t >> 5, cta = blockIdx.x;
  const int nu = cta < 32 ? 3 : 4, j0 = cta < 32 ? cta * 48 : 1536 + (cta - 32) * 64;
  const uint32_t sy = sf, sr = sf + 2048, sh = sf + 4096, sd = sf + 4608;
  {
    const uint2 v = ld_rlx64(yrow + t * 4);
    sts128(sy + t * 16, make_uint4(v.x << 16, v.x & 0xffff0000u, v.y << 16, v.y & 0xffff0000u));
  }
  bar_sync(4, 128);
#pragma unroll 1
  for (int u = 0; u < nu; u++) {
    const size_t o = (size_t)(t >> 1) * FF + j0 + u * 16 + (t & 1) * 8;
    float g[16];
#pragma unroll
    for (int i = 0; i < 16; i++) g[i] = 0.f;
#pragma unroll 1
    for (int k0 = 0; k0 < 8; k0 += 4) {
      uint4 a[4], b[4];
#pragma unroll
      for (int k = 0; k < 4; k++) {
        a[k] = __ldg((const uint4*)(prm.w_gate + o + (size_t)(k0 + k) * 64 * FF));
        b[k] = __ldg((const uint4*)(prm.w_up + o + (size_t)(k0 + k) * 64 * FF));
      }
#pragma unroll
      for (int k = 0; k < 4; k++) {
        const float yv = __uint_as_float(lds32(sy + ((t >> 1) + (k0 + k) * 64) * 4));
        g[0] += yv * bf_lo(a[k].x); g[1] += yv * bf_hi(a[k].x); g[2] += yv * bf_lo(a[k].y); g[3] += yv * bf_hi(a[k].y);
        g[4] += yv * bf_lo(a[k].z); g[5] += yv * bf_hi(a[k].z); g[6] += yv * bf_lo(a[k].w); g[7] += yv * bf_hi(a[k].w);
        g[8] += yv * bf_lo(b[k].x); g[9] += yv * bf_hi(b[k].x); g[10] += yv * bf_lo(b[k].y); g[11] += yv * bf_hi(b[k].y);
        g[12] += yv * bf_lo(b[k].z); g[13] += yv * bf_hi(b[k].z); g[14] += yv * bf_lo(b[k].w); g[15] += yv * bf_hi(b[k].w);
      }
    }
    halve<8>(g, lane); halve<4>(g, lane); halve<2>(g, lane); halve<1>(g, lane);
    sts32(sr + c * 512 + ((lane >> 4) * 64 + u * 16 + (lane & 1) * 8 + ((lane >> 1) & 7)) * 4, __float_as_uint(g[0]));
  }
  const bf16* wd = prm.w_down + (size_t)(j0 + (t >> 6)) * DM + (t & 63) * 8;
  uint4 d[8];
#pragma unroll
  for (int k = 0; k < 8; k++) d[k] = __ldg((const uint4*)(wd + (size_t)k * 2 * DM));
  bar_sync(4, 128);
  if (t < nu * 16) {
    float g = 0.f, u = 0.f;
#pragma unroll
    for (int i = 0; i < 4; i++) { g += __uint_as_float(lds32(sr + i * 512 + t * 4)); u += __uint_as_float(lds32(sr + i * 512 + 256 + t * 4)); }
    g = round_bf16(g); u = round_bf16(u);
    const float sg = round_bf16(g / (1.f + __expf(-g)));
    sts32(sh + t * 4, __float_as_uint(round_bf16(sg * u)));
  }
  bar_sync(4, 128);
  float acc[8];
#pragma unroll
  for (int i = 0; i < 8; i++) acc[i] = 0.f;
#pragma unroll 1
  for (int u = 0; u < nu; u++) {
#pragma unroll
    for (int k = 0; k < 8; k++) {
      const float hv = __uint_as_float(lds32(sh + (u * 16 + k * 2 + (t >> 6)) * 4));
      acc[0] += hv * bf_lo(d[k].x); acc[1] += hv * bf_hi(d[k].x); acc[2] += hv * bf_lo(d[k].y); acc[3] += hv * bf_hi(d[k].y);
      acc[4] += hv * bf_lo(d[k].z); acc[5] += hv * bf_hi(d[k].z); acc[6] += hv * bf_lo(d[k].w); acc[7] += hv * bf_hi(d[k].w);
      if (u + 1 < nu) d[k] = __ldg((const uint4*)(wd + (size_t)((u + 1) * 16 + k * 2) * DM));
    }
  }
  {
    const bool up = t >= 64;
    sts128(sd + (t & 63) * 32 + (up ? 0 : 16), up ? make_uint4(__float_as_uint(acc[0]), __float_as_uint(acc[1]), __float_as_uint(acc[2]), __float_as_uint(acc[3]))
                                                  : make_uint4(__float_as_uint(acc[4]), __float_as_uint(acc[5]), __float_as_uint(acc[6]), __float_as_uint(acc[7])));
    bar_sync(4, 128);
    const uint4 o = lds128(sd + (t & 63) * 32 + (up ? 16 : 0));
    asm volatile("red.relaxed.gpu.global.add.v4.f32 [%0], {%1,%2,%3,%4};" ::"l"(&g_fl.upd[ev][(t & 63) * 8 + (up ? 4 : 0)]),
                 "f"((up ? acc[4] : acc[0]) + __uint_as_float(o.x)), "f"((up ? acc[5] : acc[1]) + __uint_as_float(o.y)),
                 "f"((up ? acc[6] : acc[2]) + __uint_as_float(o.z)), "f"((up ? acc[7] : acc[3]) + __uint_as_float(o.w)) : "memory");
  }
  bar_sync(4, 128);
  if (t == 0) red_release(g_fl.ffncnt[ev]);
}
__device__ __forceinline__ void ffn_finish(int ver, int ev, u64 key, int lane, float (&x)[16]) {
  const int tok = key_token(key);
  uint2 rx[4], ry[4];
  load_row(g_xr[ver] + (size_t)tok * DM, lane, rx);
  load_row(g_y[ver] + (size_t)tok * DM, lane, ry);
  wait_count(g_fl.ffncnt[ev], NWORK, 80);
  float y[16];
  unpack_row(rx, x); unpack_row(ry, y);
  const float sig = round_bf16(1.f / (1.f + __expf(-key_score(key))));
#pragma unroll
  for (int q = 0; q < 4; q++) {
    const uint4 u = ld_rlx128(&g_fl.upd[ev][q * 128 + lane * 4]);
    const float uv[4] = {__uint_as_float(u.x), __uint_as_float(u.y), __uint_as_float(u.z), __uint_as_float(u.w)};
#pragma unroll
    for (int i = 0; i < 4; i++) x[4 * q + i] = round_bf16(x[4 * q + i] + round_bf16(y[4 * q + i] + round_bf16(round_bf16(uv[i]) * sig)));
  }
}

__global__ void __launch_bounds__(512, 1) worker_kernel(const __grid_constant__ WorkerParams prm) {
  extern __shared__ __align__(1024) uint8_t smem_raw[];
  const uint32_t sb = (smem_u32(smem_raw) + 1023) & ~1023u;
  const int tid = threadIdx.x, lane = tid & 31;
  const int w = __shfl_sync(~0u, tid >> 5, 0);
  const int me = blockIdx.x, kb = me >> 2, cb = me & 3;
  const bool full = me < 32;
  const uint32_t bars = sb + K_BAR;
  TG(0)
  if (tid == 0) {
    for (int v = 0; v < 3; v++) { mbar_init(bars + (KB_FULL + v) * 8, 1); mbar_init(bars + (KB_EMPTY + v) * 8, 2); mbar_init(bars + (KB_IN + v) * 8, 1); mbar_init(bars + (KB_OK + v) * 8, 1); }
    asm volatile("fence.mbarrier_init.release.cluster;" ::: "memory");
  }
  if (full) {
    const bf16* W1 = prm.Wo + (size_t)kb * 512 * DM + cb * 128;
#pragma unroll 4
    for (int cidx = tid; cidx < 512 * 16; cidx += 512) {
      const int d = cidx >> 4, q = cidx & 15;
      cp16(sb + d * W_STRIDE + q * 16, W1 + (size_t)d * DM + q * 8);
    }
    asm volatile("cp.async.commit_group;" ::: "memory");
    asm volatile("cp.async.wait_group 0;" ::: "memory");
  }
  fence_async_smem();
  __syncthreads();
  if (w < 8) {
    reg_inc<176>();
    if (full) {
      uint32_t wA[32][4];
      load_wfrags(wA, sb, w, lane);
      fence_async_smem();
      bar_sync(5, 384);
      float* pw = &g_part[0][0] + ((lane & 3) * 2 * 8 + kb) * DM + cb * 128 + w * 16 + (lane >> 2);
#pragma unroll 1
      for (int n = 0; n < 3 * NSTEP; n++) {
        const int st = n / 3, v = n - st * 3, sg = v ? st - DELTA : st;
        if ((unsigned)sg >= (unsigned)NSEG) continue;
        float d[16];
        mbar_wait(bars + (KB_FULL + v) * 8, sg & 1, 81);
        TR(4 * v)
        const uint32_t db = desc_lo(sb + K_O + v * 32768, 128);
        wg_fence();
#pragma unroll
        for (int ks = 0; ks < 32; ks++) {
          if (ks == 0) wg_rs32<0, 0, HI_O>(d, wA[ks], db);
          else wg_rs32<0, 1, HI_O>(d, wA[ks], db + (ks >> 3) * 512 + (ks & 7) * 16);
        }
        wg_commit();
        wg_wait<0>();
        acc_fence(d);
        TR(4 * v + 1)
        if ((tid & 127) == 0) mbar_arrive(bars + (KB_EMPTY + v) * 8);
        if (sg > 0) mbar_wait(bars + (KB_OK + v) * 8, (sg - 1) & 1, 82);
        float* p = pw + (size_t)(v * 2 + (sg & 1)) * (32 * 8 * DM);
        const uint32_t tag = ((sg >> 1) & 1) ^ 1;
#pragma unroll
        for (int j = 0; j < 4; j++) {
          st_rlx32(p + (8 * j) * 8 * DM, (__float_as_uint(d[4 * j]) & ~1u) | tag);
          st_rlx32(p + (8 * j) * 8 * DM + 8, (__float_as_uint(d[4 * j + 2]) & ~1u) | tag);
          st_rlx32(p + (8 * j + 1) * 8 * DM, (__float_as_uint(d[4 * j + 1]) & ~1u) | tag);
          st_rlx32(p + (8 * j + 1) * 8 * DM + 8, (__float_as_uint(d[4 * j + 3]) & ~1u) | tag);
        }
        bar_arrive(1 + v, 288);
        TR(4 * v + 2)
      }
      TRDUMP
    }
  } else if (w < 12) {
    reg_dec<80>();
    if (full) {
      bar_sync(5, 384);
      if (w == 11) {
#pragma unroll 1
        for (int n = 0; n < 3 * NSTEP; n++) {
          const int st = n / 3, v = n - st * 3, sg = v ? st - DELTA : st;
          if ((unsigned)sg >= (unsigned)NSEG) continue;
          if (sg > 0) mbar_wait(bars + (KB_EMPTY + v) * 8, (sg - 1) & 1, 83);
          wait_count(&g_fl.oflag[v][sg][kb], 4, 84);
          TR(v)
          if (lane == 0) {
            fence_async_glb();
            mbar_expect_tx(bars + (KB_FULL + v) * 8, 32768);
            bulk_g2s(sb + K_O + v * 32768, g_O[v] + ((size_t)(sg & (OSLOTS - 1)) * 32 + kb * 4) * 8192, 32768, bars + (KB_FULL + v) * 8);
          }
          __syncwarp();
        }
      } else {
        const int v = w - 8;
        uint2 wr[4];
        load_row(prm.w_r, lane, wr);
        u64 best = 0;
        uint32_t nin = 0;
#pragma unroll 1
        for (int sg = 0; sg < NSEG; sg++) {
          const int st = v ? sg + DELTA : sg;
          (void)st;
          const int tok = sg * 32 + me;
          uint2 rx[4];
          if (v == 0) load_row(prm.x0 + (size_t)tok * DM, lane, rx);
          bar_sync(1 + v, 288);
          TR(0)
          if (v != 0) {
            const bf16* xin = g_x2 + (size_t)tok * DM;
            const u64 k = wait_keys(g_fl.key[0][sg], lane, 86);
            if (k > best) {
              best = k;
              if (v == 2 && key_token(k) == tok) { wait_count(g_fl.patch[sg], 1, 88); xin = g_x2p + sg * DM; }
            }
            load_row(xin, lane, rx);
          } else {
            __nanosleep(GATE_R);
          }
          float x[16], y[16];
          const uint32_t flip = ((sg >> 1) & 1) ? ~0u : 0u;
          for (int it = 0;; it++) {
            TR(1)
            if (lane == 0) {
              fence_async_glb();
              mbar_expect_tx(bars + (KB_IN + v) * 8, 16384);
              bulk_g2s(sb + K_IN + v * 16384, &g_part[v][0] + (size_t)((sg & 1) * 32 + me) * 8 * DM, 16384, bars + (KB_IN + v) * 8);
            }
            __syncwarp();
#pragma unroll
            for (int i = 0; i < 16; i++) y[i] = 0.f;
            uint32_t ok = 1;
            mbar_wait(bars + (KB_IN + v) * 8, nin++ & 1, 87);
            TR(2)
#pragma unroll 2
            for (int k = 0; k < 8; k++) {
#pragma unroll
              for (int q = 0; q < 4; q++) {
                const uint4 p = lds128(sb + K_IN + v * 16384 + k * 2048 + q * 512 + lane * 16);
                y[4 * q] += __uint_as_float(p.x); y[4 * q + 1] += __uint_as_float(p.y); y[4 * q + 2] += __uint_as_float(p.z); y[4 * q + 3] += __uint_as_float(p.w);
                ok &= and_x(p.x, p.y, flip) & and_x(p.z, p.w, flip);
              }
            }
            if (__all_sync(~0u, ok != 0)) { TRV(5, it) break; }
            give_up(it, SPIN_LIMIT, 85);
          }
          if (lane == 0) mbar_arrive(bars + (KB_OK + v) * 8);
          TR(4)
          unpack_row(rx, x);
#pragma unroll
          for (int i = 0; i < 16; i++) x[i] = round_bf16(x[i] + round_bf16(y[i]));
          store_row(g_xr[v] + (size_t)tok * DM, lane, x);
          warp_ln(x, y);
          store_row(g_y[v] + (size_t)tok * DM, lane, y);
          float rr = 0.f;
#pragma unroll
          for (int q = 0; q < 4; q++)
            rr += y[4 * q] * bf_lo(wr[q].x) + y[4 * q + 1] * bf_hi(wr[q].x) + y[4 * q + 2] * bf_lo(wr[q].y) + y[4 * q + 3] * bf_hi(wr[q].y);
#pragma unroll
          for (int i = 0; i < 16; i++) x[i] = round_bf16(x[i] + y[i]);
          store_row((v == 0 ? g_x2 : v == 1 ? g_fin : prm.out) + (size_t)tok * DM, lane, x);
          if (v == 0) {
            warp_ln(x, y, rr);
            store_row_img(g_xs[1] + (size_t)(tok >> 3) * 8192, tok & 7, lane, y);
          } else {
#pragma unroll
            for (int o = 16; o; o >>= 1) rr += __shfl_xor_sync(~0u, rr, o);
          }
          __syncwarp();
          TR(6)
          if (lane == 0) {
            const uint32_t bb = __float_as_uint(round_bf16(rr)), ob = (bb & 0x80000000u) ? ~bb : (bb | 0x80000000u);
            st_release_u64(&g_fl.key[v][sg][me], (u64)ob << 32 | (uint32_t)~tok);
          }
          __syncwarp();
          TR(3)
        }
      }
      TRDUMP
    }
  } else {
    reg_dec<80>();
    const int t = tid - 384;
    {
      const int nu = full ? 3 : 4, j0 = full ? me * 48 : 1536 + (me - 32) * 64;
      for (int i = t; i < 512; i += 128) {
        asm volatile("prefetch.global.L2 [%0];" ::"l"(prm.w_gate + (size_t)i * FF + j0));
        asm volatile("prefetch.global.L2 [%0];" ::"l"(prm.w_gate + (size_t)i * FF + j0 + nu * 16 - 8));
        asm volatile("prefetch.global.L2 [%0];" ::"l"(prm.w_up + (size_t)i * FF + j0));
        asm volatile("prefetch.global.L2 [%0];" ::"l"(prm.w_up + (size_t)i * FF + j0 + nu * 16 - 8));
        if (i < nu * 128) asm volatile("prefetch.global.L2 [%0];" ::"l"(prm.w_down + (size_t)j0 * DM + i * 64));
      }
    }
    u64 best = 0;
#pragma unroll 1
    for (int sg = 0; sg < NSEG; sg++) {
      const u64 k = wait_keys(g_fl.key[0][sg], lane, 90);
      if (k <= best) continue;
      best = k;
      const int tok = key_token(k);
      ffn_slice(prm, sb + K_FFN, t, g_y[0] + (size_t)tok * DM, sg);
      if ((tok & 31) == me) {
        uint8_t* dst = g_patch + (size_t)sg * 8192;
        const uint8_t* src = g_xs[1] + (size_t)(tok >> 3) * 8192;
        if (w == 12) {
          float x[16], y[16];
          ffn_finish(0, sg, k, lane, x);
          store_row(g_x2p + sg * DM, lane, x);
          warp_ln(x, y);
          store_row_img(dst, tok & 7, lane, y);
        } else {
          for (int i = t - 32; i < 512; i += 96)
            if (((i >> 3) & 7) != (tok & 7)) *(uint4*)(dst + i * 16) = ld_rlx128(src + i * 16);
        }
        bar_sync(4, 128);
        if (t == 0) st_release32(g_fl.patch[sg], 1);
      }
    }
    const int sstar = key_token(best) >> 5;
    u64 b2 = 0;
#pragma unroll 1
    for (int sg = w - 12; sg < NSEG; sg += 4) {
      const u64 k = wait_keys(g_fl.key[sg < sstar ? 1 : 2][sg], lane, 91);
      if (k > b2) b2 = k;
      if (sg < sstar && full) {
        (void)wait_keys(g_fl.key[2][sg], lane, 92);
        const size_t o = (size_t)(sg * 32 + me) * DM + lane * 8;
        const uint4 a = ld_rlx128(g_fin + o), b = ld_rlx128(g_fin + o + 256);
        *(uint4*)(prm.out + o) = a; *(uint4*)(prm.out + o + 256) = b;
      }
    }
    if (lane == 0) asm volatile("st.shared.b64 [%0], %1;" ::"r"(sb + K_FFN + 7168 + (w - 12) * 8), "l"(b2) : "memory");
    bar_sync(4, 128);
#pragma unroll
    for (int i = 0; i < 4; i++) {
      u64 k;
      asm volatile("ld.shared.b64 %0, [%1];" : "=l"(k) : "r"(sb + K_FFN + 7168 + i * 8) : "memory");
      if (k > b2) b2 = k;
    }
    const int tok = key_token(b2), ver = (tok >> 5) < sstar ? 1 : 2;
    ffn_slice(prm, sb + K_FFN, t, g_y[ver] + (size_t)tok * DM, NSEG);
    if ((tok & 31) == me && w == 12) {
      float x[16];
      ffn_finish(ver, NSEG, b2, lane, x);
      store_row(prm.out + (size_t)tok * DM, lane, x);
    }
  }
}
#undef TRC
#undef TRS

bool g_ready;

}

extern "C" void kernel_launch(void* const* d_in, const int* in_sizes, int n_in, void* d_out, int out_size) {
  (void)in_sizes; (void)n_in; (void)out_size;
  const bf16* x0 = (const bf16*)d_in[0];
  const bf16* mem0 = (const bf16*)d_in[1];
  const bf16* Wq = (const bf16*)d_in[2];
  const bf16* Wk = (const bf16*)d_in[3];
  const bf16* Wv = (const bf16*)d_in[4];
  const bf16* Wo = (const bf16*)d_in[5];
  if (!g_ready) {
    cudaFuncSetAttribute(worker_kernel, cudaFuncAttributeMaxDynamicSharedMemorySize, K_SMEM);
    cudaFuncSetAttribute(chain_kernel, cudaFuncAttributeMaxDynamicSharedMemorySize, C_SMEM);
    g_ready = true;
  }
  cudaStream_t st = cudaStreamPerThread;
  prep_kernel<<<NTOK / 8, 256, 0, st>>>(x0);
  chain_kernel<<<96, 512, C_SMEM, st>>>(Wq, Wk, Wv, Wo, mem0);
  cudaLaunchAttribute pdl[1];
  pdl[0].id = cudaLaunchAttributeProgrammaticStreamSerialization;
  pdl[0].val.programmaticStreamSerializationAllowed = 1;
  WorkerParams wp;
  wp.x0 = x0; wp.Wo = Wo; wp.w_r = (const bf16*)d_in[8]; wp.w_gate = (const bf16*)d_in[9]; wp.w_up = (const bf16*)d_in[10];
  wp.w_down = (const bf16*)d_in[11]; wp.out = (bf16*)d_out;
  cudaLaunchConfig_t cfg = {};
  cfg.gridDim = dim3(NWORK); cfg.blockDim = dim3(512); cfg.dynamicSmemBytes = K_SMEM; cfg.stream = st;
  cfg.attrs = pdl; cfg.numAttrs = 1;
  cudaLaunchKernelEx(&cfg, worker_kernel, wp);
}
```

```cpp
#include <cuda_runtime.h>
#include <cuda_bf16.h>
#include <stdint.h>

namespace {

typedef __nv_bfloat16 bf16;
typedef unsigned long long u64;

constexpr int NTOK = 2048, DM = 512, HD = 4096, NSEG = 64, FF = 1792;
#define DELTA 4
constexpr int NSTEP = NSEG + DELTA;
constexpr int SPIN_LIMIT = 40000;
constexpr int MBAR_LIMIT = 20000;
constexpr int NWORK = 36;
constexpr int OSLOTS = 8;

__device__ __align__(1024) uint8_t g_xs[2][NSEG * 32768];
__device__ __align__(1024) uint8_t g_patch[NSEG * 8192];
__device__ __align__(1024) uint8_t g_O[3][OSLOTS * 32 * 8192];
__device__ __align__(1024) float g_part[3][2 * 32 * 8 * DM];
__device__ __align__(1024) bf16 g_xr[3][NTOK * DM];
__device__ __align__(1024) bf16 g_y[3][NTOK * DM];
__device__ __align__(1024) bf16 g_x2[NTOK * DM];
__device__ __align__(1024) bf16 g_x2p[NSEG * DM];
__device__ __align__(1024) bf16 g_fin[NTOK * DM];
__device__ __align__(65536) uint32_t g_M[4 * 16384];
__device__ __align__(65536) uint32_t g_P[96 * 4096];
struct Flags {
  uint32_t pol[96];
  uint32_t stamp[96];
  uint32_t oflag[3][NSEG][8];
  uint32_t ffncnt[NSEG + 1][8];
  uint32_t patch[NSEG][8];
  u64 key[3][NSEG][32];
  float upd[NSEG + 1][DM];
};
__device__ __align__(1024) Flags g_fl;
#define TR(e)
#define TRV(e, v)
#define TG(i)
#define TRDUMP
#define TREXTRA 0

#define STAT(e, v)
#define STATC(n)
#define STATDUMP
__device__ __forceinline__ uint32_t smem_u32(const void* p) { return (uint32_t)__cvta_generic_to_shared(p); }
__device__ __forceinline__ uint32_t pack_bf16(float lo, float hi) {
  uint32_t r;
  asm("cvt.rn.bf16x2.f32 %0, %1, %2;" : "=r"(r) : "f"(hi), "f"(lo));
  return r;
}
__device__ __forceinline__ float bf_lo(uint32_t v) { return __uint_as_float(v << 16); }
__device__ __forceinline__ float bf_hi(uint32_t v) { return __uint_as_float(v & 0xffff0000u); }
__device__ __forceinline__ float ex2_fast(float x) { float y; asm("ex2.approx.ftz.f32 %0, %1;" : "=f"(y) : "f"(x)); return y; }
__device__ __forceinline__ float rcp_fast(float x) { float y; asm("rcp.approx.ftz.f32 %0, %1;" : "=f"(y) : "f"(x)); return y; }
__device__ __forceinline__ float round_bf16(float x) { return __bfloat162float(__float2bfloat16_rn(x)); }
__device__ __forceinline__ uint32_t clk32() { uint32_t t; asm volatile("mov.u32 %0, %%clock;" : "=r"(t) :: "memory"); return t; }

__device__ __forceinline__ void mma16816(float (&d)[4], uint32_t a0, uint32_t a1, uint32_t a2, uint32_t a3,
                                         uint32_t b0, uint32_t b1) {
  asm("mma.sync.aligned.m16n8k16.row.col.f32.bf16.bf16.f32 {%0,%1,%2,%3}, {%4,%5,%6,%7}, {%8,%9}, {%0,%1,%2,%3};"
      : "+f"(d[0]), "+f"(d[1]), "+f"(d[2]), "+f"(d[3])
      : "r"(a0), "r"(a1), "r"(a2), "r"(a3), "r"(b0), "r"(b1));
}
__device__ __forceinline__ void ldsm4t(uint32_t (&r)[4], uint32_t addr) {
  asm volatile("ldmatrix.sync.aligned.m8n8.x4.trans.shared.b16 {%0,%1,%2,%3}, [%4];"
               : "=r"(r[0]), "=r"(r[1]), "=r"(r[2]), "=r"(r[3]) : "r"(addr) : "memory");
}
__device__ __forceinline__ void stsm4(uint32_t addr, uint32_t a, uint32_t b, uint32_t c, uint32_t d) {
  asm volatile("stmatrix.sync.aligned.m8n8.x4.shared.b16 [%0], {%1,%2,%3,%4};" ::"r"(addr), "r"(a), "r"(b), "r"(c), "r"(d) : "memory");
}
__device__ __forceinline__ uint4 lds128(uint32_t a) {
  uint4 v; asm volatile("ld.shared.v4.b32 {%0,%1,%2,%3}, [%4];" : "=r"(v.x), "=r"(v.y), "=r"(v.z), "=r"(v.w) : "r"(a) : "memory"); return v;
}
__device__ __forceinline__ uint32_t lds32(uint32_t a) { uint32_t v; asm volatile("ld.shared.b32 %0, [%1];" : "=r"(v) : "r"(a) : "memory"); return v; }
__device__ __forceinline__ void sts32(uint32_t a, uint32_t x) { asm volatile("st.shared.b32 [%0], %1;" ::"r"(a), "r"(x) : "memory"); }
__device__ __forceinline__ void sts128(uint32_t a, uint4 v) {
  asm volatile("st.shared.v4.b32 [%0], {%1,%2,%3,%4};" ::"r"(a), "r"(v.x), "r"(v.y), "r"(v.z), "r"(v.w) : "memory");
}
__device__ __forceinline__ void cp16(uint32_t dst, const void* src) {
  asm volatile("cp.async.cg.shared.global [%0], [%1], 16;" ::"r"(dst), "l"(src) : "memory");
}
__device__ __forceinline__ void mbar_init(uint32_t mbar, uint32_t cnt) {
  asm volatile("mbarrier.init.shared.b64 [%0], %1;" ::"r"(mbar), "r"(cnt) : "memory");
}
__device__ __forceinline__ void mbar_expect_tx(uint32_t mbar, uint32_t bytes) {
  asm volatile("mbarrier.arrive.expect_tx.shared.b64 _, [%0], %1;" ::"r"(mbar), "r"(bytes) : "memory");
}
__device__ __forceinline__ void mbar_arrive_z(uint32_t mbar, uint32_t z) {
  asm volatile("{ .reg .pred p; setp.eq.u32 p, %1, 0; @p mbarrier.arrive.shared.b64 _, [%0]; }" ::"r"(mbar), "r"(z) : "memory");
}
__device__ __forceinline__ void mbar_expect_tx_z(uint32_t mbar, uint32_t bytes, uint32_t z) {
  asm volatile("{ .reg .pred p; setp.eq.u32 p, %2, 0; @p mbarrier.arrive.expect_tx.shared.b64 _, [%0], %1; }" ::"r"(mbar), "r"(bytes), "r"(z) : "memory");
}
__device__ __forceinline__ void mbar_arrive_remote_z(uint32_t mbar, uint32_t z) {
  asm volatile("{ .reg .pred p; setp.eq.u32 p, %1, 0; @p mbarrier.arrive.shared::cluster.b64 _, [%0]; }" ::"r"(mbar), "r"(z) : "memory");
}
__device__ __forceinline__ bool mbar_try(uint32_t mbar, uint32_t par) {
  uint32_t ok;
  asm volatile("{ .reg .pred p; mbarrier.try_wait.parity.shared::cta.b64 p, [%1], %2; selp.u32 %0, 1, 0, p; }"
               : "=r"(ok) : "r"(mbar), "r"(par) : "memory");
  return ok;
}
__device__ __forceinline__ void fail(int) { __trap(); }
__device__ __forceinline__ void give_up(int it, int limit, int code) { if (it > limit) fail(code); }
__device__ __forceinline__ void mbar_wait(uint32_t mbar, uint32_t par, int code) {
  asm volatile("{ .reg .pred p; .reg .b32 n; mov.b32 n, %2;\n"
               "W: mbarrier.try_wait.parity.shared::cta.b64 p, [%0], %1; @p bra D;\n"
               "add.s32 n, n, -1; setp.eq.s32 p, n, 0; @p trap; bra W;\n"
               "D: }" ::"r"(mbar), "r"(par), "n"(MBAR_LIMIT) : "memory");
}
__device__ __forceinline__ void mbar_gate(uint32_t mbar, uint32_t par) {
  const uint32_t t0 = clk32();
  while (!mbar_try(mbar, par) && clk32() - t0 < 20000) {}
}
__device__ __forceinline__ void bulk_g2s(uint32_t dst, const void* src, uint32_t bytes, uint32_t mbar) {
  asm volatile("cp.async.bulk.shared::cluster.global.mbarrier::complete_tx::bytes [%0], [%1], %2, [%3];"
               ::"r"(dst), "l"(src), "r"(bytes), "r"(mbar) : "memory");
}
__device__ __forceinline__ void bulk_s2r(uint32_t dst, uint32_t src, uint32_t bytes, uint32_t mbar) {
  asm volatile("cp.async.bulk.shared::cluster.shared::cta.mbarrier::complete_tx::bytes [%0], [%1], %2, [%3];"
               ::"r"(dst), "r"(src), "r"(bytes), "r"(mbar) : "memory");
}
__device__ __forceinline__ void bulk_s2g(void* dst, uint32_t src, uint32_t bytes) {
  asm volatile("cp.async.bulk.global.shared::cta.bulk_group [%0], [%1], %2;" ::"l"(dst), "r"(src), "r"(bytes) : "memory");
}
__device__ __forceinline__ void fence_async_smem() { asm volatile("fence.proxy.async.shared::cta;" ::: "memory"); }
__device__ __forceinline__ void fence_async_glb() { asm volatile("fence.proxy.async.global;" ::: "memory"); }
__device__ __forceinline__ void bar_sync(int id, int n) { asm volatile("bar.sync %0, %1;" ::"r"(id), "r"(n) : "memory"); }
__device__ __forceinline__ void bar_arrive(int id, int n) { asm volatile("bar.arrive %0, %1;" ::"r"(id), "r"(n) : "memory"); }
__device__ __forceinline__ void cluster_sync() { asm volatile("barrier.cluster.arrive.release; barrier.cluster.wait.acquire;" ::: "memory"); }
__device__ __forceinline__ uint32_t mapa_u32(uint32_t a, uint32_t r) {
  uint32_t o;
  asm("mapa.shared::cluster.u32 %0, %1, %2;" : "=r"(o) : "r"(a), "r"(r));
  return o;
}
template <int OFF>
__device__ __forceinline__ void st_async32(uint32_t a, uint32_t x, uint32_t mbar) {
  asm volatile("st.async.weak.shared::cluster.mbarrier::complete_tx::bytes.b32 [%0 + %3], %1, [%2];" ::"r"(a), "r"(x), "r"(mbar), "n"(OFF) : "memory");
}
__device__ __forceinline__ uint4 ld_rlx128(const void* p) {
  uint4 v;
  asm volatile("ld.relaxed.gpu.global.v4.u32 {%0,%1,%2,%3}, [%4];" : "=r"(v.x), "=r"(v.y), "=r"(v.z), "=r"(v.w) : "l"(p) : "memory");
  return v;
}
__device__ __forceinline__ uint2 ld_rlx64(const void* p) {
  uint2 v; asm volatile("ld.relaxed.gpu.global.v2.u32 {%0,%1}, [%2];" : "=r"(v.x), "=r"(v.y) : "l"(p) : "memory"); return v;
}
__device__ __forceinline__ uint32_t ld_rlx32(const void* p) {
  uint32_t v; asm volatile("ld.relaxed.gpu.global.u32 %0, [%1];" : "=r"(v) : "l"(p) : "memory"); return v;
}
__device__ __forceinline__ void st_rlx32(void* p, uint32_t a) { asm volatile("st.relaxed.gpu.global.u32 [%0], %1;" ::"l"(p), "r"(a) : "memory"); }
__device__ __forceinline__ void red_release(uint32_t* p) { asm volatile("red.release.gpu.global.add.u32 [%0], 1;" ::"l"(p) : "memory"); }
__device__ __forceinline__ void st_release32(void* p, uint32_t a) { asm volatile("st.release.gpu.global.u32 [%0], %1;" ::"l"(p), "r"(a) : "memory"); }
__device__ __forceinline__ void st_release_u64(void* p, u64 a) { asm volatile("st.release.gpu.global.u64 [%0], %1;" ::"l"(p), "l"(a) : "memory"); }
__device__ __forceinline__ void wait_count(const uint32_t* p, uint32_t val, int code) {
  int it = 0;
  while (ld_rlx32(p) < val) {
    give_up(++it, SPIN_LIMIT, code);
    __nanosleep(40);
  }
}
__device__ __forceinline__ u64 wait_keys(const u64* keys, int lane, int code) {
  u64 k;
  int it = 0;
  while (true) {
    asm volatile("ld.relaxed.gpu.global.u64 %0, [%1];" : "=l"(k) : "l"(keys + lane) : "memory");
    if (__all_sync(~0u, k != 0)) break;
    give_up(++it, SPIN_LIMIT, code);
    __nanosleep(100);
  }
  const uint32_t hi = __reduce_max_sync(~0u, (uint32_t)(k >> 32));
  const uint32_t lo = __reduce_max_sync(~0u, (uint32_t)(k >> 32) == hi ? (uint32_t)k : 0u);
  return (u64)hi << 32 | lo;
}
__device__ __forceinline__ int key_token(u64 k) { return (int)(~(uint32_t)k) & (NTOK - 1); }
__device__ __forceinline__ float key_score(u64 k) {
  const uint32_t ob = (uint32_t)(k >> 32);
  return __uint_as_float((ob & 0x80000000u) ? (ob & 0x7fffffffu) : ~ob);
}

__device__ __forceinline__ uint64_t mk_desc(uint32_t saddr, uint32_t lbo, uint32_t sbo, uint32_t sw) {
  return (uint64_t)((saddr & 0x3FFFF) >> 4) | (uint64_t)(lbo >> 4) << 16 | (uint64_t)(sbo >> 4) << 32 | (uint64_t)sw << 62;
}
template <int N> __device__ __forceinline__ void reg_inc() { asm volatile("setmaxnreg.inc.sync.aligned.u32 %0;" ::"n"(N)); }
template <int N> __device__ __forceinline__ void reg_dec() { asm volatile("setmaxnreg.dec.sync.aligned.u32 %0;" ::"n"(N)); }
__device__ __forceinline__ void wg_fence() { asm volatile("wgmma.fence.sync.aligned;" ::: "memory"); }
__device__ __forceinline__ void wg_commit() { asm volatile("wgmma.commit_group.sync.aligned;" ::: "memory"); }
template <int N> __device__ __forceinline__ void wg_wait() { asm volatile("wgmma.wait_group.sync.aligned %0;" ::"n"(N) : "memory"); }
template <int N> __device__ __forceinline__ void acc_fence(float (&d)[N]) {
#pragma unroll
  for (int i = 0; i < N; i++) asm volatile("" : "+f"(d[i]) :: "memory");
}
#define O4(d, i) "+f"(d[i]), "+f"(d[i + 1]), "+f"(d[i + 2]), "+f"(d[i + 3])
template <int TB, int ACC>
__device__ __forceinline__ void wg_rs8(float (&d)[4], const uint32_t (&a)[4], uint64_t db) {
  asm volatile("wgmma.mma_async.sync.aligned.m64n8k16.f32.bf16.bf16 {%0,%1,%2,%3}, {%4,%5,%6,%7}, %8, %9, 1, 1, %10;"
               : O4(d, 0) : "r"(a[0]), "r"(a[1]), "r"(a[2]), "r"(a[3]), "l"(db), "n"(ACC), "n"(TB));
}
template <int TB, int ACC>
__device__ __forceinline__ void wg_rs24(float (&d)[12], const uint32_t (&a)[4], uint64_t db) {
  asm volatile("wgmma.mma_async.sync.aligned.m64n24k16.f32.bf16.bf16 {%0,%1,%2,%3,%4,%5,%6,%7,%8,%9,%10,%11}, {%12,%13,%14,%15}, %16, %17, 1, 1, %18;"
               : O4(d, 0), O4(d, 4), O4(d, 8) : "r"(a[0]), "r"(a[1]), "r"(a[2]), "r"(a[3]), "l"(db), "n"(ACC), "n"(TB));
}
template <int TB, int ACC>
__device__ __forceinline__ void wg_rs32(float (&d)[16], const uint32_t (&a)[4], uint64_t db) {
  asm volatile("wgmma.mma_async.sync.aligned.m64n32k16.f32.bf16.bf16 {%0,%1,%2,%3,%4,%5,%6,%7,%8,%9,%10,%11,%12,%13,%14,%15}, {%16,%17,%18,%19}, %20, %21, 1, 1, %22;"
               : O4(d, 0), O4(d, 4), O4(d, 8), O4(d, 12) : "r"(a[0]), "r"(a[1]), "r"(a[2]), "r"(a[3]), "l"(db), "n"(ACC), "n"(TB));
}
template <int ACC>
__device__ __forceinline__ void wg_rs64(float (&d)[32], uint32_t a0, uint32_t a1, uint32_t a2, uint32_t a3, uint64_t db) {
  asm volatile("wgmma.mma_async.sync.aligned.m64n64k16.f32.bf16.bf16 {%0,%1,%2,%3,%4,%5,%6,%7,%8,%9,%10,%11,%12,%13,%14,%15,"
               "%16,%17,%18,%19,%20,%21,%22,%23,%24,%25,%26,%27,%28,%29,%30,%31}, {%32,%33,%34,%35}, %36, %37, 1, 1, 0;"
               : O4(d, 0), O4(d, 4), O4(d, 8), O4(d, 12), O4(d, 16), O4(d, 20), O4(d, 24), O4(d, 28)
               : "r"(a0), "r"(a1), "r"(a2), "r"(a3), "l"(db), "n"(ACC));
}
template <int ACC>
__device__ __forceinline__ void wg_ss24(float (&d)[12], uint64_t da, uint64_t db) {
  asm volatile("wgmma.mma_async.sync.aligned.m64n24k16.f32.bf16.bf16 {%0,%1,%2,%3,%4,%5,%6,%7,%8,%9,%10,%11}, %12, %13, %14, 1, 1, 1, 0;"
               : O4(d, 0), O4(d, 4), O4(d, 8) : "l"(da), "l"(db), "n"(ACC));
}
template <int ACC>
__device__ __forceinline__ void wg_ss40(float (&d)[20], uint64_t da, uint64_t db) {
  asm volatile("wgmma.mma_async.sync.aligned.m64n40k16.f32.bf16.bf16 {%0,%1,%2,%3,%4,%5,%6,%7,%8,%9,%10,%11,%12,%13,%14,%15,%16,%17,%18,%19}, %20, %21, %22, 1, 1, 1, 1;"
               : O4(d, 0), O4(d, 4), O4(d, 8), O4(d, 12), O4(d, 16) : "l"(da), "l"(db), "n"(ACC));
}

struct Row { uint32_t w[8]; };
__device__ __forceinline__ uint32_t add_bf16x2(uint32_t a, uint32_t b) {
  uint32_t d; asm("add.rn.bf16x2 %0, %1, %2;" : "=r"(d) : "r"(a), "r"(b)); return d;
}
__device__ __forceinline__ Row warp_ln(const Row& r, float& extra) {
  float x[16];
#pragma unroll
  for (int i = 0; i < 8; i++) { x[2 * i] = bf_lo(r.w[i]); x[2 * i + 1] = bf_hi(r.w[i]); }
  float m = (((x[0] + x[1]) + (x[2] + x[3])) + ((x[4] + x[5]) + (x[6] + x[7]))) + (((x[8] + x[9]) + (x[10] + x[11])) + ((x[12] + x[13]) + (x[14] + x[15])));
  m *= (1.f / 16);
  float v0 = 0.f, v1 = 0.f;
#pragma unroll
  for (int i = 0; i < 16; i += 2) { const float d0 = x[i] - m, d1 = x[i + 1] - m; v0 = fmaf(d0, d0, v0); v1 = fmaf(d1, d1, v1); }
  float v = v0 + v1;
#pragma unroll
  for (int o = 1; o <= 16; o <<= 1) {
    const float mo = __shfl_xor_sync(~0u, m, o), vo = __shfl_xor_sync(~0u, v, o);
    extra += __shfl_xor_sync(~0u, extra, o);
    const float d = mo - m;
    v = fmaf(d * d, 8.f * o, v + vo);
    m = 0.5f * (m + mo);
  }
  const float var = fmaf(v, 1.f / DM, 1e-5f);
  float rs = rsqrtf(var);
  rs = rs * fmaf(-0.5f * var * rs, rs, 1.5f);
  Row y;
#pragma unroll
  for (int i = 0; i < 8; i++) y.w[i] = pack_bf16((x[2 * i] - m) * rs, (x[2 * i + 1] - m) * rs);
  return y;
}
__device__ __forceinline__ Row warp_ln(const Row& r) { float e = 0.f; return warp_ln(r, e); }
__device__ __forceinline__ Row load_row(const bf16* p, int lane) {
  Row r;
#pragma unroll
  for (int q = 0; q < 4; q++) { const uint2 v = ld_rlx64(p + lane * 4 + q * 128); r.w[2 * q] = v.x; r.w[2 * q + 1] = v.y; }
  return r;
}
__device__ __forceinline__ void store_row(bf16* p, int lane, const Row& r) {
#pragma unroll
  for (int q = 0; q < 4; q++) *(uint2*)(p + lane * 4 + q * 128) = make_uint2(r.w[2 * q], r.w[2 * q + 1]);
}
__device__ __forceinline__ void store_row_img(uint8_t* grp, int rr, int lane, const Row& r) {
  uint8_t* p = grp + (lane >> 4) * 1024 + rr * 128 + ((((lane & 15) >> 1) ^ rr) << 4) + (lane & 1) * 8;
#pragma unroll
  for (int q = 0; q < 4; q++) *(uint2*)(p + q * 2048) = make_uint2(r.w[2 * q], r.w[2 * q + 1]);
}

__global__ void __launch_bounds__(256) prep_kernel(const bf16* __restrict__ x0) {
  const int lane = threadIdx.x & 31, row = blockIdx.x * 8 + (threadIdx.x >> 5);
  const Row r = load_row(x0 + (size_t)row * DM, lane);
  const int gt = blockIdx.x * 256 + threadIdx.x, nt = gridDim.x * 256;
  uint4* M = (uint4*)g_M;
  for (int i = gt; i < 4 * 16384 / 4; i += nt) M[i] = make_uint4(~0u, ~0u, ~0u, ~0u);
  uint4* P = (uint4*)g_P;
  for (int i = gt; i < 96 * 4096 / 4; i += nt) P[i] = make_uint4(0, 0, 0, 0);
  uint4* F = (uint4*)&g_fl;
  for (int i = gt; i < (int)(sizeof(Flags) / 16); i += nt) F[i] = make_uint4(0, 0, 0, 0);
  store_row_img(g_xs[0] + (size_t)blockIdx.x * 8192, row & 7, lane, warp_ln(r));
}

constexpr int W_STRIDE = 272;
constexpr int C_WO = 0;
constexpr int C_X = 49152;
constexpr int C_M = C_X + 9 * 8192;
constexpr int C_Q = C_M + 24576;
constexpr int C_K = C_Q + 10240, C_V = C_K + 10240;
constexpr int C_SA = C_V + 10240, C_SB = C_SA + 8192, C_SP = C_SB + 8192;
constexpr int C_O = C_SP + 2048;
constexpr int C_OT = C_O + 6144;
constexpr int C_BAR = C_OT + 8192;
constexpr int C_SMEM = C_BAR + 256 + 1024 + TREXTRA;
static_assert(C_X + 512 * W_STRIDE <= C_BAR, "staging");
enum { B_M0 = 0, B_M1, B_M2, B_R, B_X, B_O, B_T, B_F, B_XL1, B_XL2, B_XL3, B_P1, B_P2, B_P3, B_OT, B_XF, B_NUM };
constexpr int C_INFO = C_BAR + 160, C_POL = C_BAR + 192;
enum { NB_ALL = 0, NB_S, NB_M0, NB_PV, NB_W0, NB_TA, NB_X1, NB_M1, NB_M2, NB_V, NB_RD };
constexpr float SCALE_LOG2E = 0.08838834764831845f * 1.4426950408889634f;
#define N0STEPS 8
#define N2STEPS 10
#define OGATE 3
#define SHIPLATE 0
#define XGATE 3
#define SHIP 1024
#define GATE_P 2700
#define BUMP_P 32
#define BUMP_M 48
#define GATE_W 200
#define GATE_G 200
#define GATE_M 3750
#define HOLE0 32
#define HOLE1 32
#define HOLE2 32
__device__ __forceinline__ uint32_t gtime() { uint32_t t; asm volatile("mov.u32 %0, %%globaltimer_lo;" : "=r"(t) :: "memory"); return t; }
__device__ __forceinline__ void wait_clock(uint32_t t) { while ((int)(clk32() - t) < 0) {} }
__device__ __forceinline__ bool bar_or(int id, int n, uint32_t v) {
  uint32_t r;
  asm volatile("{ .reg .pred p, q; setp.ne.u32 p, %1, 0; bar.red.or.pred q, %2, %3, p; vote.sync.any.pred q, q, 0xffffffff; selp.u32 %0, 1, 0, q; }"
               : "=r"(r) : "r"(v), "r"(id), "r"(n) : "memory");
  return r;
}
__device__ __forceinline__ void bar_sync_z(int id, int n, uint32_t z) {
  asm volatile("{ .reg .pred p; setp.eq.u32 p, %2, 0; @p bar.sync %0, %1; }" ::"r"(id), "r"(n), "r"(z) : "memory");
}

__device__ __forceinline__ uint32_t probe_polarity(uint32_t* p) {
  uint32_t best[2] = {~0u, ~0u};
#pragma unroll 1
  for (int rep = 0; rep < 4; rep++) {
#pragma unroll
    for (int pg = 0; pg < 2; pg++) {
      uint32_t t0, t1, v;
      asm volatile("mov.u32 %0, %%clock;" : "=r"(t0) :: "memory");
      asm volatile("atom.relaxed.gpu.global.add.u32 %0, [%1], 0;" : "=r"(v) : "l"(p + pg * 1024) : "memory");
      asm volatile("{ .reg .pred p; setp.ne.u32 p, %1, 0x13572468; mov.u32 %0, 0; @p mov.u32 %0, %%clock; }" : "=r"(t1) : "r"(v) : "memory");
      if (rep > 0) best[pg] = min(best[pg], t1 - t0);
    }
  }
  return best[1] < best[0] ? 1u : 0u;
}
__device__ __forceinline__ uint32_t ppage(uint32_t lp, uint32_t pol) { return lp ? 3 - pol : pol; }
__device__ __forceinline__ uint32_t and_x(uint32_t a, uint32_t b, uint32_t m) {
  uint32_t d; asm("lop3.b32 %0, %1, %2, %3, 0x42;" : "=r"(d) : "r"(a), "r"(b), "r"(m)); return d;
}
__device__ __forceinline__ uint32_t and3(uint32_t a, uint32_t b, uint32_t c) {
  uint32_t d; asm("lop3.b32 %0, %1, %2, %3, 0x80;" : "=r"(d) : "r"(a), "r"(b), "r"(c)); return d;
}

template <int N> struct IC { static constexpr int value = N; };
template <class F> __device__ __forceinline__ void static_for2(F f) { f(IC<0>()); f(IC<1>()); }
template <class F> __device__ __forceinline__ void static_for3(F f) { f(IC<0>()); f(IC<1>()); f(IC<2>()); }
__device__ __forceinline__ void load_wfrags(uint32_t (&wA)[32][4], uint32_t stage, int w, int lane) {
  const int mi = lane >> 3, r = lane & 7;
#pragma unroll
  for (int ks = 0; ks < 32; ks++) ldsm4t(wA[ks], stage + (ks * 16 + (mi >> 1) * 8 + r) * W_STRIDE + (w * 16 + (mi & 1) * 8) * 2);
}
template <int K0, int K1>
__device__ __forceinline__ void tok_seq(float (&d)[16], const uint32_t (&wA)[32][4], uint64_t desc, uint32_t wave) {
#pragma unroll
  for (int k = K0; k < K1; k++) {
    const int ks = k & 31;
    constexpr int HM0 = 1, HM1 = 2, HM2 = 4;
    const int hm = (k == HOLE0 ? HM0 : 0) | (k == HOLE1 ? HM1 : 0) | (k == HOLE2 ? HM2 : 0);
    if (hm) bar_sync_z(NB_RD, 384, ((hm >> wave) & 1) ^ 1);
    if (ks == 0) wg_rs32<0, 0>(d, wA[ks], desc);
    else wg_rs32<0, 1>(d, wA[ks], desc + (ks >> 2) * 64 + (ks & 3) * 2);
  }
}
template <int K0, int K1>
__device__ __forceinline__ void mem_part(float (&d)[12], const uint32_t (&wA)[32][4], uint64_t desc) {
#pragma unroll
  for (int ks = K0; ks < K1; ks++) {
    if (ks == 0) wg_rs24<1, 0>(d, wA[ks], desc);
    else wg_rs24<1, 1>(d, wA[ks], desc + ks * 48);
  }
}
__device__ __forceinline__ void out_tile(float (&d)[12], uint64_t da, uint64_t db) {
#pragma unroll
  for (int i = 0; i < 8; i++) { if (i == 0) wg_ss24<0>(d, da, db); else wg_ss24<1>(d, da + i * 128, db + (i >> 1) * 32 + (i & 1) * 2); }
}
__device__ __forceinline__ void tok_pack(uint32_t (&p)[8], const float (&d)[16]) {
#pragma unroll
  for (int i = 0; i < 8; i++) p[i] = pack_bf16(d[2 * i], d[2 * i + 1]);
}
__device__ __forceinline__ void tok_store(uint32_t dst, const uint32_t (&p)[8]) {
  stsm4(dst, p[0], p[1], p[2], p[3]);
  stsm4(dst + 4096, p[4], p[5], p[6], p[7]);
}
template <class T> __device__ __forceinline__ T keep(T v) { asm volatile("" : "+r"(v)); return v; }
__device__ __forceinline__ uint32_t pin(uint32_t v) { return __shfl_sync(~0u, v, threadIdx.x & 31); }

#define TRC blockIdx.x
#define TRS (C_BAR + 256)
__device__ __forceinline__ void chain_proj(const uint32_t sb, const int w, const int lane_, const uint32_t rank) {
  uint32_t wA[32][4];
  load_wfrags(wA, sb + C_X, w, lane_);
  bar_sync(NB_ALL, 512);
  bar_sync(NB_ALL, 512);
  cluster_sync();
  const int lane = pin(lane_);
  const uint32_t bars = sb + C_BAR;
  const uint32_t quad = pin(sb + (lane_ >> 4) * 2048 + (lane_ & 15) * 16);
  const uint32_t own = C_Q + rank * 10240;
  const uint64_t dX1 = mk_desc(sb + C_X, 16, 8192, 1), dX2 = dX1 + 2048, dX3 = dX1 + 4096;
  const uint64_t dM = mk_desc(sb + C_M, 128, 256, 0);
  const uint32_t r1 = rank == 0 ? 1 : 0, r2 = rank == 2 ? 1 : 2;
  const uint32_t xa = pin(sb + own + 8192 + w * 256 + lane_ * 4);
  const uint32_t a1x = pin(mapa_u32(xa, r1)), a2x = pin(mapa_u32(xa, r2));
  const uint32_t b1x = pin(mapa_u32(bars + B_X * 8, r1)), b2x = pin(mapa_u32(bars + B_X * 8, r2));
  const uint32_t wave = rank == 2 ? 0 : rank + 1;
  uint32_t npatch = 0;
  constexpr int K3 = 32 - N0STEPS - N2STEPS;
  float a[16];
  bar_sync(NB_X1, 288);
  wg_fence();
  tok_seq<32, 32 + K3>(a, wA, dX1, 3);
  wg_commit();
  wg_wait<0>();
#pragma unroll 1
  for (int st = 0; st < NSTEP; st++) {
    uint32_t pk[8];
    wg_fence();
    tok_seq<32 + K3, 32 + K3 + N0STEPS>(a, wA, dX1, 3);
    TR(0)
    bar_sync(NB_PV, 384);
    tok_seq<32 + K3 + N0STEPS, 64>(a, wA, dX1, 3);
    wg_commit();
    wg_wait<0>();
    acc_fence(a);
    mbar_arrive_z(bars + B_XF * 8, lane);
    tok_pack(pk, a);
    TR(1)
    bar_sync(NB_W0, 416);
    tok_store(quad + w * 256 + (rank == 0 ? own : C_SA), pk);
    __syncwarp();
    mbar_arrive_z(bars + B_P2 * 8, lane);
    wg_fence();
    tok_seq<0, 32>(a, wA, dX2, wave);
    wg_commit();
    const uint32_t info = lds32(sb + C_INFO + (st & 1) * 4);
    TR(2)
    wg_wait<0>();
    acc_fence(a);
    TR(3)
    tok_pack(pk, a);
    tok_store(quad + w * 256 + (rank == 0 ? C_SA : own), pk);
    if (rank == 2) tok_store(quad + w * 256 + C_SB, pk);
    __syncwarp();
    mbar_arrive_z(bars + B_P1 * 8, lane);
    if (__builtin_expect(info & 4, 0)) {
      float a3[4];
      mbar_wait(bars + B_XL3 * 8, npatch & 1, 32);
      npatch++;
      wg_fence();
#pragma unroll
      for (int ks = 0; ks < 32; ks++) {
        if (ks == 0) wg_rs8<0, 0>(a3, wA[ks], dX3);
        else wg_rs8<0, 1>(a3, wA[ks], dX3 + (ks >> 2) * 64 + (ks & 3) * 2);
      }
      wg_commit();
      wg_wait<0>();
      acc_fence(a3);
      const uint32_t dst = sb + (rank == 2 ? own + (info & 3) * 2048 : C_SP) + w * 256 + lane * 4;
      sts32(dst, pack_bf16(a3[0], a3[1])); sts32(dst + 128, pack_bf16(a3[2], a3[3]));
      __syncwarp();
      mbar_arrive_z(bars + B_P3 * 8, lane);
    }
    TR(4)
    bar_sync(NB_X1, 288);
    wg_fence();
    tok_seq<32, 32 + K3>(a, wA, dX1, wave);
    TR(6)
    {
      float am[12];
      bar_sync(NB_M0, 384);
      mem_part<0, 10>(am, wA, dM);
      TR(7)
      bar_sync(NB_M1, 384);
      mem_part<10, 21>(am, wA, dM);
      const bool redo = bar_or(NB_M2, 384, 0);
      mem_part<21, 32>(am, wA, dM);
      wg_commit();
      wg_wait<0>();
      if (__builtin_expect(redo, 0)) {
        bar_sync(NB_V, 384);
        wg_fence();
        mem_part<0, 32>(am, wA, dM);
        wg_commit();
        wg_wait<0>();
      }
      acc_fence(am);
      TR(8)
      const uint32_t x00 = pack_bf16(am[0], am[1]), x01 = pack_bf16(am[2], am[3]), x10 = pack_bf16(am[4], am[5]), x11 = pack_bf16(am[6], am[7]);
      uint32_t x20 = pack_bf16(am[8], am[9]), x21 = pack_bf16(am[10], am[11]);
      if (info & 4) { x20 = x10; x21 = x11; }
      st_async32<0>(a1x, rank == 0 ? x10 : x00, b1x); st_async32<0>(a2x, rank == 2 ? x10 : x20, b2x);
      st_async32<128>(a1x, rank == 0 ? x11 : x01, b1x); st_async32<128>(a2x, rank == 2 ? x11 : x21, b2x);
      sts32(xa, rank == 0 ? x00 : rank == 2 ? x20 : x10); sts32(xa + 128, rank == 0 ? x01 : rank == 2 ? x21 : x11);
      __syncwarp();
      mbar_arrive_z(bars + B_X * 8, lane);
      if (w == 7) {
        const uint32_t stamp = (gtime() & ~31u) | ((st + 1) & 31);
        asm volatile("{ .reg .pred p; setp.eq.u32 p, %2, 0; @p st.relaxed.gpu.global.u32 [%0], %1; }" ::"l"(&g_fl.stamp[blockIdx.x]), "r"(stamp), "r"(lane) : "memory");
      }
    }
    TR(9)
  }
}

__device__ __forceinline__ void chain_mem(const uint32_t sb, const int w, const int lane_, const uint32_t rank, const int h,
                                          const bf16* __restrict__ mem0) {
  const int lane = pin(lane_);
  const int wave = rank == 2 ? 0 : rank + 1;
  const int c = w - 8, t = c * 32 + lane, b = wave * 32 + h;
  const uint32_t bars = sb + C_BAR;
  uint32_t pgbits = 0;
  {
    uint32_t pol = 1;
    const int tl = lane / 3, u = ((tl * 3 + rank) * 4 + c) * 3 + (lane - tl * 3);
    if (lane < 9 && u < 96) {
      int it = 0;
      while ((pol = ld_rlx32(&g_fl.pol[u])) == 0) give_up(++it, SPIN_LIMIT, 40);
    }
    pgbits = __reduce_or_sync(~0u, lane < 9 ? ppage(h >> 4, (pol - 1) & 1) << (2 * lane) : 0u);
  }
  const int wi = (lane & 1) * 2 + (lane >> 4), cq = (lane >> 2) & 3;
  bar_sync(NB_ALL, 512);
#pragma unroll 1
  for (int i = t; i < 2048; i += 128) {
    const unsigned short* mp = (const unsigned short*)mem0 + 2 * (i & 3) * DM + (i >> 2);
    const uint32_t v = (uint32_t)mp[0] | (uint32_t)mp[DM] << 16;
    const uint32_t a = sb + C_M + (i >> 6) * 768 + (i & 63) * 4;
    sts32(a, v); sts32(a + 256, v); sts32(a + 512, v);
  }
  fence_async_smem();
  mbar_expect_tx_z(bars + B_X * 8, 4096, t); mbar_expect_tx_z(bars + B_O * 8, 4096, t);
  bar_sync(NB_ALL, 512);
  cluster_sync();
  bar_arrive(NB_PV, 384); bar_arrive(NB_W0, 416); bar_arrive(NB_M0, 384); bar_arrive(NB_M1, 384);
  bar_arrive(NB_RD, 384);

  const int mi = lane >> 3;
  const uint32_t l16 = pin(sb + lane * 16);
  const uint32_t r1 = rank == 2 ? 0 : rank + 1, r2 = rank == 0 ? 2 : rank - 1;
  const uint32_t oa = pin(sb + C_O + rank * 2048 + (lane >> 2) * 64 + (((lane & 3) ^ (lane >> 3)) << 4));
  const uint32_t a1 = mapa_u32(oa, r1), b1 = mapa_u32(bars + B_O * 8, r1), a2 = mapa_u32(oa, r2), b2 = mapa_u32(bars + B_O * 8, r2);
  const uint64_t dWo = mk_desc(sb + C_WO, 8192, 1024, 1), dO = mk_desc(sb + C_O, 16, 2048, 2);
  const uint64_t dQ = mk_desc(sb + C_Q, 128, 2048, 0), dK = mk_desc(sb + C_K, 128, 2048, 0);
  const uint64_t dV = mk_desc(sb + C_V, 2048, 128, 0), dVm = mk_desc(sb + C_V + 8192, 0, 128, 0);
  const int lim = pin(c < 2 ? 16 * c + (lane >> 2) - 2 * (lane & 3) : 64);
  uint8_t* Pw = (uint8_t*)g_P + (rank * 4 + c) * 3 * 16384 + (h & 15) * 256 + lane * 4;
  const uint32_t polP = lds32(sb + C_POL + 16);
  const uint8_t* Pr0 = (const uint8_t*)g_P + b * 16384 + ((lane >> 4) * 4 + (lane & 3)) * 256 + c * 64 + cq * 16 + ppage(0, polP) * 4096;
  const uint8_t* Pr1 = Pr0 + (3 - 2 * polP) * 4096;
  uint8_t* Mw = (uint8_t*)g_M + (b >> 5) * 16384 + ((lane & 2) ? 4096 : 12288) + (b & 31) * 256 + c * 64 + cq * 16 + wi * 4;
  uint32_t nretry = 0;
  uint32_t gate_p = GATE_P + wave * GATE_W;
  sts32(sb + C_INFO + 20, GATE_M);

  (void)bar_or(NB_M2, 384, 0);
#pragma unroll 1
  for (int st = 0;; st++) {
    mbar_wait(bars + B_T * 8, st & 1, 42);
    STAT(10, clk32())
    mbar_wait(bars + B_X * 8, st & 1, 41);
    STAT(11, clk32())
    fence_async_smem();
    TR(0)
    {
      float s[20];
      wg_fence();
#pragma unroll
      for (int i = 0; i < 8; i++) { if (i == 0) wg_ss40<0>(s, dQ, dK); else wg_ss40<1>(s, dQ + i * 16, dK + i * 16); }
      wg_commit();
      wg_wait<0>();
      acc_fence(s);
      TR(1)
#pragma unroll
      for (int j = 0; j < 4; j++) {
        if (lim < 8 * j) s[4 * j] = -INFINITY;
        if (lim < 8 * j + 1) s[4 * j + 1] = -INFINITY;
        if (lim < 8 * j - 8) s[4 * j + 2] = -INFINITY;
        if (lim < 8 * j - 7) s[4 * j + 3] = -INFINITY;
      }
      float m0 = fmaxf(fmaxf(fmaxf(s[0], s[1]), fmaxf(s[4], s[5])), fmaxf(fmaxf(s[8], s[9]), fmaxf(s[12], s[13])));
      float m1 = fmaxf(fmaxf(fmaxf(s[2], s[3]), fmaxf(s[6], s[7])), fmaxf(fmaxf(s[10], s[11]), fmaxf(s[14], s[15])));
      m0 = fmaxf(m0, fmaxf(s[16], s[17])); m1 = fmaxf(m1, fmaxf(s[18], s[19]));
      m0 = fmaxf(m0, __shfl_xor_sync(~0u, m0, 1)); m1 = fmaxf(m1, __shfl_xor_sync(~0u, m1, 1));
      m0 = fmaxf(m0, __shfl_xor_sync(~0u, m0, 2)); m1 = fmaxf(m1, __shfl_xor_sync(~0u, m1, 2));
      m0 *= -SCALE_LOG2E; m1 *= -SCALE_LOG2E;
      uint32_t p[10];
      float l0 = 0.f, l1 = 0.f;
#pragma unroll
      for (int k = 0; k < 10; k++) {
        const float e0 = ex2_fast(fmaf(s[2 * k], SCALE_LOG2E, (k & 1) ? m1 : m0)), e1 = ex2_fast(fmaf(s[2 * k + 1], SCALE_LOG2E, (k & 1) ? m1 : m0));
        p[k] = pack_bf16(e0, e1);
        if (k & 1) l1 += e0 + e1; else l0 += e0 + e1;
      }
      asm volatile("" : "+f"(l0), "+f"(l1));
      float oA[32], oB[32];
      wg_fence();
      wg_rs64<0>(oA, p[0], p[1], p[2], p[3], dV); wg_rs64<1>(oA, p[4], p[5], p[6], p[7], dV + 256); wg_rs64<1>(oA, p[8], p[9], 0, 0, dVm);
      wg_commit();
      wg_rs64<0>(oB, p[0], p[1], p[2], p[3], dV + 64); wg_rs64<1>(oB, p[4], p[5], p[6], p[7], dV + 320); wg_rs64<1>(oB, p[8], p[9], 0, 0, dVm + 64);
      wg_commit();
      l0 += __shfl_xor_sync(~0u, l0, 1); l1 += __shfl_xor_sync(~0u, l1, 1);
      l0 += __shfl_xor_sync(~0u, l0, 2); l1 += __shfl_xor_sync(~0u, l1, 2);
      const float i0 = rcp_fast(l0), i1 = rcp_fast(l1);
      const bool mrows = c == 2 && st < NSTEP - 1;
      auto send = [&](const float (&o)[32], auto hc) {
        constexpr int H = decltype(hc)::value;
        static_for2([&](auto bc) {
          constexpr int B = decltype(bc)::value, J = 16 * B;
          asm volatile("st.async.weak.shared::cluster.mbarrier::complete_tx::bytes.v4.b32 [%0 + %9], {%5,%6,%7,%8}, [%1];\n"
                       "st.async.weak.shared::cluster.mbarrier::complete_tx::bytes.v4.b32 [%2 + %9], {%5,%6,%7,%8}, [%3];\n"
                       "st.shared.v4.b32 [%4 + %9], {%5,%6,%7,%8};"
                       ::"r"(a1), "r"(b1), "r"(a2), "r"(b2), "r"(oa), "r"(pack_bf16(o[J] * i0, o[J + 1] * i0)), "r"(pack_bf16(o[J + 4] * i0, o[J + 5] * i0)),
                         "r"(pack_bf16(o[J + 8] * i0, o[J + 9] * i0)), "r"(pack_bf16(o[J + 12] * i0, o[J + 13] * i0)), "n"(H * 1024 + B * 512) : "memory");
        });
      };
      auto keep_tok = [&](const float (&o)[32], int H) {
        const uint32_t ta = l16 + C_OT + c * 4096 + H * 1024;
#pragma unroll
        for (int k = 0; k < 4; k++) {
          const int J = (k & 1) * 16 + (k >> 1) * 2;
          const float iv = (k >> 1) ? i1 : i0;
          stsm4(ta + (k & 1) * 512 + (k >> 1) * 2048, pack_bf16(o[J] * iv, o[J + 1] * iv), pack_bf16(o[J + 4] * iv, o[J + 5] * iv),
                pack_bf16(o[J + 8] * iv, o[J + 9] * iv), pack_bf16(o[J + 12] * iv, o[J + 13] * iv));
        }
      };
      wg_wait<1>();
      acc_fence(oA);
      if (mrows) send(oA, IC<0>());
      wg_wait<0>();
      acc_fence(oB);
      if (st < NSTEP - 1) bar_arrive(NB_PV, 384);
      if (mrows) {
        send(oB, IC<1>());
        __syncwarp();
        mbar_arrive_z(bars + B_O * 8, lane);
      } else if (c < 2) {
        keep_tok(oA, 0);
        keep_tok(oB, 1);
        __syncwarp();
        mbar_arrive_z(bars + B_OT * 8, lane);
      }
      TR(2)
      if (st == NSTEP - 1) break;
      mbar_expect_tx_z(bars + B_X * 8, 4096, t);
    }
    uint32_t tref;
    {
      const uint32_t tag = (st & 1) ^ 1;
      float oc0[12], oc1[12], oc2[12];
      mbar_wait(bars + B_O * 8, st & 1, 43);
      fence_async_smem();
      TR(3)
      wg_fence();
      out_tile(oc0, dWo, dO);
      wg_commit();
      out_tile(oc1, dWo + 1024, dO);
      wg_commit();
      asm volatile("" : "+r"(pgbits));
      auto put = [&](const float (&oc)[12], auto tlc) {
        constexpr int TL = decltype(tlc)::value;
        static_for3([&](auto jc) {
          constexpr int j = decltype(jc)::value;
          uint8_t* p = Pw + ((pgbits >> (2 * (TL * 3 + j))) & 3) * 4096;
          asm volatile("st.relaxed.gpu.global.u32 [%0 + %3], %1; st.relaxed.gpu.global.u32 [%0 + %3 + 128], %2;" ::"l"(p),
                       "r"((pack_bf16(oc[4 * j], oc[4 * j + 1]) & ~1u) | tag), "r"((pack_bf16(oc[4 * j + 2], oc[4 * j + 3]) & ~1u) | tag),
                       "n"((TL * 36 + j) * 16384) : "memory");
        });
      };
      wg_wait<1>();
      acc_fence(oc0);
      put(oc0, IC<0>());
      sts32(sb + C_INFO + 24, clk32());
      TR(4)
      wg_wait<0>();
      if (rank != 2) {
        wg_fence();
        out_tile(oc2, dWo + 2048, dO);
        wg_commit();
        acc_fence(oc1);
        put(oc1, IC<1>());
        bar_sync(NB_TA, 160);
        TR(5)
        wg_wait<0>();
        bar_arrive(NB_W0, 416);
        acc_fence(oc2);
        put(oc2, IC<2>());
      } else {
        bar_arrive(NB_W0, 416);
        acc_fence(oc1);
        put(oc1, IC<1>());
        bar_sync(NB_TA, 160);
      }
      tref = __shfl_sync(~0u, lds32(sb + C_INFO + 12), 0);
      mbar_arrive_remote_z(((t & 1) ? b2 : b1) + (B_F - B_O) * 8, t >> 1);
      mbar_expect_tx_z(bars + B_O * 8, 4096, t);
      TR(6)
    }
    const int sn = (st + 1) & 3;
    {
      const uint32_t flip = (st & 1) ? ~0u : 0u;
      const bool u16 = lane & 16;
      uint8_t* mw = Mw + sn * 65536;
      asm volatile("" : "+l"(mw));
      const uint32_t bs = (lane & 4) ? 0x3f800000u : 0x00003f80u, bs0 = (lane & 8) ? 0u : bs, bs1 = (lane & 8) ? bs : 0u;
      const bool early = st < DELTA && b % 3 != 0;
      uint32_t m0word = 0;
      if (__builtin_expect(early, 0)) {
        const unsigned short* mp = (const unsigned short*)mem0 + ((lane & 1) * 4 + (lane >> 4) * 2) * DM + b / 3 * 16 + c * 4 + ((lane >> 2) & 3);
        m0word = (uint32_t)mp[0] | (uint32_t)mp[DM] << 16;
      }
      STATC(c_rdy)
      wait_clock(tref + gate_p);
      TR(7)
      uint32_t mword;
      int it = 0;
      bool all;
#pragma unroll 1
      do {
        const uint4 q0 = ld_rlx128(Pr0), q1 = ld_rlx128(Pr0 + 2048), q2 = ld_rlx128(Pr1), q3 = ld_rlx128(Pr1 + 2048);
        float d0[4] = {0.f, 0.f, 0.f, 0.f}, d1[4] = {0.f, 0.f, 0.f, 0.f};
        mma16816(d0, q0.x, q0.y, q0.z, q0.w, bs0, bs1);
        mma16816(d1, q1.x, q1.y, q1.z, q1.w, bs0, bs1);
        mma16816(d0, q2.x, q2.y, q2.z, q2.w, bs0, bs1);
        mma16816(d1, q3.x, q3.y, q3.z, q3.w, bs0, bs1);
        all = __all_sync(~0u, (int)and3(and_x(q0.x, q1.x, flip), and_x(q2.x, q3.x, flip), 1u));
        const float a0 = d0[0] + d1[0], a1 = d0[1] + d1[1], a2 = d0[2] + d1[2], a3 = d0[3] + d1[3];
        mword = pack_bf16((u16 ? a2 : a0) + __shfl_xor_sync(~0u, u16 ? a0 : a2, 16), (u16 ? a3 : a1) + __shfl_xor_sync(~0u, u16 ? a1 : a3, 16));
        asm volatile("{ .reg .pred p; setp.ne.u32 p, %2, 0; @p st.relaxed.gpu.global.u32 [%0], %1; }" ::"l"(mw), "r"(early ? m0word : mword), "r"((uint32_t)all) : "memory");
      } while (__builtin_expect(!all, 0) && ++it < SPIN_LIMIT);
      bar_arrive(NB_RD, 384);
      STATC(c_mst)
      STAT(0, lds32(sb + C_INFO + 24) - tref) STAT(1, c_rdy - tref) STAT(2, c_mst - tref) STAT(3, tref) STAT(4, it)
      if (!all) fail(44);
      TRV(14, it)
    }
    TR(9)
    {
      const uint32_t ma = l16 + C_M + c * 512 + mi * 4;
      auto scan = [&](uint32_t m, uint32_t a) { return __vimax3_u32(__vimax3_u32(m, lds32(a), lds32(a + 2048)), lds32(a + 4096), lds32(a + 6144)); };
      mbar_wait(bars + B_M0 * 8, (st + 1) & 1, 45);
      bar_arrive(NB_M0, 384);
      STATC(c_g0)
      TR(10)
      uint32_t m = scan(0, ma);
      mbar_wait(bars + B_M1 * 8, (st + 1) & 1, 46);
      bar_arrive(NB_M1, 384);
      STATC(c_g1)
      TR(11)
      m = scan(m, ma + 8192);
      mbar_wait(bars + B_M2 * 8, (st + 1) & 1, 47);
      STATC(c_g2)
      TR(12)
      m = scan(m, ma + 16384);
      int it = 0;
      if (__builtin_expect(bar_or(NB_M2, 384, m == ~0u), 0)) {
#pragma unroll 1
        do {
          give_up(++it, SPIN_LIMIT, 48);
          if (t == 0) {
            const uint8_t* src = (const uint8_t*)g_M + sn * 65536 + (lds32(sb + C_POL + sn * 4) ? 4096 : 12288);
            mbar_expect_tx(bars + B_R * 8, 24576);
#pragma unroll 1
            for (int g = 0; g < 3; g++) bulk_g2s(sb + C_M + g * 8192, src + g * 16384, 8192, bars + B_R * 8);
          }
          __syncwarp();
          mbar_wait(bars + B_R * 8, nretry++ & 1, 49);
        } while (bar_or(NB_S, 128, scan(scan(scan(0, ma), ma + 8192), ma + 16384) == ~0u));
        bar_arrive(NB_V, 384);
        if (st > DELTA) {
          gate_p += BUMP_P;
          if (t == 0) sts32(sb + C_INFO + 20, lds32(sb + C_INFO + 20) + BUMP_M);
          __syncwarp();
        }
      }
      STAT(9, clk32() - tref) STAT(5, c_g0 - tref) STAT(6, it) STAT(7, c_g1 - tref) STAT(8, c_g2 - tref)
      TR(13)
      TRV(15, it)
      st_rlx32(Mw + (st & 3) * 65536, ~0u);
    }
  }
}

__device__ __forceinline__ void chain_dma(const uint32_t sb, const int w, const int lane, const uint32_t rank, const int h) {
  const uint32_t bars = sb + C_BAR;
  bar_sync(NB_ALL, 512);
  bar_sync(NB_ALL, 512);
  cluster_sync();
  if (w == 12) {
    u64 best = 0;
    uint32_t npatch = 0;
#pragma unroll 1
    for (int st = -1; st < NSTEP; st++) {
      const int sg = st - DELTA;
      uint32_t info = 0;
      if (st >= 0) {
        if (sg >= 0) {
          const u64 k = wait_keys(g_fl.key[0][sg], lane, 50);
          if (k > best) { best = k; info = 4 | ((key_token(k) >> 3) & 3); }
        }
        TR(0)
        if (st > 0) mbar_wait(bars + B_P1 * 8, (st - 1) & 1, 51);
        sts32(sb + C_INFO + (st & 1) * 4, info);
        if (sg >= 0) {
          if (XGATE == 3) mbar_wait(bars + B_X * 8, (st - 1) & 1, 58);
          else if ((int)lds32(sb + C_INFO + 8) < st - 1) mbar_gate(bars + (B_M0 + XGATE) * 8, (st - 1) & 1);
          TR(1)
          if (lane == 0) {
            fence_async_glb();
            mbar_expect_tx(bars + B_XL2 * 8, 32768);
            bulk_g2s(sb + C_X + 32768, g_xs[1] + (size_t)sg * 32768, 32768, bars + B_XL2 * 8);
          }
          __syncwarp();
          mbar_wait(bars + B_XL2 * 8, sg & 1, 52);
        }
        TR(2)
        bar_arrive(NB_W0, 416);
        mbar_wait(bars + B_XF * 8, st & 1, 53);
      }
      if (st + 1 < NSEG) {
        if (lane == 0) {
          mbar_expect_tx(bars + B_XL1 * 8, 32768);
          bulk_g2s(sb + C_X, g_xs[0] + (size_t)(st + 1) * 32768, 32768, bars + B_XL1 * 8);
        }
        __syncwarp();
        mbar_wait(bars + B_XL1 * 8, (st + 1) & 1, 57);
      }
      TR(3)
      bar_arrive(NB_X1, 288);
      if (__builtin_expect(info, 0)) {
        if (npatch > 0) mbar_wait(bars + B_P3 * 8, (npatch - 1) & 1, 55);
        npatch++;
        wait_count(g_fl.patch[sg], 1, 56);
        if (lane == 0) {
          fence_async_glb();
          mbar_expect_tx(bars + B_XL3 * 8, 8192);
          bulk_g2s(sb + C_X + 65536, g_patch + (size_t)sg * 8192, 8192, bars + B_XL3 * 8);
        }
        __syncwarp();
      }
    }
  } else if (w == 13) {
    constexpr uint32_t NP = 8192 / SHIP;
    const uint32_t o = (lane >> 1) * SHIP, own = sb + C_Q + rank * 10240, bt = bars + B_T * 8;
    const uint32_t d2 = 1 + (lane & 1);
    const uint32_t src2 = (rank == 0 ? sb + C_SA : rank == 1 ? own : sb + C_SB) + o;
    const uint32_t skip = (lane & 1) ? 4 | (o >> 11) : 8;
    uint32_t npatch = 0;
#pragma unroll 1
    for (int st = 0; st < NSTEP; st++) {
      mbar_wait(bars + (SHIPLATE ? B_P1 : B_P2) * 8, st & 1, 62);
      fence_async_smem();
      if (st > 0) mbar_wait(bars + B_F * 8, (st - 1) & 1, 60);
      const uint32_t info = lds32(sb + C_INFO + (st & 1) * 4);
      TR(2)
      if (st < NSEG && rank != 0 && lane < 2 * NP && d2 == 1) bulk_s2r(mapa_u32(own + o, 0), sb + C_SA + o, SHIP, mapa_u32(bt, 0));
      __syncwarp();
      TR(3)
      mbar_wait(bars + B_P1 * 8, st & 1, 61);
      fence_async_smem();
      TR(0)
      if (st >= DELTA && lane < 2 * NP && d2 != rank && info != skip) bulk_s2r(mapa_u32(own + o, d2), src2, SHIP, mapa_u32(bt, d2));
      __syncwarp();
      TR(1)
      if (__builtin_expect(info, 0)) {
        mbar_wait(bars + B_P3 * 8, npatch & 1, 63);
        npatch++;
        fence_async_smem();
        if (rank != 2 && lane == 0) bulk_s2r(mapa_u32(own + (info & 3) * 2048, 2), sb + C_SP, 2048, mapa_u32(bt, 2));
        __syncwarp();
      }
    }
  } else if (w == 14) {
    const int s0 = rank == 0 ? 0 : DELTA;
    mbar_expect_tx_z(bars + B_T * 8, s0 == 0 ? 16384 : 0, lane);
#pragma unroll 1
    for (int st = 0; st < NSTEP; st++) {
      const int sg = st - s0;
      const bool act = (unsigned)sg < (unsigned)NSEG;
      mbar_wait(bars + B_OT * 8, st & 1, 70);
      fence_async_smem();
      if (OGATE >= 0 && st < NSTEP - 1) mbar_wait(bars + (OGATE > 0 ? B_M0 + OGATE - 1 : B_F) * 8, (st + (OGATE > 0)) & 1, 71);
      TR(0)
      if (lane == 0) {
        if (act) bulk_s2g(g_O[rank] + ((size_t)(sg & (OSLOTS - 1)) * 32 + h) * 8192, sb + C_OT, 8192);
        asm volatile("cp.async.bulk.commit_group;" ::: "memory");
        asm volatile("cp.async.bulk.wait_group.read 0;" ::: "memory");
        mbar_expect_tx(bars + B_T * 8, (unsigned)(sg + 1) < (unsigned)NSEG ? 16384 : 0);
        asm volatile("cp.async.bulk.wait_group 0;" ::: "memory");
        if (act) red_release(&g_fl.oflag[rank][sg][h >> 2]);
      }
      __syncwarp();
      TR(1)
    }
  } else {
    mbar_arrive_z(bars + B_M0 * 8, lane); mbar_arrive_z(bars + B_M1 * 8, lane); mbar_arrive_z(bars + B_M2 * 8, lane);
    const uint32_t gate_g = GATE_G;
#pragma unroll 1
    for (int st = 0; st < NSTEP; st++) {
      mbar_wait(bars + B_M2 * 8, st & 1, 74);
      sts32(sb + C_INFO + 8, st);
      if (st == NSTEP - 1) break;
      mbar_wait(bars + B_X * 8, st & 1, 75);
      const uint32_t now = gtime() & ~31u, tag = (st + 1) & 31;
      uint32_t s0, s1, s2;
      int it = 0;
#pragma unroll 1
      do {
        s0 = ld_rlx32(&g_fl.stamp[lane]) ^ tag; s1 = ld_rlx32(&g_fl.stamp[32 + lane]) ^ tag; s2 = ld_rlx32(&g_fl.stamp[64 + lane]) ^ tag;
        give_up(it++, SPIN_LIMIT, 76);
      } while (__any_sync(~0u, ((s0 | s1 | s2) & 31) != 0));
      const uint32_t tref = now + __reduce_max_sync(~0u, __vimax3_s32((int)(s0 - now), (int)(s1 - now), (int)(s2 - now)));
      const uint32_t g0 = gtime();
      uint32_t g1, c1;
      it = 0;
      do { g1 = gtime(); c1 = clk32(); } while (g1 == g0 && ++it < 64);
      c1 -= (g1 - tref) * 7 / 4;
      sts32(sb + C_INFO + 12, c1);
      TR(0)
      bar_arrive(NB_TA, 160);
      const int sn = (st + 1) & 3;
      const uint8_t* src = (const uint8_t*)g_M + sn * 65536 + (lds32(sb + C_POL + sn * 4) ? 4096 : 12288);
      c1 += lds32(sb + C_INFO + 20);
      const int d = (int)(c1 - 600 - clk32());
      if (d > 0) __nanosleep(d / 4);
#pragma unroll 1
      for (int g = 0; g < 3; g++) {
        mbar_expect_tx_z(bars + (B_M0 + g) * 8, 8192, lane);
        wait_clock(c1 + g * gate_g);
        if (lane == 0) bulk_g2s(sb + C_M + g * 8192, src + g * 16384, 8192, bars + (B_M0 + g) * 8);
        __syncwarp();
        TR(1 + g)
      }
    }
  }
}

__global__ void __cluster_dims__(3, 1, 1) __launch_bounds__(512, 1)
chain_kernel(const bf16* __restrict__ Wq, const bf16* __restrict__ Wk, const bf16* __restrict__ Wv,
             const bf16* __restrict__ Wo, const bf16* __restrict__ mem0) {
  extern __shared__ __align__(1024) uint8_t smem_raw[];
  const uint32_t sb = (smem_u32(smem_raw) + 1023) & ~1023u;
  const int tid = threadIdx.x, lane = tid & 31;
  const int w = __shfl_sync(~0u, tid >> 5, 0);
  uint32_t rank;
  asm volatile("mov.u32 %0, %%cluster_ctarank;" : "=r"(rank));
  const int h = blockIdx.x / 3;
  asm volatile("griddepcontrol.launch_dependents;" ::: "memory");
  TG(0)
  if (tid == 0) {
    const uint32_t bars = sb + C_BAR;
    mbar_init(bars + B_M0 * 8, 1); mbar_init(bars + B_M1 * 8, 1); mbar_init(bars + B_M2 * 8, 1); mbar_init(bars + B_R * 8, 1);
    mbar_init(bars + B_X * 8, 9); mbar_init(bars + B_O * 8, 2); mbar_init(bars + B_T * 8, 1); mbar_init(bars + B_F * 8, 2);
    mbar_init(bars + B_XL1 * 8, 1); mbar_init(bars + B_XL2 * 8, 1); mbar_init(bars + B_XL3 * 8, 1);
    mbar_init(bars + B_P1 * 8, 8); mbar_init(bars + B_P2 * 8, 8); mbar_init(bars + B_P3 * 8, 8); mbar_init(bars + B_OT * 8, 2); mbar_init(bars + B_XF * 8, 8);
    asm volatile("fence.mbarrier_init.release.cluster;" ::: "memory");
  }
  {
    const bf16* W1 = (rank == 0 ? Wq : rank == 1 ? Wk : Wv) + h * 128;
#pragma unroll 4
    for (int cidx = tid; cidx < 512 * 16; cidx += 512) {
      const int d = cidx >> 4, q = cidx & 15;
      cp16(sb + C_X + d * W_STRIDE + q * 16, W1 + (size_t)d * HD + q * 8);
    }
    const int nt = rank == 2 ? 2 : 3;
    for (int cidx = tid; cidx < nt * 1024; cidx += 512) {
      const int tl = cidx >> 10, e = (cidx >> 3) & 127, q = cidx & 7;
      const int es = (e & ~30) | ((e & 6) << 2) | ((e >> 2) & 6);
      cp16(sb + C_WO + tl * 16384 + e * 128 + ((q ^ (e & 7)) << 4), Wo + (size_t)(h * 128 + es) * DM + (tl * 3 + rank) * 64 + q * 8);
    }
    asm volatile("cp.async.commit_group;" ::: "memory");
    if (lane == 0) {
      if (w < 4) sts32(sb + C_POL + w * 4, probe_polarity(g_M + w * 16384 + (blockIdx.x & 31) * 32));
      else if (w == 4) {
        const int u = (rank == 2 ? 0 : rank + 1) * 32 + h;
        const uint32_t pol = probe_polarity(g_P + u * 4096);
        sts32(sb + C_POL + 16, pol);
        st_rlx32(&g_fl.pol[u], pol + 1);
      }
    }
    asm volatile("cp.async.wait_group 0;" ::: "memory");
    fence_async_smem();
    __syncthreads();
  }
  if (w < 8) {
    reg_inc<184>();
    chain_proj(sb, w, lane, rank);
    TG(1)
    TRDUMP
    cluster_sync();
  } else if (w < 12) {
    reg_dec<120>();
    chain_mem(sb, w, lane, rank, h, mem0);
    STATDUMP
    TRDUMP
    cluster_sync();
  } else {
    reg_dec<24>();
    chain_dma(sb, w, lane, rank, h);
    TRDUMP
    cluster_sync();
  }
}
#undef TRC
#undef TRS

constexpr int K_O = 0;
constexpr int K_IN = 98304;
constexpr int K_FFN = K_IN + 49152;
constexpr int K_BAR = K_FFN + 8192;
constexpr int K_SMEM = K_BAR + 256 + 1024 + TREXTRA;
static_assert(512 * W_STRIDE <= K_FFN, "staging");
enum { KB_FULL = 0, KB_EMPTY = 3, KB_IN = 6, KB_OK = 9 };
#define GATE_R 300
struct WorkerParams {
  const bf16 *x0, *Wo, *w_r, *w_gate, *w_up, *w_down;
  bf16* out;
};
#define TRC (96 + blockIdx.x)
#define TRS (K_BAR + 256)

template <int N> __device__ __forceinline__ void halve(float (&g)[16], int lane) {
  const bool up = lane & (2 * N);
#pragma unroll
  for (int i = 0; i < N; i++) g[i] = (up ? g[N + i] : g[i]) + __shfl_xor_sync(~0u, up ? g[i] : g[N + i], 2 * N);
}
__device__ __forceinline__ void ffn_slice(const WorkerParams& prm, uint32_t sf, int t, const bf16* yrow, int ev) {
  const int lane = t & 31, c = t >> 5, cta = blockIdx.x;
  const int nu = cta < 32 ? 3 : 4, j0 = cta < 32 ? cta * 48 : 1536 + (cta - 32) * 64;
  const uint32_t sy = sf, sr = sf + 2048, sh = sf + 4096, sd = sf + 4608;
  {
    const uint2 v = ld_rlx64(yrow + t * 4);
    sts128(sy + t * 16, make_uint4(v.x << 16, v.x & 0xffff0000u, v.y << 16, v.y & 0xffff0000u));
  }
  bar_sync(4, 128);
#pragma unroll 1
  for (int u = 0; u < nu; u++) {
    const size_t o = (size_t)(t >> 1) * FF + j0 + u * 16 + (t & 1) * 8;
    float g[16];
#pragma unroll
    for (int i = 0; i < 16; i++) g[i] = 0.f;
#pragma unroll 1
    for (int k0 = 0; k0 < 8; k0 += 4) {
      uint4 a[4], b[4];
#pragma unroll
      for (int k = 0; k < 4; k++) {
        a[k] = __ldg((const uint4*)(prm.w_gate + o + (size_t)(k0 + k) * 64 * FF));
        b[k] = __ldg((const uint4*)(prm.w_up + o + (size_t)(k0 + k) * 64 * FF));
      }
#pragma unroll
      for (int k = 0; k < 4; k++) {
        const float yv = __uint_as_float(lds32(sy + ((t >> 1) + (k0 + k) * 64) * 4));
        g[0] += yv * bf_lo(a[k].x); g[1] += yv * bf_hi(a[k].x); g[2] += yv * bf_lo(a[k].y); g[3] += yv * bf_hi(a[k].y);
        g[4] += yv * bf_lo(a[k].z); g[5] += yv * bf_hi(a[k].z); g[6] += yv * bf_lo(a[k].w); g[7] += yv * bf_hi(a[k].w);
        g[8] += yv * bf_lo(b[k].x); g[9] += yv * bf_hi(b[k].x); g[10] += yv * bf_lo(b[k].y); g[11] += yv * bf_hi(b[k].y);
        g[12] += yv * bf_lo(b[k].z); g[13] += yv * bf_hi(b[k].z); g[14] += yv * bf_lo(b[k].w); g[15] += yv * bf_hi(b[k].w);
      }
    }
    halve<8>(g, lane); halve<4>(g, lane); halve<2>(g, lane); halve<1>(g, lane);
    sts32(sr + c * 512 + ((lane >> 4) * 64 + u * 16 + (lane & 1) * 8 + ((lane >> 1) & 7)) * 4, __float_as_uint(g[0]));
  }
  const bf16* wd = prm.w_down + (size_t)(j0 + (t >> 6)) * DM + (t & 63) * 8;
  uint4 d[8];
#pragma unroll
  for (int k = 0; k < 8; k++) d[k] = __ldg((const uint4*)(wd + (size_t)k * 2 * DM));
  bar_sync(4, 128);
  if (t < nu * 16) {
    float g = 0.f, u = 0.f;
#pragma unroll
    for (int i = 0; i < 4; i++) { g += __uint_as_float(lds32(sr + i * 512 + t * 4)); u += __uint_as_float(lds32(sr + i * 512 + 256 + t * 4)); }
    g = round_bf16(g); u = round_bf16(u);
    const float sg = round_bf16(g / (1.f + __expf(-g)));
    sts32(sh + t * 4, __float_as_uint(round_bf16(sg * u)));
  }
  bar_sync(4, 128);
  float acc[8];
#pragma unroll
  for (int i = 0; i < 8; i++) acc[i] = 0.f;
#pragma unroll 1
  for (int u = 0; u < nu; u++) {
#pragma unroll
    for (int k = 0; k < 8; k++) {
      const float hv = __uint_as_float(lds32(sh + (u * 16 + k * 2 + (t >> 6)) * 4));
      acc[0] += hv * bf_lo(d[k].x); acc[1] += hv * bf_hi(d[k].x); acc[2] += hv * bf_lo(d[k].y); acc[3] += hv * bf_hi(d[k].y);
      acc[4] += hv * bf_lo(d[k].z); acc[5] += hv * bf_hi(d[k].z); acc[6] += hv * bf_lo(d[k].w); acc[7] += hv * bf_hi(d[k].w);
      if (u + 1 < nu) d[k] = __ldg((const uint4*)(wd + (size_t)((u + 1) * 16 + k * 2) * DM));
    }
  }
  {
    const bool up = t >= 64;
    sts128(sd + (t & 63) * 32 + (up ? 0 : 16), up ? make_uint4(__float_as_uint(acc[0]), __float_as_uint(acc[1]), __float_as_uint(acc[2]), __float_as_uint(acc[3]))
                                                  : make_uint4(__float_as_uint(acc[4]), __float_as_uint(acc[5]), __float_as_uint(acc[6]), __float_as_uint(acc[7])));
    bar_sync(4, 128);
    const uint4 o = lds128(sd + (t & 63) * 32 + (up ? 16 : 0));
    asm volatile("red.relaxed.gpu.global.add.v4.f32 [%0], {%1,%2,%3,%4};" ::"l"(&g_fl.upd[ev][(t & 63) * 8 + (up ? 4 : 0)]),
                 "f"((up ? acc[4] : acc[0]) + __uint_as_float(o.x)), "f"((up ? acc[5] : acc[1]) + __uint_as_float(o.y)),
                 "f"((up ? acc[6] : acc[2]) + __uint_as_float(o.z)), "f"((up ? acc[7] : acc[3]) + __uint_as_float(o.w)) : "memory");
  }
  bar_sync(4, 128);
  if (t == 0) red_release(g_fl.ffncnt[ev]);
}
__device__ __forceinline__ Row ffn_finish(int ver, int ev, u64 key, int lane) {
  const int tok = key_token(key);
  Row x = load_row(g_xr[ver] + (size_t)tok * DM, lane);
  const Row y = load_row(g_y[ver] + (size_t)tok * DM, lane);
  const float sig = round_bf16(1.f / (1.f + __expf(-key_score(key))));
  wait_count(g_fl.ffncnt[ev], NWORK, 80);
#pragma unroll
  for (int q = 0; q < 4; q++) {
    const uint4 u = ld_rlx128(&g_fl.upd[ev][q * 128 + lane * 4]);
    const uint32_t a = pack_bf16(__uint_as_float(u.x), __uint_as_float(u.y)), b = pack_bf16(__uint_as_float(u.z), __uint_as_float(u.w));
    x.w[2 * q] = add_bf16x2(x.w[2 * q], add_bf16x2(y.w[2 * q], pack_bf16(bf_lo(a) * sig, bf_hi(a) * sig)));
    x.w[2 * q + 1] = add_bf16x2(x.w[2 * q + 1], add_bf16x2(y.w[2 * q + 1], pack_bf16(bf_lo(b) * sig, bf_hi(b) * sig)));
  }
  return x;
}

__global__ void __launch_bounds__(512, 1) worker_kernel(const __grid_constant__ WorkerParams prm) {
  extern __shared__ __align__(1024) uint8_t smem_raw[];
  const uint32_t sb = (smem_u32(smem_raw) + 1023) & ~1023u;
  const int tid = threadIdx.x, lane = tid & 31;
  const int w = __shfl_sync(~0u, tid >> 5, 0);
  const int me = blockIdx.x, kb = me >> 2, cb = me & 3;
  const bool full = me < 32;
  const uint32_t bars = sb + K_BAR;
  TG(0)
  if (tid == 0) {
    for (int v = 0; v < 3; v++) { mbar_init(bars + (KB_FULL + v) * 8, 1); mbar_init(bars + (KB_EMPTY + v) * 8, 2); mbar_init(bars + (KB_IN + v) * 8, 1); mbar_init(bars + (KB_OK + v) * 8, 1); }
    asm volatile("fence.mbarrier_init.release.cluster;" ::: "memory");
  }
  if (full) {
    const bf16* W1 = prm.Wo + (size_t)kb * 512 * DM + cb * 128;
#pragma unroll 4
    for (int cidx = tid; cidx < 512 * 16; cidx += 512) {
      const int d = cidx >> 4, q = cidx & 15;
      cp16(sb + d * W_STRIDE + q * 16, W1 + (size_t)d * DM + q * 8);
    }
    asm volatile("cp.async.commit_group;" ::: "memory");
    asm volatile("cp.async.wait_group 0;" ::: "memory");
  }
  fence_async_smem();
  __syncthreads();
  if (w < 8) {
    reg_inc<176>();
    if (full) {
      uint32_t wA[32][4];
      load_wfrags(wA, sb, w, lane);
      fence_async_smem();
      bar_sync(5, 384);
      float* pw = &g_part[0][0] + ((lane & 3) * 2 * 8 + kb) * DM + cb * 128 + w * 16 + (lane >> 2);
#pragma unroll 1
      for (int n = 0; n < 3 * NSTEP; n++) {
        const int st = n / 3, v = n - st * 3, sg = v ? st - DELTA : st;
        if ((unsigned)sg >= (unsigned)NSEG) continue;
        float d[16];
        mbar_wait(bars + (KB_FULL + v) * 8, sg & 1, 81);
        TR(4 * v)
        const uint64_t db = mk_desc(sb + K_O + v * 32768, 128, 2048, 0);
        wg_fence();
#pragma unroll
        for (int ks = 0; ks < 32; ks++) {
          if (ks == 0) wg_rs32<0, 0>(d, wA[ks], db);
          else wg_rs32<0, 1>(d, wA[ks], db + (ks >> 3) * 512 + (ks & 7) * 16);
        }
        wg_commit();
        wg_wait<0>();
        acc_fence(d);
        TR(4 * v + 1)
        mbar_arrive_z(bars + (KB_EMPTY + v) * 8, tid & 127);
        if (sg > 0) mbar_wait(bars + (KB_OK + v) * 8, (sg - 1) & 1, 82);
        float* p = pw + (size_t)(v * 2 + (sg & 1)) * (32 * 8 * DM);
        const uint32_t tag = ((sg >> 1) & 1) ^ 1;
#pragma unroll
        for (int j = 0; j < 4; j++) {
          st_rlx32(p + (8 * j) * 8 * DM, (__float_as_uint(d[4 * j]) & ~1u) | tag);
          st_rlx32(p + (8 * j) * 8 * DM + 8, (__float_as_uint(d[4 * j + 2]) & ~1u) | tag);
          st_rlx32(p + (8 * j + 1) * 8 * DM, (__float_as_uint(d[4 * j + 1]) & ~1u) | tag);
          st_rlx32(p + (8 * j + 1) * 8 * DM + 8, (__float_as_uint(d[4 * j + 3]) & ~1u) | tag);
        }
        bar_arrive(1 + v, 288);
        TR(4 * v + 2)
      }
      TRDUMP
    }
  } else if (w < 12) {
    reg_dec<80>();
    if (full) {
      bar_sync(5, 384);
      if (w == 11) {
#pragma unroll 1
        for (int n = 0; n < 3 * NSTEP; n++) {
          const int st = n / 3, v = n - st * 3, sg = v ? st - DELTA : st;
          if ((unsigned)sg >= (unsigned)NSEG) continue;
          if (sg > 0) mbar_wait(bars + (KB_EMPTY + v) * 8, (sg - 1) & 1, 83);
          wait_count(&g_fl.oflag[v][sg][kb], 4, 84);
          TR(v)
          if (lane == 0) {
            fence_async_glb();
            mbar_expect_tx(bars + (KB_FULL + v) * 8, 32768);
            bulk_g2s(sb + K_O + v * 32768, g_O[v] + ((size_t)(sg & (OSLOTS - 1)) * 32 + kb * 4) * 8192, 32768, bars + (KB_FULL + v) * 8);
          }
          __syncwarp();
        }
      } else {
        const int v = w - 8;
        Row wr = load_row(prm.w_r, lane);
        u64 best = 0;
        uint32_t nin = 0;
#pragma unroll 1
        for (int sg = 0; sg < NSEG; sg++) {
          const int st = v ? sg + DELTA : sg;
          (void)st;
          const int tok = sg * 32 + me;
          const bf16* xin = (v ? g_x2 : prm.x0) + (size_t)tok * DM;
          if (v != 0) {
            const u64 k = wait_keys(g_fl.key[0][sg], lane, 86);
            if (k > best) {
              best = k;
              if (v == 2 && key_token(k) == tok) { wait_count(g_fl.patch[sg], 1, 88); xin = g_x2p + sg * DM; }
            }
          }
          Row x = load_row(xin, lane);
          bar_sync(1 + v, 288);
          TR(0)
          __nanosleep(GATE_R);
          float a[16];
          const uint32_t flip = ((sg >> 1) & 1) ? ~0u : 0u;
          for (int it = 0;; it++) {
            TR(1)
            if (lane == 0) {
              fence_async_glb();
              mbar_expect_tx(bars + (KB_IN + v) * 8, 16384);
              bulk_g2s(sb + K_IN + v * 16384, &g_part[v][0] + (size_t)((sg & 1) * 32 + me) * 8 * DM, 16384, bars + (KB_IN + v) * 8);
            }
            __syncwarp();
#pragma unroll
            for (int i = 0; i < 16; i++) a[i] = 0.f;
            uint32_t ok = 1;
            mbar_wait(bars + (KB_IN + v) * 8, nin++ & 1, 87);
            TR(2)
#pragma unroll 1
            for (int k = 0; k < 8; k += 2) {
              uint4 p[8];
#pragma unroll
              for (int q = 0; q < 8; q++) p[q] = lds128(sb + K_IN + v * 16384 + k * 2048 + q * 512 + lane * 16);
#pragma unroll
              for (int q = 0; q < 8; q++) asm volatile("" : "+r"(p[q].x), "+r"(p[q].y), "+r"(p[q].z), "+r"(p[q].w));
#pragma unroll
              for (int q = 0; q < 8; q++) {
                float* aq = a + 4 * (q & 3);
                aq[0] += __uint_as_float(p[q].x); aq[1] += __uint_as_float(p[q].y); aq[2] += __uint_as_float(p[q].z); aq[3] += __uint_as_float(p[q].w);
                ok &= and_x(p[q].x, p[q].y, flip) & and_x(p[q].z, p[q].w, flip);
              }
            }
            if (__all_sync(~0u, ok != 0)) { TRV(5, it) break; }
            give_up(it, SPIN_LIMIT, 85);
          }
          mbar_arrive_z(bars + (KB_OK + v) * 8, lane);
          TR(4)
#pragma unroll
          for (int i = 0; i < 8; i++) x.w[i] = add_bf16x2(x.w[i], pack_bf16(a[2 * i], a[2 * i + 1]));
          store_row(g_xr[v] + (size_t)tok * DM, lane, x);
          const Row y = warp_ln(x);
          store_row(g_y[v] + (size_t)tok * DM, lane, y);
          float rr = 0.f, r2 = 0.f;
#pragma unroll
          for (int i = 0; i < 8; i++) {
            asm volatile("" : "+r"(wr.w[i]));
            rr = fmaf(bf_lo(y.w[i]), bf_lo(wr.w[i]), rr); r2 = fmaf(bf_hi(y.w[i]), bf_hi(wr.w[i]), r2);
            x.w[i] = add_bf16x2(x.w[i], y.w[i]);
          }
          rr += r2;
          store_row((v == 0 ? g_x2 : v == 1 ? g_fin : prm.out) + (size_t)tok * DM, lane, x);
          const Row z = warp_ln(x, rr);
          if (v == 0) store_row_img(g_xs[1] + (size_t)(tok >> 3) * 8192, tok & 7, lane, z);
          __syncwarp();
          TR(6)
          if (lane == 0) {
            const uint32_t bb = pack_bf16(0.f, rr), ob = (bb & 0x80000000u) ? ~bb : (bb | 0x80000000u);
            st_release_u64(&g_fl.key[v][sg][me], (u64)ob << 32 | (uint32_t)~tok);
          }
          __syncwarp();
          TR(3)
        }
      }
      TRDUMP
    }
  } else {
    reg_dec<80>();
    const int t = tid - 384;
    {
      const int nu = full ? 3 : 4, j0 = full ? me * 48 : 1536 + (me - 32) * 64;
      for (int i = t; i < 512; i += 128) {
        asm volatile("prefetch.global.L2 [%0];" ::"l"(prm.w_gate + (size_t)i * FF + j0));
        asm volatile("prefetch.global.L2 [%0];" ::"l"(prm.w_gate + (size_t)i * FF + j0 + nu * 16 - 8));
        asm volatile("prefetch.global.L2 [%0];" ::"l"(prm.w_up + (size_t)i * FF + j0));
        asm volatile("prefetch.global.L2 [%0];" ::"l"(prm.w_up + (size_t)i * FF + j0 + nu * 16 - 8));
        if (i < nu * 128) asm volatile("prefetch.global.L2 [%0];" ::"l"(prm.w_down + (size_t)j0 * DM + i * 64));
      }
    }
    u64 best = 0;
#pragma unroll 1
    for (int sg = 0; sg < NSEG; sg++) {
      if (w == 12) {
        u64 k;
        while ((k = wait_keys(g_fl.key[0][sg], lane, 90)) <= best && ++sg < NSEG) {}
        if (lane == 0) asm volatile("st.shared.b64 [%0], %1;" ::"r"(sb + K_FFN + 7232), "l"(sg < NSEG ? k : 0ull) : "memory");
      }
      bar_sync(4, 128);
      u64 k;
      asm volatile("ld.shared.b64 %0, [%1];" : "=l"(k) : "r"(sb + K_FFN + 7232) : "memory");
      if (k == 0) break;
      best = k;
      sg = key_token(k) >> 5;
      const int tok = key_token(k);
      ffn_slice(prm, sb + K_FFN, t, g_y[0] + (size_t)tok * DM, sg);
      if ((tok & 31) == me) {
        uint8_t* dst = g_patch + (size_t)sg * 8192;
        const uint8_t* src = g_xs[1] + (size_t)(tok >> 3) * 8192;
        if (w == 12) {
          const Row x = ffn_finish(0, sg, k, lane);
          store_row(g_x2p + sg * DM, lane, x);
          store_row_img(dst, tok & 7, lane, warp_ln(x));
        } else {
          for (int i = t - 32; i < 512; i += 96)
            if (((i >> 3) & 7) != (tok & 7)) *(uint4*)(dst + i * 16) = ld_rlx128(src + i * 16);
        }
        bar_sync(4, 128);
        if (t == 0) st_release32(g_fl.patch[sg], 1);
      }
    }
    const int sstar = key_token(best) >> 5;
    u64 b2 = 0;
#pragma unroll 1
    for (int sg = w - 12; sg < NSEG; sg += 4) {
      const u64 k = wait_keys(g_fl.key[sg < sstar ? 1 : 2][sg], lane, 91);
      if (k > b2) b2 = k;
      if (sg < sstar && full) {
        (void)wait_keys(g_fl.key[2][sg], lane, 92);
        const size_t o = (size_t)(sg * 32 + me) * DM + lane * 8;
        const uint4 a = ld_rlx128(g_fin + o), b = ld_rlx128(g_fin + o + 256);
        *(uint4*)(prm.out + o) = a; *(uint4*)(prm.out + o + 256) = b;
      }
    }
    if (lane == 0) asm volatile("st.shared.b64 [%0], %1;" ::"r"(sb + K_FFN + 7168 + (w - 12) * 8), "l"(b2) : "memory");
    bar_sync(4, 128);
#pragma unroll
    for (int i = 0; i < 4; i++) {
      u64 k;
      asm volatile("ld.shared.b64 %0, [%1];" : "=l"(k) : "r"(sb + K_FFN + 7168 + i * 8) : "memory");
      if (k > b2) b2 = k;
    }
    const int tok = key_token(b2), ver = (tok >> 5) < sstar ? 1 : 2;
    ffn_slice(prm, sb + K_FFN, t, g_y[ver] + (size_t)tok * DM, NSEG);
    if ((tok & 31) == me && w == 12) {
      store_row(prm.out + (size_t)tok * DM, lane, ffn_finish(ver, NSEG, b2, lane));
    }
  }
}
#undef TRC
#undef TRS

bool g_ready;

}

extern "C" void kernel_launch(void* const* d_in, const int* in_sizes, int n_in, void* d_out, int out_size) {
  (void)in_sizes; (void)n_in; (void)out_size;
  const bf16* x0 = (const bf16*)d_in[0];
  const bf16* mem0 = (const bf16*)d_in[1];
  const bf16* Wq = (const bf16*)d_in[2];
  const bf16* Wk = (const bf16*)d_in[3];
  const bf16* Wv = (const bf16*)d_in[4];
  const bf16* Wo = (const bf16*)d_in[5];
  if (!g_ready) {
    cudaFuncSetAttribute(worker_kernel, cudaFuncAttributeMaxDynamicSharedMemorySize, K_SMEM);
    cudaFuncSetAttribute(chain_kernel, cudaFuncAttributeMaxDynamicSharedMemorySize, C_SMEM);
    g_ready = true;
  }
  cudaStream_t st = cudaStreamPerThread;
  prep_kernel<<<NTOK / 8, 256, 0, st>>>(x0);
  chain_kernel<<<96, 512, C_SMEM, st>>>(Wq, Wk, Wv, Wo, mem0);
  cudaLaunchAttribute pdl[1];
  pdl[0].id = cudaLaunchAttributeProgrammaticStreamSerialization;
  pdl[0].val.programmaticStreamSerializationAllowed = 1;
  WorkerParams wp;
  wp.x0 = x0; wp.Wo = Wo; wp.w_r = (const bf16*)d_in[8]; wp.w_gate = (const bf16*)d_in[9]; wp.w_up = (const bf16*)d_in[10];
  wp.w_down = (const bf16*)d_in[11]; wp.out = (bf16*)d_out;
  cudaLaunchConfig_t cfg = {};
  cfg.gridDim = dim3(NWORK); cfg.blockDim = dim3(512); cfg.dynamicSmemBytes = K_SMEM; cfg.stream = st;
  cfg.attrs = pdl; cfg.numAttrs = 1;
  cudaLaunchKernelEx(&cfg, worker_kernel, wp);
}
```

```cpp
#include <cuda_runtime.h>
#include <cuda_bf16.h>
#include <stdint.h>

namespace {

typedef __nv_bfloat16 bf16;
typedef unsigned long long u64;

constexpr int NTOK = 2048, DM = 512, HD = 4096, NSEG = 64, FF = 1792;
#define DELTA 4
constexpr int NSTEP = NSEG + DELTA;
constexpr int SPIN_LIMIT = 40000;
constexpr int MBAR_LIMIT = 20000;
constexpr int NWORK = 36;
constexpr int OSLOTS = 8;

__device__ __align__(1024) uint8_t g_xs[2][NSEG * 32768];
__device__ __align__(1024) uint8_t g_patch[NSEG * 8192];
__device__ __align__(1024) uint8_t g_O[3][OSLOTS * 32 * 8192];
__device__ __align__(1024) uint8_t g_part[3][2 * 32 * 8192];
__device__ __align__(1024) bf16 g_rows[3][3][NTOK * DM];
__device__ __align__(1024) bf16 g_x2p[NSEG * DM];
__device__ __align__(65536) uint32_t g_M[4 * 16384];
__device__ __align__(65536) uint32_t g_P[96 * 4096];
struct Flags {
  uint32_t pol[96];
  uint32_t stamp[96];
  uint32_t oflag[3][NSEG][8];
  uint32_t ffncnt[NSEG + 1][8];
  uint32_t patch[NSEG][8];
  u64 key[3][NSEG][32];
  float upd[NSEG + 1][DM];
};
__device__ __align__(1024) Flags g_fl;
#define TR(e)
#define TRV(e, v)
#define TG(i)
#define TRDUMP
#define TREXTRA 0

#define STAT(e, v)
#define STATC(n)
#define STATDUMP
__device__ __forceinline__ uint32_t smem_u32(const void* p) { return (uint32_t)__cvta_generic_to_shared(p); }
__device__ __forceinline__ uint32_t pack_bf16(float lo, float hi) {
  uint32_t r;
  asm("cvt.rn.bf16x2.f32 %0, %1, %2;" : "=r"(r) : "f"(hi), "f"(lo));
  return r;
}
__device__ __forceinline__ float bf_lo(uint32_t v) { return __uint_as_float(v << 16); }
__device__ __forceinline__ float bf_hi(uint32_t v) { return __uint_as_float(v & 0xffff0000u); }
__device__ __forceinline__ float ex2_fast(float x) { float y; asm("ex2.approx.ftz.f32 %0, %1;" : "=f"(y) : "f"(x)); return y; }
__device__ __forceinline__ float rcp_fast(float x) { float y; asm("rcp.approx.ftz.f32 %0, %1;" : "=f"(y) : "f"(x)); return y; }
__device__ __forceinline__ float round_bf16(float x) { return __bfloat162float(__float2bfloat16_rn(x)); }
__device__ __forceinline__ uint32_t clk32() { uint32_t t; asm volatile("mov.u32 %0, %%clock;" : "=r"(t) :: "memory"); return t; }

__device__ __forceinline__ void mma16816(float (&d)[4], uint32_t a0, uint32_t a1, uint32_t a2, uint32_t a3,
                                         uint32_t b0, uint32_t b1) {
  asm("mma.sync.aligned.m16n8k16.row.col.f32.bf16.bf16.f32 {%0,%1,%2,%3}, {%4,%5,%6,%7}, {%8,%9}, {%0,%1,%2,%3};"
      : "+f"(d[0]), "+f"(d[1]), "+f"(d[2]), "+f"(d[3])
      : "r"(a0), "r"(a1), "r"(a2), "r"(a3), "r"(b0), "r"(b1));
}
__device__ __forceinline__ void ldsm4t(uint32_t (&r)[4], uint32_t addr) {
  asm volatile("ldmatrix.sync.aligned.m8n8.x4.trans.shared.b16 {%0,%1,%2,%3}, [%4];"
               : "=r"(r[0]), "=r"(r[1]), "=r"(r[2]), "=r"(r[3]) : "r"(addr) : "memory");
}
__device__ __forceinline__ void stsm4(uint32_t addr, uint32_t a, uint32_t b, uint32_t c, uint32_t d) {
  asm volatile("stmatrix.sync.aligned.m8n8.x4.shared.b16 [%0], {%1,%2,%3,%4};" ::"r"(addr), "r"(a), "r"(b), "r"(c), "r"(d) : "memory");
}
__device__ __forceinline__ void stsm4t(uint32_t addr, uint32_t a, uint32_t b, uint32_t c, uint32_t d) {
  asm volatile("stmatrix.sync.aligned.m8n8.x4.trans.shared.b16 [%0], {%1,%2,%3,%4};" ::"r"(addr), "r"(a), "r"(b), "r"(c), "r"(d) : "memory");
}
__device__ __forceinline__ uint4 lds128(uint32_t a) {
  uint4 v; asm volatile("ld.shared.v4.b32 {%0,%1,%2,%3}, [%4];" : "=r"(v.x), "=r"(v.y), "=r"(v.z), "=r"(v.w) : "r"(a) : "memory"); return v;
}
__device__ __forceinline__ uint32_t lds32(uint32_t a) { uint32_t v; asm volatile("ld.shared.b32 %0, [%1];" : "=r"(v) : "r"(a) : "memory"); return v; }
__device__ __forceinline__ void sts32(uint32_t a, uint32_t x) { asm volatile("st.shared.b32 [%0], %1;" ::"r"(a), "r"(x) : "memory"); }
__device__ __forceinline__ void sts128(uint32_t a, uint4 v) {
  asm volatile("st.shared.v4.b32 [%0], {%1,%2,%3,%4};" ::"r"(a), "r"(v.x), "r"(v.y), "r"(v.z), "r"(v.w) : "memory");
}
__device__ __forceinline__ void cp16(uint32_t dst, const void* src) {
  asm volatile("cp.async.cg.shared.global [%0], [%1], 16;" ::"r"(dst), "l"(src) : "memory");
}
__device__ __forceinline__ void mbar_init(uint32_t mbar, uint32_t cnt) {
  asm volatile("mbarrier.init.shared.b64 [%0], %1;" ::"r"(mbar), "r"(cnt) : "memory");
}
__device__ __forceinline__ void mbar_expect_tx(uint32_t mbar, uint32_t bytes) {
  asm volatile("mbarrier.arrive.expect_tx.shared.b64 _, [%0], %1;" ::"r"(mbar), "r"(bytes) : "memory");
}
__device__ __forceinline__ void mbar_arrive_z(uint32_t mbar, uint32_t z) {
  asm volatile("{ .reg .pred p; setp.eq.u32 p, %1, 0; @p mbarrier.arrive.shared.b64 _, [%0]; }" ::"r"(mbar), "r"(z) : "memory");
}
__device__ __forceinline__ void mbar_expect_tx_z(uint32_t mbar, uint32_t bytes, uint32_t z) {
  asm volatile("{ .reg .pred p; setp.eq.u32 p, %2, 0; @p mbarrier.arrive.expect_tx.shared.b64 _, [%0], %1; }" ::"r"(mbar), "r"(bytes), "r"(z) : "memory");
}
__device__ __forceinline__ void mbar_arrive_remote_z(uint32_t mbar, uint32_t z) {
  asm volatile("{ .reg .pred p; setp.eq.u32 p, %1, 0; @p mbarrier.arrive.shared::cluster.b64 _, [%0]; }" ::"r"(mbar), "r"(z) : "memory");
}
__device__ __forceinline__ bool mbar_try(uint32_t mbar, uint32_t par) {
  uint32_t ok;
  asm volatile("{ .reg .pred p; mbarrier.try_wait.parity.shared::cta.b64 p, [%1], %2; selp.u32 %0, 1, 0, p; }"
               : "=r"(ok) : "r"(mbar), "r"(par) : "memory");
  return ok;
}
__device__ __forceinline__ void fail(int) { __trap(); }
__device__ __forceinline__ void give_up(int it, int limit, int code) { if (it > limit) fail(code); }
__device__ __forceinline__ void mbar_wait(uint32_t mbar, uint32_t par, int code) {
  asm volatile("{ .reg .pred p; .reg .b32 n; mov.b32 n, %2;\n"
               "W: mbarrier.try_wait.parity.shared::cta.b64 p, [%0], %1; @p bra D;\n"
               "add.s32 n, n, -1; setp.eq.s32 p, n, 0; @p trap; bra W;\n"
               "D: }" ::"r"(mbar), "r"(par), "n"(MBAR_LIMIT) : "memory");
}
__device__ __forceinline__ void mbar_gate(uint32_t mbar, uint32_t par) {
  const uint32_t t0 = clk32();
  while (!mbar_try(mbar, par) && clk32() - t0 < 20000) {}
}
__device__ __forceinline__ void bulk_g2s(uint32_t dst, const void* src, uint32_t bytes, uint32_t mbar) {
  asm volatile("cp.async.bulk.shared::cluster.global.mbarrier::complete_tx::bytes [%0], [%1], %2, [%3];"
               ::"r"(dst), "l"(src), "r"(bytes), "r"(mbar) : "memory");
}
__device__ __forceinline__ void bulk_s2r(uint32_t dst, uint32_t src, uint32_t bytes, uint32_t mbar) {
  asm volatile("cp.async.bulk.shared::cluster.shared::cta.mbarrier::complete_tx::bytes [%0], [%1], %2, [%3];"
               ::"r"(dst), "r"(src), "r"(bytes), "r"(mbar) : "memory");
}
__device__ __forceinline__ void bulk_s2g(void* dst, uint32_t src, uint32_t bytes) {
  asm volatile("cp.async.bulk.global.shared::cta.bulk_group [%0], [%1], %2;" ::"l"(dst), "r"(src), "r"(bytes) : "memory");
}
__device__ __forceinline__ void fence_async_smem() { asm volatile("fence.proxy.async.shared::cta;" ::: "memory"); }
__device__ __forceinline__ void fence_async_glb() { asm volatile("fence.proxy.async.global;" ::: "memory"); }
__device__ __forceinline__ void bar_sync(int id, int n) { asm volatile("bar.sync %0, %1;" ::"r"(id), "r"(n) : "memory"); }
__device__ __forceinline__ void bar_arrive(int id, int n) { asm volatile("bar.arrive %0, %1;" ::"r"(id), "r"(n) : "memory"); }
__device__ __forceinline__ void cluster_sync() { asm volatile("barrier.cluster.arrive.release; barrier.cluster.wait.acquire;" ::: "memory"); }
__device__ __forceinline__ uint32_t mapa_u32(uint32_t a, uint32_t r) {
  uint32_t o;
  asm("mapa.shared::cluster.u32 %0, %1, %2;" : "=r"(o) : "r"(a), "r"(r));
  return o;
}
template <int OFF>
__device__ __forceinline__ void st_async32(uint32_t a, uint32_t x, uint32_t mbar) {
  asm volatile("st.async.weak.shared::cluster.mbarrier::complete_tx::bytes.b32 [%0 + %3], %1, [%2];" ::"r"(a), "r"(x), "r"(mbar), "n"(OFF) : "memory");
}
__device__ __forceinline__ uint4 ld_rlx128(const void* p) {
  uint4 v;
  asm volatile("ld.relaxed.gpu.global.v4.u32 {%0,%1,%2,%3}, [%4];" : "=r"(v.x), "=r"(v.y), "=r"(v.z), "=r"(v.w) : "l"(p) : "memory");
  return v;
}
__device__ __forceinline__ uint2 ld_rlx64(const void* p) {
  uint2 v; asm volatile("ld.relaxed.gpu.global.v2.u32 {%0,%1}, [%2];" : "=r"(v.x), "=r"(v.y) : "l"(p) : "memory"); return v;
}
__device__ __forceinline__ uint32_t ld_rlx32(const void* p) {
  uint32_t v; asm volatile("ld.relaxed.gpu.global.u32 %0, [%1];" : "=r"(v) : "l"(p) : "memory"); return v;
}
__device__ __forceinline__ void st_rlx32(void* p, uint32_t a) { asm volatile("st.relaxed.gpu.global.u32 [%0], %1;" ::"l"(p), "r"(a) : "memory"); }
__device__ __forceinline__ void red_release(uint32_t* p) { asm volatile("red.release.gpu.global.add.u32 [%0], 1;" ::"l"(p) : "memory"); }
__device__ __forceinline__ void st_release32(void* p, uint32_t a) { asm volatile("st.release.gpu.global.u32 [%0], %1;" ::"l"(p), "r"(a) : "memory"); }
__device__ __forceinline__ void st_release_u64(void* p, u64 a) { asm volatile("st.release.gpu.global.u64 [%0], %1;" ::"l"(p), "l"(a) : "memory"); }
__device__ __forceinline__ void wait_count(const uint32_t* p, uint32_t val, int code) {
  int it = 0;
  while (ld_rlx32(p) < val) {
    give_up(++it, SPIN_LIMIT, code);
    __nanosleep(40);
  }
}
__device__ __forceinline__ u64 wait_keys(const u64* keys, int lane, int code) {
  u64 k;
  int it = 0;
  while (true) {
    asm volatile("ld.relaxed.gpu.global.u64 %0, [%1];" : "=l"(k) : "l"(keys + lane) : "memory");
    if (__all_sync(~0u, k != 0)) break;
    give_up(++it, SPIN_LIMIT, code);
    __nanosleep(100);
  }
  const uint32_t hi = __reduce_max_sync(~0u, (uint32_t)(k >> 32));
  const uint32_t lo = __reduce_max_sync(~0u, (uint32_t)(k >> 32) == hi ? (uint32_t)k : 0u);
  return (u64)hi << 32 | lo;
}
__device__ __forceinline__ int key_token(u64 k) { return (int)(~(uint32_t)k) & (NTOK - 1); }
__device__ __forceinline__ float key_score(u64 k) {
  const uint32_t ob = (uint32_t)(k >> 32);
  return __uint_as_float((ob & 0x80000000u) ? (ob & 0x7fffffffu) : ~ob);
}

__device__ __forceinline__ uint64_t mk_desc(uint32_t saddr, uint32_t lbo, uint32_t sbo, uint32_t sw) {
  return (uint64_t)((saddr & 0x3FFFF) >> 4) | (uint64_t)(lbo >> 4) << 16 | (uint64_t)(sbo >> 4) << 32 | (uint64_t)sw << 62;
}
template <int N> __device__ __forceinline__ void reg_inc() { asm volatile("setmaxnreg.inc.sync.aligned.u32 %0;" ::"n"(N)); }
template <int N> __device__ __forceinline__ void reg_dec() { asm volatile("setmaxnreg.dec.sync.aligned.u32 %0;" ::"n"(N)); }
__device__ __forceinline__ void wg_fence() { asm volatile("wgmma.fence.sync.aligned;" ::: "memory"); }
__device__ __forceinline__ void wg_commit() { asm volatile("wgmma.commit_group.sync.aligned;" ::: "memory"); }
template <int N> __device__ __forceinline__ void wg_wait() { asm volatile("wgmma.wait_group.sync.aligned %0;" ::"n"(N) : "memory"); }
template <int N> __device__ __forceinline__ void acc_fence(float (&d)[N]) {
#pragma unroll
  for (int i = 0; i < N; i++) asm volatile("" : "+f"(d[i]) :: "memory");
}
#define O4(d, i) "+f"(d[i]), "+f"(d[i + 1]), "+f"(d[i + 2]), "+f"(d[i + 3])
template <int TB, int ACC>
__device__ __forceinline__ void wg_rs8(float (&d)[4], const uint32_t (&a)[4], uint64_t db) {
  asm volatile("wgmma.mma_async.sync.aligned.m64n8k16.f32.bf16.bf16 {%0,%1,%2,%3}, {%4,%5,%6,%7}, %8, %9, 1, 1, %10;"
               : O4(d, 0) : "r"(a[0]), "r"(a[1]), "r"(a[2]), "r"(a[3]), "l"(db), "n"(ACC), "n"(TB));
}
template <int TB, int ACC>
__device__ __forceinline__ void wg_rs24(float (&d)[12], const uint32_t (&a)[4], uint64_t db) {
  asm volatile("wgmma.mma_async.sync.aligned.m64n24k16.f32.bf16.bf16 {%0,%1,%2,%3,%4,%5,%6,%7,%8,%9,%10,%11}, {%12,%13,%14,%15}, %16, %17, 1, 1, %18;"
               : O4(d, 0), O4(d, 4), O4(d, 8) : "r"(a[0]), "r"(a[1]), "r"(a[2]), "r"(a[3]), "l"(db), "n"(ACC), "n"(TB));
}
template <int TB, int ACC>
__device__ __forceinline__ void wg_rs32(float (&d)[16], const uint32_t (&a)[4], uint64_t db) {
  asm volatile("wgmma.mma_async.sync.aligned.m64n32k16.f32.bf16.bf16 {%0,%1,%2,%3,%4,%5,%6,%7,%8,%9,%10,%11,%12,%13,%14,%15}, {%16,%17,%18,%19}, %20, %21, 1, 1, %22;"
               : O4(d, 0), O4(d, 4), O4(d, 8), O4(d, 12) : "r"(a[0]), "r"(a[1]), "r"(a[2]), "r"(a[3]), "l"(db), "n"(ACC), "n"(TB));
}
template <int ACC>
__device__ __forceinline__ void wg_rs64(float (&d)[32], uint32_t a0, uint32_t a1, uint32_t a2, uint32_t a3, uint64_t db) {
  asm volatile("wgmma.mma_async.sync.aligned.m64n64k16.f32.bf16.bf16 {%0,%1,%2,%3,%4,%5,%6,%7,%8,%9,%10,%11,%12,%13,%14,%15,"
               "%16,%17,%18,%19,%20,%21,%22,%23,%24,%25,%26,%27,%28,%29,%30,%31}, {%32,%33,%34,%35}, %36, %37, 1, 1, 0;"
               : O4(d, 0), O4(d, 4), O4(d, 8), O4(d, 12), O4(d, 16), O4(d, 20), O4(d, 24), O4(d, 28)
               : "r"(a0), "r"(a1), "r"(a2), "r"(a3), "l"(db), "n"(ACC));
}
template <int ACC>
__device__ __forceinline__ void wg_ss24(float (&d)[12], uint64_t da, uint64_t db) {
  asm volatile("wgmma.mma_async.sync.aligned.m64n24k16.f32.bf16.bf16 {%0,%1,%2,%3,%4,%5,%6,%7,%8,%9,%10,%11}, %12, %13, %14, 1, 1, 1, 0;"
               : O4(d, 0), O4(d, 4), O4(d, 8) : "l"(da), "l"(db), "n"(ACC));
}
template <int ACC>
__device__ __forceinline__ void wg_ss40(float (&d)[20], uint64_t da, uint64_t db) {
  asm volatile("wgmma.mma_async.sync.aligned.m64n40k16.f32.bf16.bf16 {%0,%1,%2,%3,%4,%5,%6,%7,%8,%9,%10,%11,%12,%13,%14,%15,%16,%17,%18,%19}, %20, %21, %22, 1, 1, 1, 1;"
               : O4(d, 0), O4(d, 4), O4(d, 8), O4(d, 12), O4(d, 16) : "l"(da), "l"(db), "n"(ACC));
}

struct Row { uint32_t w[8]; };
__device__ __forceinline__ uint32_t add_bf16x2(uint32_t a, uint32_t b) {
  uint32_t d; asm("add.rn.bf16x2 %0, %1, %2;" : "=r"(d) : "r"(a), "r"(b)); return d;
}
__device__ __forceinline__ Row warp_ln(const Row& r, float& extra) {
  float x[16];
#pragma unroll
  for (int i = 0; i < 8; i++) { x[2 * i] = bf_lo(r.w[i]); x[2 * i + 1] = bf_hi(r.w[i]); }
  float m = (((x[0] + x[1]) + (x[2] + x[3])) + ((x[4] + x[5]) + (x[6] + x[7]))) + (((x[8] + x[9]) + (x[10] + x[11])) + ((x[12] + x[13]) + (x[14] + x[15])));
  m *= (1.f / 16);
  float v0 = 0.f, v1 = 0.f;
#pragma unroll
  for (int i = 0; i < 16; i += 2) { const float d0 = x[i] - m, d1 = x[i + 1] - m; v0 = fmaf(d0, d0, v0); v1 = fmaf(d1, d1, v1); }
  float v = v0 + v1;
#pragma unroll
  for (int o = 1; o <= 16; o <<= 1) {
    const float mo = __shfl_xor_sync(~0u, m, o), vo = __shfl_xor_sync(~0u, v, o);
    extra += __shfl_xor_sync(~0u, extra, o);
    const float d = mo - m;
    v = fmaf(d * d, 8.f * o, v + vo);
    m = 0.5f * (m + mo);
  }
  const float var = fmaf(v, 1.f / DM, 1e-5f);
  float rs = rsqrtf(var);
  rs = rs * fmaf(-0.5f * var * rs, rs, 1.5f);
  Row y;
#pragma unroll
  for (int i = 0; i < 8; i++) y.w[i] = pack_bf16((x[2 * i] - m) * rs, (x[2 * i + 1] - m) * rs);
  return y;
}
__device__ __forceinline__ Row warp_ln(const Row& r) { float e = 0.f; return warp_ln(r, e); }
__device__ __forceinline__ Row load_row(const bf16* p, int lane) {
  Row r;
#pragma unroll
  for (int q = 0; q < 4; q++) { const uint2 v = ld_rlx64(p + lane * 4 + q * 128); r.w[2 * q] = v.x; r.w[2 * q + 1] = v.y; }
  return r;
}
__device__ __forceinline__ void store_row(bf16* p, int lane, const Row& r) {
#pragma unroll
  for (int q = 0; q < 4; q++) *(uint2*)(p + lane * 4 + q * 128) = make_uint2(r.w[2 * q], r.w[2 * q + 1]);
}
__device__ __forceinline__ void store_row_img(uint8_t* grp, int rr, int lane, const Row& r) {
  uint8_t* p = grp + (lane >> 4) * 1024 + rr * 128 + ((((lane & 15) >> 1) ^ rr) << 4) + (lane & 1) * 8;
#pragma unroll
  for (int q = 0; q < 4; q++) *(uint2*)(p + q * 2048) = make_uint2(r.w[2 * q], r.w[2 * q + 1]);
}

__global__ void __launch_bounds__(256) prep_kernel(const bf16* __restrict__ x0) {
  const int lane = threadIdx.x & 31, row = blockIdx.x * 8 + (threadIdx.x >> 5);
  const Row r = load_row(x0 + (size_t)row * DM, lane);
  const int gt = blockIdx.x * 256 + threadIdx.x, nt = gridDim.x * 256;
  uint4* M = (uint4*)g_M;
  for (int i = gt; i < 4 * 16384 / 4; i += nt) M[i] = make_uint4(~0u, ~0u, ~0u, ~0u);
  uint4* P = (uint4*)g_P;
  for (int i = gt; i < 96 * 4096 / 4; i += nt) P[i] = make_uint4(0, 0, 0, 0);
  uint4* F = (uint4*)&g_fl;
  for (int i = gt; i < (int)(sizeof(Flags) / 16); i += nt) F[i] = make_uint4(0, 0, 0, 0);
  store_row_img(g_xs[0] + (size_t)blockIdx.x * 8192, row & 7, lane, warp_ln(r));
}

constexpr int W_STRIDE = 272;
constexpr int C_WO = 0;
constexpr int C_X = 49152;
constexpr int C_M = C_X + 9 * 8192;
constexpr int C_Q = C_M + 24576;
constexpr int C_K = C_Q + 10240, C_V = C_K + 10240;
constexpr int C_SA = C_V + 10240, C_SB = C_SA + 8192, C_SP = C_SB + 8192;
constexpr int C_O = C_SP + 2048;
constexpr int C_OT = C_O + 6144;
constexpr int C_BAR = C_OT + 8192;
constexpr int C_SMEM = C_BAR + 256 + 1024 + TREXTRA;
static_assert(C_X + 512 * W_STRIDE <= C_BAR, "staging");
enum { B_M0 = 0, B_M1, B_M2, B_R, B_X, B_O, B_T, B_F, B_XL1, B_XL2, B_XL3, B_P1, B_P2, B_P3, B_OT, B_XF, B_NUM };
constexpr int C_INFO = C_BAR + 160, C_POL = C_BAR + 192;
enum { NB_ALL = 0, NB_S, NB_M0, NB_PV, NB_W0, NB_TA, NB_X1, NB_M1, NB_M2, NB_V, NB_RD };
constexpr float SCALE_LOG2E = 0.08838834764831845f * 1.4426950408889634f;
#define N0STEPS 9
#define N2STEPS 12
#define OGATE 3
#define SHIPLATE 0
#define XGATE 3
#define SHIP 1024
#define GATE_P 2700
#define BUMP_P 32
#define BUMP_M 48
#define GATE_W 200
#define GATE_G 200
#define GATE_M 3850
#define HOLE0 29
#define HOLE1 32
#define HOLE2 32
__device__ __forceinline__ uint32_t gtime() { uint32_t t; asm volatile("mov.u32 %0, %%globaltimer_lo;" : "=r"(t) :: "memory"); return t; }
__device__ __forceinline__ void wait_clock(uint32_t t) { while ((int)(clk32() - t) < 0) {} }
__device__ __forceinline__ bool bar_or(int id, int n, uint32_t v) {
  uint32_t r;
  asm volatile("{ .reg .pred p, q; setp.ne.u32 p, %1, 0; bar.red.or.pred q, %2, %3, p; vote.sync.any.pred q, q, 0xffffffff; selp.u32 %0, 1, 0, q; }"
               : "=r"(r) : "r"(v), "r"(id), "r"(n) : "memory");
  return r;
}
__device__ __forceinline__ void bar_sync_z(int id, int n, uint32_t z) {
  asm volatile("{ .reg .pred p; setp.eq.u32 p, %2, 0; @p bar.sync %0, %1; }" ::"r"(id), "r"(n), "r"(z) : "memory");
}

__device__ __forceinline__ uint32_t probe_polarity(uint32_t* p) {
  uint32_t best[2] = {~0u, ~0u};
#pragma unroll 1
  for (int rep = 0; rep < 4; rep++) {
#pragma unroll
    for (int pg = 0; pg < 2; pg++) {
      uint32_t t0, t1, v;
      asm volatile("mov.u32 %0, %%clock;" : "=r"(t0) :: "memory");
      asm volatile("atom.relaxed.gpu.global.add.u32 %0, [%1], 0;" : "=r"(v) : "l"(p + pg * 1024) : "memory");
      asm volatile("{ .reg .pred p; setp.ne.u32 p, %1, 0x13572468; mov.u32 %0, 0; @p mov.u32 %0, %%clock; }" : "=r"(t1) : "r"(v) : "memory");
      if (rep > 0) best[pg] = min(best[pg], t1 - t0);
    }
  }
  return best[1] < best[0] ? 1u : 0u;
}
__device__ __forceinline__ uint32_t ppage(uint32_t lp, uint32_t pol) { return lp ? 3 - pol : pol; }
__device__ __forceinline__ uint32_t and_x(uint32_t a, uint32_t b, uint32_t m) {
  uint32_t d; asm("lop3.b32 %0, %1, %2, %3, 0x42;" : "=r"(d) : "r"(a), "r"(b), "r"(m)); return d;
}
__device__ __forceinline__ uint32_t and3(uint32_t a, uint32_t b, uint32_t c) {
  uint32_t d; asm("lop3.b32 %0, %1, %2, %3, 0x80;" : "=r"(d) : "r"(a), "r"(b), "r"(c)); return d;
}

template <int N> struct IC { static constexpr int value = N; };
template <class F> __device__ __forceinline__ void static_for2(F f) { f(IC<0>()); f(IC<1>()); }
template <class F> __device__ __forceinline__ void static_for3(F f) { f(IC<0>()); f(IC<1>()); f(IC<2>()); }
__device__ __forceinline__ void load_wfrags(uint32_t (&wA)[32][4], uint32_t stage, int w, int lane) {
  const int mi = lane >> 3, r = lane & 7;
#pragma unroll
  for (int ks = 0; ks < 32; ks++) ldsm4t(wA[ks], stage + (ks * 16 + (mi >> 1) * 8 + r) * W_STRIDE + (w * 16 + (mi & 1) * 8) * 2);
}
template <int K0, int K1>
__device__ __forceinline__ void tok_seq(float (&d)[16], const uint32_t (&wA)[32][4], uint64_t desc, uint32_t wave) {
#pragma unroll
  for (int k = K0; k < K1; k++) {
    const int ks = k & 31;
    constexpr int HM0 = 1, HM1 = 2, HM2 = 4;
    const int hm = (k == HOLE0 ? HM0 : 0) | (k == HOLE1 ? HM1 : 0) | (k == HOLE2 ? HM2 : 0);
    if (hm) bar_sync_z(NB_RD, 384, ((hm >> wave) & 1) ^ 1);
    if (ks == 0) wg_rs32<0, 0>(d, wA[ks], desc);
    else wg_rs32<0, 1>(d, wA[ks], desc + (ks >> 2) * 64 + (ks & 3) * 2);
  }
}
template <int K0, int K1>
__device__ __forceinline__ void mem_part(float (&d)[12], const uint32_t (&wA)[32][4], uint64_t desc) {
#pragma unroll
  for (int ks = K0; ks < K1; ks++) {
    if (ks == 0) wg_rs24<1, 0>(d, wA[ks], desc);
    else wg_rs24<1, 1>(d, wA[ks], desc + ks * 48);
  }
}
__device__ __forceinline__ void out_tile(float (&d)[12], uint64_t da, uint64_t db) {
#pragma unroll
  for (int i = 0; i < 8; i++) { if (i == 0) wg_ss24<0>(d, da, db); else wg_ss24<1>(d, da + i * 128, db + (i >> 1) * 32 + (i & 1) * 2); }
}
__device__ __forceinline__ void tok_pack(uint32_t (&p)[8], const float (&d)[16]) {
#pragma unroll
  for (int i = 0; i < 8; i++) p[i] = pack_bf16(d[2 * i], d[2 * i + 1]);
}
__device__ __forceinline__ void tok_store(uint32_t dst, const uint32_t (&p)[8]) {
  stsm4(dst, p[0], p[1], p[2], p[3]);
  stsm4(dst + 4096, p[4], p[5], p[6], p[7]);
}
template <class T> __device__ __forceinline__ T keep(T v) { asm volatile("" : "+r"(v)); return v; }
__device__ __forceinline__ uint32_t pin(uint32_t v) { return __shfl_sync(~0u, v, threadIdx.x & 31); }

#define TRC blockIdx.x
#define TRS (C_BAR + 256)
__device__ __forceinline__ void chain_proj(const uint32_t sb, const int w, const int lane_, const uint32_t rank) {
  uint32_t wA[32][4];
  load_wfrags(wA, sb + C_X, w, lane_);
  bar_sync(NB_ALL, 512);
  bar_sync(NB_ALL, 512);
  cluster_sync();
  const int lane = pin(lane_);
  const uint32_t bars = sb + C_BAR;
  const uint32_t quad = pin(sb + (lane_ >> 4) * 2048 + (lane_ & 15) * 16);
  const uint32_t own = C_Q + rank * 10240;
  const uint64_t dX1 = mk_desc(sb + C_X, 16, 8192, 1), dX2 = dX1 + 2048, dX3 = dX1 + 4096;
  const uint64_t dM = mk_desc(sb + C_M, 128, 256, 0);
  const uint32_t r1 = rank == 0 ? 1 : 0, r2 = rank == 2 ? 1 : 2;
  const uint32_t xa = pin(sb + own + 8192 + w * 256 + lane_ * 4);
  const uint32_t a1x = pin(mapa_u32(xa, r1)), a2x = pin(mapa_u32(xa, r2));
  const uint32_t b1x = pin(mapa_u32(bars + B_X * 8, r1)), b2x = pin(mapa_u32(bars + B_X * 8, r2));
  const uint32_t wave = rank == 2 ? 0 : rank + 1;
  uint32_t npatch = 0;
  constexpr int K3 = 32 - N0STEPS - N2STEPS;
  float a[16];
  bar_sync(NB_X1, 288);
  wg_fence();
  tok_seq<32, 32 + K3>(a, wA, dX1, 3);
  wg_commit();
  wg_wait<0>();
#pragma unroll 1
  for (int st = 0; st < NSTEP; st++) {
    uint32_t pk[8];
    wg_fence();
    tok_seq<32 + K3, 32 + K3 + N0STEPS>(a, wA, dX1, 3);
    TR(0)
    bar_sync(NB_PV, 384);
    tok_seq<32 + K3 + N0STEPS, 64>(a, wA, dX1, 3);
    wg_commit();
    wg_wait<0>();
    acc_fence(a);
    mbar_arrive_z(bars + B_XF * 8, lane);
    tok_pack(pk, a);
    TR(1)
    bar_sync(NB_W0, 416);
    tok_store(quad + w * 256 + (rank == 0 ? own : C_SA), pk);
    __syncwarp();
    mbar_arrive_z(bars + B_P2 * 8, lane);
    wg_fence();
    tok_seq<0, 32>(a, wA, dX2, wave);
    wg_commit();
    const uint32_t info = lds32(sb + C_INFO + (st & 1) * 4);
    TR(2)
    wg_wait<0>();
    acc_fence(a);
    TR(3)
    tok_pack(pk, a);
    tok_store(quad + w * 256 + (rank == 0 ? C_SA : own), pk);
    if (rank == 2) tok_store(quad + w * 256 + C_SB, pk);
    __syncwarp();
    mbar_arrive_z(bars + B_P1 * 8, lane);
    if (__builtin_expect(info & 4, 0)) {
      float a3[4];
      mbar_wait(bars + B_XL3 * 8, npatch & 1, 32);
      npatch++;
      wg_fence();
#pragma unroll
      for (int ks = 0; ks < 32; ks++) {
        if (ks == 0) wg_rs8<0, 0>(a3, wA[ks], dX3);
        else wg_rs8<0, 1>(a3, wA[ks], dX3 + (ks >> 2) * 64 + (ks & 3) * 2);
      }
      wg_commit();
      wg_wait<0>();
      acc_fence(a3);
      const uint32_t dst = sb + (rank == 2 ? own + (info & 3) * 2048 : C_SP) + w * 256 + lane * 4;
      sts32(dst, pack_bf16(a3[0], a3[1])); sts32(dst + 128, pack_bf16(a3[2], a3[3]));
      __syncwarp();
      mbar_arrive_z(bars + B_P3 * 8, lane);
    }
    TR(4)
    bar_sync(NB_X1, 288);
    wg_fence();
    tok_seq<32, 32 + K3>(a, wA, dX1, wave);
    TR(6)
    {
      float am[12];
      bar_sync(NB_M0, 384);
      mem_part<0, 10>(am, wA, dM);
      TR(7)
      bar_sync(NB_M1, 384);
      mem_part<10, 21>(am, wA, dM);
      const bool redo = bar_or(NB_M2, 384, 0);
      mem_part<21, 32>(am, wA, dM);
      wg_commit();
      wg_wait<0>();
      if (__builtin_expect(redo, 0)) {
        bar_sync(NB_V, 384);
        wg_fence();
        mem_part<0, 32>(am, wA, dM);
        wg_commit();
        wg_wait<0>();
      }
      acc_fence(am);
      TR(8)
      const uint32_t x00 = pack_bf16(am[0], am[1]), x01 = pack_bf16(am[2], am[3]), x10 = pack_bf16(am[4], am[5]), x11 = pack_bf16(am[6], am[7]);
      uint32_t x20 = pack_bf16(am[8], am[9]), x21 = pack_bf16(am[10], am[11]);
      if (info & 4) { x20 = x10; x21 = x11; }
      st_async32<0>(a1x, rank == 0 ? x10 : x00, b1x); st_async32<0>(a2x, rank == 2 ? x10 : x20, b2x);
      st_async32<128>(a1x, rank == 0 ? x11 : x01, b1x); st_async32<128>(a2x, rank == 2 ? x11 : x21, b2x);
      sts32(xa, rank == 0 ? x00 : rank == 2 ? x20 : x10); sts32(xa + 128, rank == 0 ? x01 : rank == 2 ? x21 : x11);
      __syncwarp();
      mbar_arrive_z(bars + B_X * 8, lane);
      if (w == 7) {
        const uint32_t stamp = (gtime() & ~31u) | ((st + 1) & 31);
        asm volatile("{ .reg .pred p; setp.eq.u32 p, %2, 0; @p st.relaxed.gpu.global.u32 [%0], %1; }" ::"l"(&g_fl.stamp[blockIdx.x]), "r"(stamp), "r"(lane) : "memory");
      }
    }
    TR(9)
  }
}

__device__ __forceinline__ void chain_mem(const uint32_t sb, const int w, const int lane_, const uint32_t rank, const int h,
                                          const bf16* __restrict__ mem0) {
  const int lane = pin(lane_);
  const int wave = rank == 2 ? 0 : rank + 1;
  const int c = w - 8, t = c * 32 + lane, b = wave * 32 + h;
  const uint32_t bars = sb + C_BAR;
  uint32_t pgbits = 0;
  {
    uint32_t pol = 1;
    const int tl = lane / 3, u = ((tl * 3 + rank) * 4 + c) * 3 + (lane - tl * 3);
    if (lane < 9 && u < 96) {
      int it = 0;
      while ((pol = ld_rlx32(&g_fl.pol[u])) == 0) give_up(++it, SPIN_LIMIT, 40);
    }
    pgbits = __reduce_or_sync(~0u, lane < 9 ? ppage(h >> 4, (pol - 1) & 1) << (2 * lane) : 0u);
  }
  const int wi = (lane & 1) * 2 + (lane >> 4), cq = (lane >> 2) & 3;
  bar_sync(NB_ALL, 512);
#pragma unroll 1
  for (int i = t; i < 2048; i += 128) {
    const unsigned short* mp = (const unsigned short*)mem0 + 2 * (i & 3) * DM + (i >> 2);
    const uint32_t v = (uint32_t)mp[0] | (uint32_t)mp[DM] << 16;
    const uint32_t a = sb + C_M + (i >> 6) * 768 + (i & 63) * 4;
    sts32(a, v); sts32(a + 256, v); sts32(a + 512, v);
  }
  fence_async_smem();
  mbar_expect_tx_z(bars + B_X * 8, 4096, t); mbar_expect_tx_z(bars + B_O * 8, 4096, t);
  bar_sync(NB_ALL, 512);
  cluster_sync();
  bar_arrive(NB_PV, 384); bar_arrive(NB_W0, 416); bar_arrive(NB_M0, 384); bar_arrive(NB_M1, 384);
  bar_arrive(NB_RD, 384);

  const int mi = lane >> 3;
  const uint32_t l16 = pin(sb + lane * 16);
  const uint32_t r1 = rank == 2 ? 0 : rank + 1, r2 = rank == 0 ? 2 : rank - 1;
  const uint32_t oa = pin(sb + C_O + rank * 2048 + (lane >> 2) * 64 + (((lane & 3) ^ (lane >> 3)) << 4));
  const uint32_t a1 = mapa_u32(oa, r1), b1 = mapa_u32(bars + B_O * 8, r1), a2 = mapa_u32(oa, r2), b2 = mapa_u32(bars + B_O * 8, r2);
  const uint64_t dWo = mk_desc(sb + C_WO, 8192, 1024, 1), dO = mk_desc(sb + C_O, 16, 2048, 2);
  const uint64_t dQ = mk_desc(sb + C_Q, 128, 2048, 0), dK = mk_desc(sb + C_K, 128, 2048, 0);
  const uint64_t dV = mk_desc(sb + C_V, 2048, 128, 0), dVm = mk_desc(sb + C_V + 8192, 0, 128, 0);
  const int lim = pin(c < 2 ? 16 * c + (lane >> 2) - 2 * (lane & 3) : 64);
  uint8_t* Pw = (uint8_t*)g_P + (rank * 4 + c) * 3 * 16384 + (h & 15) * 256 + lane * 4;
  const uint32_t polP = lds32(sb + C_POL + 16);
  const uint8_t* Pr0 = (const uint8_t*)g_P + b * 16384 + ((lane >> 4) * 4 + (lane & 3)) * 256 + c * 64 + cq * 16 + ppage(0, polP) * 4096;
  const uint8_t* Pr1 = Pr0 + (3 - 2 * polP) * 4096;
  uint8_t* Mw = (uint8_t*)g_M + (b >> 5) * 16384 + ((lane & 2) ? 4096 : 12288) + (b & 31) * 256 + c * 64 + cq * 16 + wi * 4;
  uint32_t nretry = 0;
  uint32_t gate_p = GATE_P + wave * GATE_W;
  sts32(sb + C_INFO + 20, GATE_M);

  (void)bar_or(NB_M2, 384, 0);
#pragma unroll 1
  for (int st = 0;; st++) {
    mbar_wait(bars + B_T * 8, st & 1, 42);
    STAT(10, clk32())
    mbar_wait(bars + B_X * 8, st & 1, 41);
    STAT(11, clk32())
    fence_async_smem();
    TR(0)
    {
      float s[20];
      wg_fence();
#pragma unroll
      for (int i = 0; i < 8; i++) { if (i == 0) wg_ss40<0>(s, dQ, dK); else wg_ss40<1>(s, dQ + i * 16, dK + i * 16); }
      wg_commit();
      wg_wait<0>();
      acc_fence(s);
      TR(1)
#pragma unroll
      for (int j = 0; j < 4; j++) {
        if (lim < 8 * j) s[4 * j] = -INFINITY;
        if (lim < 8 * j + 1) s[4 * j + 1] = -INFINITY;
        if (lim < 8 * j - 8) s[4 * j + 2] = -INFINITY;
        if (lim < 8 * j - 7) s[4 * j + 3] = -INFINITY;
      }
      float m0 = fmaxf(fmaxf(fmaxf(s[0], s[1]), fmaxf(s[4], s[5])), fmaxf(fmaxf(s[8], s[9]), fmaxf(s[12], s[13])));
      float m1 = fmaxf(fmaxf(fmaxf(s[2], s[3]), fmaxf(s[6], s[7])), fmaxf(fmaxf(s[10], s[11]), fmaxf(s[14], s[15])));
      m0 = fmaxf(m0, fmaxf(s[16], s[17])); m1 = fmaxf(m1, fmaxf(s[18], s[19]));
      m0 = fmaxf(m0, __shfl_xor_sync(~0u, m0, 1)); m1 = fmaxf(m1, __shfl_xor_sync(~0u, m1, 1));
      m0 = fmaxf(m0, __shfl_xor_sync(~0u, m0, 2)); m1 = fmaxf(m1, __shfl_xor_sync(~0u, m1, 2));
      m0 *= -SCALE_LOG2E; m1 *= -SCALE_LOG2E;
      uint32_t p[10];
      float l0 = 0.f, l1 = 0.f;
#pragma unroll
      for (int k = 0; k < 10; k++) {
        const float e0 = ex2_fast(fmaf(s[2 * k], SCALE_LOG2E, (k & 1) ? m1 : m0)), e1 = ex2_fast(fmaf(s[2 * k + 1], SCALE_LOG2E, (k & 1) ? m1 : m0));
        p[k] = pack_bf16(e0, e1);
        if (k & 1) l1 += e0 + e1; else l0 += e0 + e1;
      }
      asm volatile("" : "+f"(l0), "+f"(l1));
      float oA[32], oB[32];
      wg_fence();
      wg_rs64<0>(oA, p[0], p[1], p[2], p[3], dV); wg_rs64<1>(oA, p[4], p[5], p[6], p[7], dV + 256); wg_rs64<1>(oA, p[8], p[9], 0, 0, dVm);
      wg_commit();
      wg_rs64<0>(oB, p[0], p[1], p[2], p[3], dV + 64); wg_rs64<1>(oB, p[4], p[5], p[6], p[7], dV + 320); wg_rs64<1>(oB, p[8], p[9], 0, 0, dVm + 64);
      wg_commit();
      l0 += __shfl_xor_sync(~0u, l0, 1); l1 += __shfl_xor_sync(~0u, l1, 1);
      l0 += __shfl_xor_sync(~0u, l0, 2); l1 += __shfl_xor_sync(~0u, l1, 2);
      const float i0 = rcp_fast(l0), i1 = rcp_fast(l1);
      const bool mrows = c == 2 && st < NSTEP - 1;
      auto send = [&](const float (&o)[32], auto hc) {
        constexpr int H = decltype(hc)::value;
        static_for2([&](auto bc) {
          constexpr int B = decltype(bc)::value, J = 16 * B;
          asm volatile("st.async.weak.shared::cluster.mbarrier::complete_tx::bytes.v4.b32 [%0 + %9], {%5,%6,%7,%8}, [%1];\n"
                       "st.async.weak.shared::cluster.mbarrier::complete_tx::bytes.v4.b32 [%2 + %9], {%5,%6,%7,%8}, [%3];\n"
                       "st.shared.v4.b32 [%4 + %9], {%5,%6,%7,%8};"
                       ::"r"(a1), "r"(b1), "r"(a2), "r"(b2), "r"(oa), "r"(pack_bf16(o[J] * i0, o[J + 1] * i0)), "r"(pack_bf16(o[J + 4] * i0, o[J + 5] * i0)),
                         "r"(pack_bf16(o[J + 8] * i0, o[J + 9] * i0)), "r"(pack_bf16(o[J + 12] * i0, o[J + 13] * i0)), "n"(H * 1024 + B * 512) : "memory");
        });
      };
      auto keep_tok = [&](const float (&o)[32], int H) {
        const uint32_t ta = l16 + C_OT + c * 4096 + H * 1024;
#pragma unroll
        for (int k = 0; k < 4; k++) {
          const int J = (k & 1) * 16 + (k >> 1) * 2;
          const float iv = (k >> 1) ? i1 : i0;
          stsm4(ta + (k & 1) * 512 + (k >> 1) * 2048, pack_bf16(o[J] * iv, o[J + 1] * iv), pack_bf16(o[J + 4] * iv, o[J + 5] * iv),
                pack_bf16(o[J + 8] * iv, o[J + 9] * iv), pack_bf16(o[J + 12] * iv, o[J + 13] * iv));
        }
      };
      wg_wait<1>();
      acc_fence(oA);
      if (mrows) send(oA, IC<0>());
      wg_wait<0>();
      acc_fence(oB);
      if (st < NSTEP - 1) bar_arrive(NB_PV, 384);
      if (mrows) {
        send(oB, IC<1>());
        __syncwarp();
        mbar_arrive_z(bars + B_O * 8, lane);
      } else if (c < 2) {
        keep_tok(oA, 0);
        keep_tok(oB, 1);
        __syncwarp();
        mbar_arrive_z(bars + B_OT * 8, lane);
      }
      TR(2)
      if (st == NSTEP - 1) break;
      mbar_expect_tx_z(bars + B_X * 8, 4096, t);
    }
    uint32_t tref;
    {
      const uint32_t tag = (st & 1) ^ 1;
      float oc0[12], oc1[12], oc2[12];
      mbar_wait(bars + B_O * 8, st & 1, 43);
      fence_async_smem();
      TR(3)
      wg_fence();
      out_tile(oc0, dWo, dO);
      wg_commit();
      out_tile(oc1, dWo + 1024, dO);
      wg_commit();
      asm volatile("" : "+r"(pgbits));
      auto put = [&](const float (&oc)[12], auto tlc) {
        constexpr int TL = decltype(tlc)::value;
        static_for3([&](auto jc) {
          constexpr int j = decltype(jc)::value;
          uint8_t* p = Pw + ((pgbits >> (2 * (TL * 3 + j))) & 3) * 4096;
          asm volatile("st.relaxed.gpu.global.u32 [%0 + %3], %1; st.relaxed.gpu.global.u32 [%0 + %3 + 128], %2;" ::"l"(p),
                       "r"((pack_bf16(oc[4 * j], oc[4 * j + 1]) & ~1u) | tag), "r"((pack_bf16(oc[4 * j + 2], oc[4 * j + 3]) & ~1u) | tag),
                       "n"((TL * 36 + j) * 16384) : "memory");
        });
      };
      wg_wait<1>();
      acc_fence(oc0);
      put(oc0, IC<0>());
      sts32(sb + C_INFO + 24, clk32());
      TR(4)
      wg_wait<0>();
      if (rank != 2) {
        wg_fence();
        out_tile(oc2, dWo + 2048, dO);
        wg_commit();
        acc_fence(oc1);
        put(oc1, IC<1>());
        bar_sync(NB_TA, 160);
        TR(5)
        wg_wait<0>();
        bar_arrive(NB_W0, 416);
        acc_fence(oc2);
        put(oc2, IC<2>());
      } else {
        bar_arrive(NB_W0, 416);
        acc_fence(oc1);
        put(oc1, IC<1>());
        bar_sync(NB_TA, 160);
      }
      tref = __shfl_sync(~0u, lds32(sb + C_INFO + 12), 0);
      mbar_arrive_remote_z(((t & 1) ? b2 : b1) + (B_F - B_O) * 8, t >> 1);
      mbar_expect_tx_z(bars + B_O * 8, 4096, t);
      TR(6)
    }
    const int sn = (st + 1) & 3;
    {
      const uint32_t flip = (st & 1) ? ~0u : 0u;
      const bool u16 = lane & 16;
      uint8_t* mw = Mw + sn * 65536;
      asm volatile("" : "+l"(mw));
      const uint32_t bs = (lane & 4) ? 0x3f800000u : 0x00003f80u, bs0 = (lane & 8) ? 0u : bs, bs1 = (lane & 8) ? bs : 0u;
      const bool early = st < DELTA && b % 3 != 0;
      uint32_t m0word = 0;
      if (__builtin_expect(early, 0)) {
        const unsigned short* mp = (const unsigned short*)mem0 + ((lane & 1) * 4 + (lane >> 4) * 2) * DM + b / 3 * 16 + c * 4 + ((lane >> 2) & 3);
        m0word = (uint32_t)mp[0] | (uint32_t)mp[DM] << 16;
      }
      STATC(c_rdy)
      wait_clock(tref + gate_p);
      TR(7)
      uint32_t mword;
      int it = 0;
      bool all;
#pragma unroll 1
      do {
        const uint4 q0 = ld_rlx128(Pr0), q1 = ld_rlx128(Pr0 + 2048), q2 = ld_rlx128(Pr1), q3 = ld_rlx128(Pr1 + 2048);
        float d0[4] = {0.f, 0.f, 0.f, 0.f}, d1[4] = {0.f, 0.f, 0.f, 0.f};
        mma16816(d0, q0.x, q0.y, q0.z, q0.w, bs0, bs1);
        mma16816(d1, q1.x, q1.y, q1.z, q1.w, bs0, bs1);
        mma16816(d0, q2.x, q2.y, q2.z, q2.w, bs0, bs1);
        mma16816(d1, q3.x, q3.y, q3.z, q3.w, bs0, bs1);
        all = __all_sync(~0u, (int)and3(and_x(q0.x, q1.x, flip), and_x(q2.x, q3.x, flip), 1u));
        const float a0 = d0[0] + d1[0], a1 = d0[1] + d1[1], a2 = d0[2] + d1[2], a3 = d0[3] + d1[3];
        mword = pack_bf16((u16 ? a2 : a0) + __shfl_xor_sync(~0u, u16 ? a0 : a2, 16), (u16 ? a3 : a1) + __shfl_xor_sync(~0u, u16 ? a1 : a3, 16));
        asm volatile("{ .reg .pred p; setp.ne.u32 p, %2, 0; @p st.relaxed.gpu.global.u32 [%0], %1; }" ::"l"(mw), "r"(early ? m0word : mword), "r"((uint32_t)all) : "memory");
      } while (__builtin_expect(!all, 0) && ++it < SPIN_LIMIT);
      bar_arrive(NB_RD, 384);
      STATC(c_mst)
      STAT(0, lds32(sb + C_INFO + 24) - tref) STAT(1, c_rdy - tref) STAT(2, c_mst - tref) STAT(3, tref) STAT(4, it)
      if (!all) fail(44);
      TRV(14, it)
    }
    TR(9)
    {
      const uint32_t ma = l16 + C_M + c * 512 + mi * 4;
      auto scan = [&](uint32_t m, uint32_t a) { return __vimax3_u32(__vimax3_u32(m, lds32(a), lds32(a + 2048)), lds32(a + 4096), lds32(a + 6144)); };
      mbar_wait(bars + B_M0 * 8, (st + 1) & 1, 45);
      bar_arrive(NB_M0, 384);
      STATC(c_g0)
      TR(10)
      uint32_t m = scan(0, ma);
      mbar_wait(bars + B_M1 * 8, (st + 1) & 1, 46);
      bar_arrive(NB_M1, 384);
      STATC(c_g1)
      TR(11)
      m = scan(m, ma + 8192);
      mbar_wait(bars + B_M2 * 8, (st + 1) & 1, 47);
      STATC(c_g2)
      TR(12)
      m = scan(m, ma + 16384);
      int it = 0;
      if (__builtin_expect(bar_or(NB_M2, 384, m == ~0u), 0)) {
#pragma unroll 1
        do {
          give_up(++it, SPIN_LIMIT, 48);
          if (t == 0) {
            const uint8_t* src = (const uint8_t*)g_M + sn * 65536 + (lds32(sb + C_POL + sn * 4) ? 4096 : 12288);
            mbar_expect_tx(bars + B_R * 8, 24576);
#pragma unroll 1
            for (int g = 0; g < 3; g++) bulk_g2s(sb + C_M + g * 8192, src + g * 16384, 8192, bars + B_R * 8);
          }
          __syncwarp();
          mbar_wait(bars + B_R * 8, nretry++ & 1, 49);
        } while (bar_or(NB_S, 128, scan(scan(scan(0, ma), ma + 8192), ma + 16384) == ~0u));
        bar_arrive(NB_V, 384);
        if (st > DELTA) {
          gate_p += BUMP_P;
          if (t == 0) sts32(sb + C_INFO + 20, lds32(sb + C_INFO + 20) + BUMP_M);
          __syncwarp();
        }
      }
      STAT(9, clk32() - tref) STAT(5, c_g0 - tref) STAT(6, it) STAT(7, c_g1 - tref) STAT(8, c_g2 - tref)
      TR(13)
      TRV(15, it)
      st_rlx32(Mw + (st & 3) * 65536, ~0u);
    }
  }
}

__device__ __forceinline__ void chain_dma(const uint32_t sb, const int w, const int lane, const uint32_t rank, const int h) {
  const uint32_t bars = sb + C_BAR;
  bar_sync(NB_ALL, 512);
  bar_sync(NB_ALL, 512);
  cluster_sync();
  if (w == 12) {
    u64 best = 0;
    uint32_t npatch = 0;
#pragma unroll 1
    for (int st = -1; st < NSTEP; st++) {
      const int sg = st - DELTA;
      uint32_t info = 0;
      if (st >= 0) {
        if (sg >= 0) {
          const u64 k = wait_keys(g_fl.key[0][sg], lane, 50);
          if (k > best) { best = k; info = 4 | ((key_token(k) >> 3) & 3); }
        }
        TR(0)
        if (st > 0) mbar_wait(bars + B_P1 * 8, (st - 1) & 1, 51);
        sts32(sb + C_INFO + (st & 1) * 4, info);
        if (sg >= 0) {
          if (XGATE == 3) mbar_wait(bars + B_X * 8, (st - 1) & 1, 58);
          else if ((int)lds32(sb + C_INFO + 8) < st - 1) mbar_gate(bars + (B_M0 + XGATE) * 8, (st - 1) & 1);
          TR(1)
          if (lane == 0) {
            fence_async_glb();
            mbar_expect_tx(bars + B_XL2 * 8, 32768);
            bulk_g2s(sb + C_X + 32768, g_xs[1] + (size_t)sg * 32768, 32768, bars + B_XL2 * 8);
          }
          __syncwarp();
          mbar_wait(bars + B_XL2 * 8, sg & 1, 52);
        }
        TR(2)
        bar_arrive(NB_W0, 416);
        mbar_wait(bars + B_XF * 8, st & 1, 53);
      }
      if (st + 1 < NSEG) {
        if (lane == 0) {
          mbar_expect_tx(bars + B_XL1 * 8, 32768);
          bulk_g2s(sb + C_X, g_xs[0] + (size_t)(st + 1) * 32768, 32768, bars + B_XL1 * 8);
        }
        __syncwarp();
        mbar_wait(bars + B_XL1 * 8, (st + 1) & 1, 57);
      }
      TR(3)
      bar_arrive(NB_X1, 288);
      if (__builtin_expect(info, 0)) {
        if (npatch > 0) mbar_wait(bars + B_P3 * 8, (npatch - 1) & 1, 55);
        npatch++;
        wait_count(g_fl.patch[sg], 1, 56);
        if (lane == 0) {
          fence_async_glb();
          mbar_expect_tx(bars + B_XL3 * 8, 8192);
          bulk_g2s(sb + C_X + 65536, g_patch + (size_t)sg * 8192, 8192, bars + B_XL3 * 8);
        }
        __syncwarp();
      }
    }
  } else if (w == 13) {
    constexpr uint32_t NP = 8192 / SHIP;
    const uint32_t o = (lane >> 1) * SHIP, own = sb + C_Q + rank * 10240, bt = bars + B_T * 8;
    const uint32_t d2 = 1 + (lane & 1);
    const uint32_t src2 = (rank == 0 ? sb + C_SA : rank == 1 ? own : sb + C_SB) + o;
    const uint32_t skip = (lane & 1) ? 4 | (o >> 11) : 8;
    uint32_t npatch = 0;
#pragma unroll 1
    for (int st = 0; st < NSTEP; st++) {
      mbar_wait(bars + (SHIPLATE ? B_P1 : B_P2) * 8, st & 1, 62);
      fence_async_smem();
      if (st > 0) mbar_wait(bars + B_F * 8, (st - 1) & 1, 60);
      const uint32_t info = lds32(sb + C_INFO + (st & 1) * 4);
      TR(2)
      if (st < NSEG && rank != 0 && lane < 2 * NP && d2 == 1) bulk_s2r(mapa_u32(own + o, 0), sb + C_SA + o, SHIP, mapa_u32(bt, 0));
      __syncwarp();
      TR(3)
      mbar_wait(bars + B_P1 * 8, st & 1, 61);
      fence_async_smem();
      TR(0)
      if (st >= DELTA && lane < 2 * NP && d2 != rank && info != skip) bulk_s2r(mapa_u32(own + o, d2), src2, SHIP, mapa_u32(bt, d2));
      __syncwarp();
      TR(1)
      if (__builtin_expect(info, 0)) {
        mbar_wait(bars + B_P3 * 8, npatch & 1, 63);
        npatch++;
        fence_async_smem();
        if (rank != 2 && lane == 0) bulk_s2r(mapa_u32(own + (info & 3) * 2048, 2), sb + C_SP, 2048, mapa_u32(bt, 2));
        __syncwarp();
      }
    }
  } else if (w == 14) {
    const int s0 = rank == 0 ? 0 : DELTA;
    mbar_expect_tx_z(bars + B_T * 8, s0 == 0 ? 16384 : 0, lane);
#pragma unroll 1
    for (int st = 0; st < NSTEP; st++) {
      const int sg = st - s0;
      const bool act = (unsigned)sg < (unsigned)NSEG;
      mbar_wait(bars + B_OT * 8, st & 1, 70);
      fence_async_smem();
      if (OGATE >= 0 && st < NSTEP - 1) mbar_wait(bars + (OGATE > 0 ? B_M0 + OGATE - 1 : B_F) * 8, (st + (OGATE > 0)) & 1, 71);
      TR(0)
      if (lane == 0) {
        if (act) bulk_s2g(g_O[rank] + ((size_t)(sg & (OSLOTS - 1)) * 32 + h) * 8192, sb + C_OT, 8192);
        asm volatile("cp.async.bulk.commit_group;" ::: "memory");
        asm volatile("cp.async.bulk.wait_group.read 0;" ::: "memory");
        mbar_expect_tx(bars + B_T * 8, (unsigned)(sg + 1) < (unsigned)NSEG ? 16384 : 0);
        asm volatile("cp.async.bulk.wait_group 0;" ::: "memory");
        if (act) red_release(&g_fl.oflag[rank][sg][h >> 2]);
      }
      __syncwarp();
      TR(1)
    }
  } else {
    mbar_arrive_z(bars + B_M0 * 8, lane); mbar_arrive_z(bars + B_M1 * 8, lane); mbar_arrive_z(bars + B_M2 * 8, lane);
    const uint32_t gate_g = GATE_G;
#pragma unroll 1
    for (int st = 0; st < NSTEP; st++) {
      mbar_wait(bars + B_M2 * 8, st & 1, 74);
      sts32(sb + C_INFO + 8, st);
      if (st == NSTEP - 1) break;
      mbar_wait(bars + B_X * 8, st & 1, 75);
      const uint32_t now = gtime() & ~31u, tag = (st + 1) & 31;
      uint32_t s0, s1, s2;
      int it = 0;
#pragma unroll 1
      do {
        s0 = ld_rlx32(&g_fl.stamp[lane]) ^ tag; s1 = ld_rlx32(&g_fl.stamp[32 + lane]) ^ tag; s2 = ld_rlx32(&g_fl.stamp[64 + lane]) ^ tag;
        give_up(it++, SPIN_LIMIT, 76);
      } while (__any_sync(~0u, ((s0 | s1 | s2) & 31) != 0));
      const uint32_t tref = now + __reduce_max_sync(~0u, __vimax3_s32((int)(s0 - now), (int)(s1 - now), (int)(s2 - now)));
      const uint32_t g0 = gtime();
      uint32_t g1, c1;
      it = 0;
      do { g1 = gtime(); c1 = clk32(); } while (g1 == g0 && ++it < 64);
      c1 -= (g1 - tref) * 7 / 4;
      sts32(sb + C_INFO + 12, c1);
      TR(0)
      bar_arrive(NB_TA, 160);
      const int sn = (st + 1) & 3;
      const uint8_t* src = (const uint8_t*)g_M + sn * 65536 + (lds32(sb + C_POL + sn * 4) ? 4096 : 12288);
      c1 += lds32(sb + C_INFO + 20);
      const int d = (int)(c1 - 600 - clk32());
      if (d > 0) __nanosleep(d / 4);
#pragma unroll 1
      for (int g = 0; g < 3; g++) {
        mbar_expect_tx_z(bars + (B_M0 + g) * 8, 8192, lane);
        wait_clock(c1 + g * gate_g);
        if (lane == 0) bulk_g2s(sb + C_M + g * 8192, src + g * 16384, 8192, bars + (B_M0 + g) * 8);
        __syncwarp();
        TR(1 + g)
      }
    }
  }
}

__global__ void __cluster_dims__(3, 1, 1) __launch_bounds__(512, 1)
chain_kernel(const bf16* __restrict__ Wq, const bf16* __restrict__ Wk, const bf16* __restrict__ Wv,
             const bf16* __restrict__ Wo, const bf16* __restrict__ mem0) {
  extern __shared__ __align__(1024) uint8_t smem_raw[];
  const uint32_t sb = (smem_u32(smem_raw) + 1023) & ~1023u;
  const int tid = threadIdx.x, lane = tid & 31;
  const int w = __shfl_sync(~0u, tid >> 5, 0);
  uint32_t rank;
  asm volatile("mov.u32 %0, %%cluster_ctarank;" : "=r"(rank));
  const int h = blockIdx.x / 3;
  asm volatile("griddepcontrol.launch_dependents;" ::: "memory");
  TG(0)
  if (tid == 0) {
    const uint32_t bars = sb + C_BAR;
    mbar_init(bars + B_M0 * 8, 1); mbar_init(bars + B_M1 * 8, 1); mbar_init(bars + B_M2 * 8, 1); mbar_init(bars + B_R * 8, 1);
    mbar_init(bars + B_X * 8, 9); mbar_init(bars + B_O * 8, 2); mbar_init(bars + B_T * 8, 1); mbar_init(bars + B_F * 8, 2);
    mbar_init(bars + B_XL1 * 8, 1); mbar_init(bars + B_XL2 * 8, 1); mbar_init(bars + B_XL3 * 8, 1);
    mbar_init(bars + B_P1 * 8, 8); mbar_init(bars + B_P2 * 8, 8); mbar_init(bars + B_P3 * 8, 8); mbar_init(bars + B_OT * 8, 2); mbar_init(bars + B_XF * 8, 8);
    asm volatile("fence.mbarrier_init.release.cluster;" ::: "memory");
  }
  {
    const bf16* W1 = (rank == 0 ? Wq : rank == 1 ? Wk : Wv) + h * 128;
#pragma unroll 4
    for (int cidx = tid; cidx < 512 * 16; cidx += 512) {
      const int d = cidx >> 4, q = cidx & 15;
      cp16(sb + C_X + d * W_STRIDE + q * 16, W1 + (size_t)d * HD + q * 8);
    }
    const int nt = rank == 2 ? 2 : 3;
    for (int cidx = tid; cidx < nt * 1024; cidx += 512) {
      const int tl = cidx >> 10, e = (cidx >> 3) & 127, q = cidx & 7;
      const int es = (e & ~30) | ((e & 6) << 2) | ((e >> 2) & 6);
      cp16(sb + C_WO + tl * 16384 + e * 128 + ((q ^ (e & 7)) << 4), Wo + (size_t)(h * 128 + es) * DM + (tl * 3 + rank) * 64 + q * 8);
    }
    asm volatile("cp.async.commit_group;" ::: "memory");
    if (lane == 0) {
      if (w < 4) sts32(sb + C_POL + w * 4, probe_polarity(g_M + w * 16384 + (blockIdx.x & 31) * 32));
      else if (w == 4) {
        const int u = (rank == 2 ? 0 : rank + 1) * 32 + h;
        const uint32_t pol = probe_polarity(g_P + u * 4096);
        sts32(sb + C_POL + 16, pol);
        st_rlx32(&g_fl.pol[u], pol + 1);
      }
    }
    asm volatile("cp.async.wait_group 0;" ::: "memory");
    fence_async_smem();
    __syncthreads();
  }
  if (w < 8) {
    reg_inc<184>();
    chain_proj(sb, w, lane, rank);
    TG(1)
    TRDUMP
    cluster_sync();
  } else if (w < 12) {
    reg_dec<120>();
    chain_mem(sb, w, lane, rank, h, mem0);
    STATDUMP
    TRDUMP
    cluster_sync();
  } else {
    reg_dec<24>();
    chain_dma(sb, w, lane, rank, h);
    TRDUMP
    cluster_sync();
  }
}
#undef TRC
#undef TRS

constexpr int K_BAR = 0, K_LN = 128, K_FH = 320, K_FS = 512, K_WR = 2048;
constexpr int K_W = 3072;
constexpr int K_O = K_W + 3 * 49152;
constexpr int K_ST = K_O + 65536;
constexpr int K_SMEM = K_ST + 16384;
static_assert(K_SMEM <= 232448 && 512 * W_STRIDE <= 3 * 49152, "shared memory");
enum { KB_FULL = 0, KB_EMPTY = 2, KB_OK = 4, KB_GO = 7, KB_ST = 10, KB_REL = 12 };
enum { KN_ST = 1, KN_ST1, KN_REL, KN_FFN, KN_INIT, KN_RES, KN_CAND, KN_TAKEN };
#define GATE_R 450
struct WorkerParams {
  const bf16 *x0, *Wo, *w_r, *w_gate, *w_up, *w_down;
  bf16* out;
};
#define TRC (96 + blockIdx.x)
#define FOR_UNITS _Pragma("unroll 1") for (int st = 0, n = 0; st < NSTEP; st++) \
                  _Pragma("unroll 1") for (int v = st < NSEG ? 0 : 1, sg = v ? st - DELTA : st; v < (st >= DELTA ? 3 : 1); v++, n++, sg = st - DELTA)

__device__ __forceinline__ void ffn_slice(uint32_t sb, int t, int nu, const bf16* yrow, int ev) {
  const int lane = t & 31, c = t >> 5;
  const uint32_t sg_ = sb + K_FS, sh = sb + (nu == 3 ? K_FH : K_FS + 2048);
  float y[16];
  {
    const uint2 r = ld_rlx64(yrow + t * 4);
#pragma unroll
    for (int i = 0; i < 16; i++) {
      const uint32_t lo = __shfl_sync(~0u, r.x, 2 * i + (lane >> 4)), hi = __shfl_sync(~0u, r.y, 2 * i + (lane >> 4));
      const uint32_t wv = (lane & 8) ? hi : lo;
      y[i] = (lane & 4) ? bf_hi(wv) : bf_lo(wv);
    }
  }
#pragma unroll 1
  for (int u = 0; u < nu; u++) {
    float g[8];
#pragma unroll
    for (int i = 0; i < 8; i++) g[i] = 0.f;
    const uint32_t wa = sb + K_W + u * 49152 + c * 8192 + lane * 16;
#pragma unroll
    for (int i = 0; i < 16; i++) {
      const uint4 a = lds128(wa + i * 512);
      g[0] += y[i] * bf_lo(a.x); g[1] += y[i] * bf_hi(a.x); g[2] += y[i] * bf_lo(a.y); g[3] += y[i] * bf_hi(a.y);
      g[4] += y[i] * bf_lo(a.z); g[5] += y[i] * bf_hi(a.z); g[6] += y[i] * bf_lo(a.w); g[7] += y[i] * bf_hi(a.w);
    }
#pragma unroll
    for (int i = 0; i < 4; i++) g[i] = ((lane & 16) ? g[4 + i] : g[i]) + __shfl_xor_sync(~0u, (lane & 16) ? g[i] : g[4 + i], 16);
#pragma unroll
    for (int i = 0; i < 2; i++) g[i] = ((lane & 8) ? g[2 + i] : g[i]) + __shfl_xor_sync(~0u, (lane & 8) ? g[i] : g[2 + i], 8);
    g[0] = ((lane & 4) ? g[1] : g[0]) + __shfl_xor_sync(~0u, (lane & 4) ? g[0] : g[1], 4);
    sts32(sg_ + u * 512 + c * 128 + ((lane & 3) * 8 + (lane >> 2)) * 4, __float_as_uint(g[0]));
  }
  bar_sync(KN_FFN, 128);
  {
    const uint32_t pa = sg_ + c * 512 + lane * 4;
    const float gt = round_bf16((__uint_as_float(lds32(pa)) + __uint_as_float(lds32(pa + 128))) + (__uint_as_float(lds32(pa + 256)) + __uint_as_float(lds32(pa + 384))));
    const float up = __shfl_xor_sync(~0u, gt, 16);
    if (lane < 16 && c < nu) sts32(sh + (c * 16 + lane) * 4, __float_as_uint(round_bf16(round_bf16(gt / (1.f + __expf(-gt))) * up)));
  }
  bar_sync(KN_FFN, 128);
  float a0 = 0.f, a1 = 0.f, a2 = 0.f, a3 = 0.f;
#pragma unroll 1
  for (int u = 0; u < nu; u++) {
    const uint32_t wa = sb + K_W + u * 49152 + 32768 + t * 8;
#pragma unroll
    for (int i = 0; i < 16; i += 4) {
      const uint4 hq = lds128(sh + (u * 16 + i) * 4);
      const uint32_t hv[4] = {hq.x, hq.y, hq.z, hq.w};
#pragma unroll
      for (int k = 0; k < 4; k++) {
        uint2 d;
        asm volatile("ld.shared.v2.b32 {%0,%1}, [%2];" : "=r"(d.x), "=r"(d.y) : "r"(wa + (i + k) * 1024) : "memory");
        const float hf = __uint_as_float(hv[k]);
        a0 += hf * bf_lo(d.x); a1 += hf * bf_hi(d.x); a2 += hf * bf_lo(d.y); a3 += hf * bf_hi(d.y);
      }
    }
  }
  asm volatile("red.relaxed.gpu.global.add.v4.f32 [%0], {%1,%2,%3,%4};" ::"l"(&g_fl.upd[ev][t * 4]), "f"(a0), "f"(a1), "f"(a2), "f"(a3) : "memory");
  bar_sync(KN_FFN, 128);
  if (t == 96) red_release(g_fl.ffncnt[ev]);
  __syncwarp();
}
__device__ __forceinline__ Row ffn_finish(int ver, int ev, u64 key, int lane) {
  const int tok = key_token(key);
  Row x = load_row(g_rows[ver][0] + (size_t)tok * DM, lane);
  const Row y = load_row(g_rows[ver][1] + (size_t)tok * DM, lane);
  const float sig = round_bf16(1.f / (1.f + __expf(-key_score(key))));
  wait_count(g_fl.ffncnt[ev], NWORK, 80);
#pragma unroll
  for (int q = 0; q < 4; q++) {
    const uint4 u = ld_rlx128(&g_fl.upd[ev][q * 128 + lane * 4]);
    const uint32_t a = pack_bf16(__uint_as_float(u.x), __uint_as_float(u.y)), b = pack_bf16(__uint_as_float(u.z), __uint_as_float(u.w));
    x.w[2 * q] = add_bf16x2(x.w[2 * q], add_bf16x2(y.w[2 * q], pack_bf16(bf_lo(a) * sig, bf_hi(a) * sig)));
    x.w[2 * q + 1] = add_bf16x2(x.w[2 * q + 1], add_bf16x2(y.w[2 * q + 1], pack_bf16(bf_lo(b) * sig, bf_hi(b) * sig)));
  }
  return x;
}
__device__ __forceinline__ uint2 group_ln(uint2 r, float& e, uint32_t sl, uint32_t sw, int lane) {
  const float x0 = bf_lo(r.x), x1 = bf_hi(r.x), x2 = bf_lo(r.y), x3 = bf_hi(r.y);
  const float s = (x0 + x1) + (x2 + x3), q = fmaf(x0, x0, x1 * x1) + fmaf(x2, x2, x3 * x3);
  const bool u16 = lane & 16, u8 = lane & 8;
  const float a = (u16 ? q : s) + __shfl_xor_sync(~0u, u16 ? s : q, 16), b = e + __shfl_xor_sync(~0u, e, 16);
  float v = (u8 ? b : a) + __shfl_xor_sync(~0u, u8 ? a : b, 8);
  v += __shfl_xor_sync(~0u, v, 4); v += __shfl_xor_sync(~0u, v, 2); v += __shfl_xor_sync(~0u, v, 1);
  sts32(sl + sw, __float_as_uint(v));
  bar_sync(KN_RES, 128);
  const uint4 ss = lds128(sl), qq = lds128(sl + 32), ee = lds128(sl + 16);
  const float m = ((__uint_as_float(ss.x) + __uint_as_float(ss.y)) + (__uint_as_float(ss.z) + __uint_as_float(ss.w))) * (1.f / DM);
  const float m2 = ((__uint_as_float(qq.x) + __uint_as_float(qq.y)) + (__uint_as_float(qq.z) + __uint_as_float(qq.w))) * (1.f / DM);
  e = (__uint_as_float(ee.x) + __uint_as_float(ee.y)) + (__uint_as_float(ee.z) + __uint_as_float(ee.w));
  float rs;
  asm("rsqrt.approx.ftz.f32 %0, %1;" : "=f"(rs) : "f"(fmaxf(fmaf(-m, m, m2), 0.f) + 1e-5f));
  return make_uint2(pack_bf16((x0 - m) * rs, (x1 - m) * rs), pack_bf16((x2 - m) * rs, (x3 - m) * rs));
}
__device__ __forceinline__ uint32_t score_bits(float r) {
  const uint32_t b = pack_bf16(0.f, r);
  return (b & 0x80000000u) ? ~b : (b | 0x80000000u);
}

__global__ void __launch_bounds__(640, 1) worker_kernel(const __grid_constant__ WorkerParams prm) {
  extern __shared__ __align__(1024) uint8_t smem_raw[];
  const uint32_t sb = smem_u32(smem_raw);
  const int tid = threadIdx.x, lane = tid & 31;
  const int w = __shfl_sync(~0u, tid >> 5, 0);
  const int me = blockIdx.x, kb = me >> 2, cb = me & 3;
  const bool full = me < 32;
  const uint32_t bars = sb + K_BAR;
  TG(0)
  if (tid == 0) {
    for (int i = 0; i < 2; i++) { mbar_init(bars + (KB_FULL + i) * 8, 1); mbar_init(bars + (KB_EMPTY + i) * 8, 1); }
    for (int i = 0; i < 9; i++) mbar_init(bars + (KB_OK + i) * 8, i < 3 ? 4 : 1);
    sts32(sb + K_LN + 144, 0); sts32(sb + K_LN + 176, 0); sts32(sb + K_LN + 180, ~0u);
    asm volatile("fence.mbarrier_init.release.cluster;" ::: "memory");
  }
  if (full) {
    const bf16* W1 = prm.Wo + (size_t)kb * 512 * DM + cb * 128;
#pragma unroll 4
    for (int cidx = tid; cidx < 512 * 16; cidx += 640) {
      const int d = cidx >> 4, q = cidx & 15;
      cp16(sb + K_W + d * W_STRIDE + q * 16, W1 + (size_t)d * DM + q * 8);
    }
    asm volatile("cp.async.commit_group;" ::: "memory");
    asm volatile("cp.async.wait_group 0;" ::: "memory");
  }
  fence_async_smem();
  __syncthreads();
  if (w < 8) {
    reg_inc<176>();
    if (full) {
      uint32_t wA[32][4];
      load_wfrags(wA, sb + K_W, w, lane);
      bar_arrive(KN_INIT, 384);
      const uint32_t sp = pin(sb + K_ST + ((lane >> 4) * 8 + (lane & 7)) * 256 + (((2 * w + ((lane >> 3) & 1)) ^ (lane & 7)) << 4));
      const uint32_t tm = pin(lane < 4 ? 0x00010001u : 0u);
      FOR_UNITS {
        float d[16];
        mbar_wait(bars + (KB_FULL + (n & 1)) * 8, (n >> 1) & 1, 81);
        TR(4 * v)
        const uint64_t db = mk_desc(sb + K_O + (n & 1) * 32768, 128, 2048, 0);
        wg_fence();
#pragma unroll
        for (int ks = 0; ks < 32; ks++) {
          if (ks == 0) wg_rs32<0, 0>(d, wA[ks], db);
          else wg_rs32<0, 1>(d, wA[ks], db + (ks >> 3) * 512 + (ks & 7) * 16);
        }
        wg_commit();
        mbar_wait(bars + (KB_ST + (n & 1)) * 8, ((n >> 1) & 1) ^ 1, 82);
        wg_wait<0>();
        acc_fence(d);
        TR(4 * v + 1)
        const uint32_t tag = (sg & 2) ? 0u : tm;
        uint32_t pk[8];
#pragma unroll
        for (int i = 0; i < 8; i++) pk[i] = (pack_bf16(d[2 * i], d[2 * i + 1]) & ~tm) | tag;
        stsm4t(sp + (n & 1) * 8192, pk[0], pk[1], pk[2], pk[3]);
        stsm4t(sp + (n & 1) * 8192 + 4096, pk[4], pk[5], pk[6], pk[7]);
        bar_arrive(KN_ST + (n & 1), 288);
        TR(4 * v + 2)
      }
    }
  } else if (w < 12) {
    reg_dec<56>();
    if (full) {
      const int t = pin(tid - 256), ln = t & 31;
      const uint32_t sw = pin((lane >> 3) * 16 + (w - 8) * 4);
      const uint32_t so = pin((w - 8) * 8192 + me * 256 + ((lane * 8) ^ ((me & 7) << 4)));
      sts32(sb + K_WR + t * 8, ld_rlx32(prm.w_r + t * 4)); sts32(sb + K_WR + t * 8 + 4, ld_rlx32(prm.w_r + t * 4 + 2));
      int sstar = -1;
      auto records = [&](int sg) {
        uint4 r;
        int it = 0;
        while ((int)(r = lds128(sb + K_LN + 144)).x <= sg) { give_up(++it, SPIN_LIMIT, 86); __nanosleep(50); }
        return r;
      };
      uint32_t sl = sb + K_LN;
      float rr = 0.f;
      int kprev = -1, pv = 0, psg = 0;
      uint2 x = make_uint2(0, 0);
      auto finish = [&](int v, int sg) {
        bf16* dst = g_rows[v][0] + (sg * 32 + me) * DM + t * 4;
        *(uint2*)dst = x;
        sl ^= 64;
        const uint2 y = group_ln(x, rr, sl, sw, ln);
        uint2 wr;
        asm volatile("ld.shared.v2.b32 {%0,%1}, [%2];" : "=r"(wr.x), "=r"(wr.y) : "r"(sb + K_WR + t * 8) : "memory");
        *(uint2*)(dst + NTOK * DM) = y;
        x = make_uint2(add_bf16x2(x.x, y.x), add_bf16x2(x.y, y.y));
        *(uint2*)(v == (sg < sstar ? 1 : 2) ? prm.out + (sg * 32 + me) * DM + t * 4 : dst + 2 * NTOK * DM) = x;
        asm volatile("{ .reg .pred p; setp.eq.u32 p, %2, 0; @p st.relaxed.gpu.global.u64 [%0], %1; }" ::"l"(&g_fl.key[0][0][0] + max(kprev, 0)),
                     "l"((u64)score_bits(rr) << 32 | (uint32_t)~(kprev & (NTOK - 1))), "r"(t | (kprev < 0)) : "memory");
        kprev = v * NTOK + sg * 32 + me;
        rr = fmaf(bf_lo(y.x), bf_lo(wr.x), bf_hi(y.x) * bf_hi(wr.x)) + fmaf(bf_lo(y.y), bf_lo(wr.y), bf_hi(y.y) * bf_hi(wr.y));
      };
      FOR_UNITS {
        const uint8_t* src = g_part[v] + (sg & 1) * (32 * 8192) + so;
        const bf16* xin = (v ? g_rows[0][2] : prm.x0) + (sg * 32 + me) * DM;
        if (v == 2) {
          const uint4 r = records(sg);
          if (((sg < 32 ? r.y : r.z) >> (sg & 31)) & 1) xin = g_x2p + sg * DM;
        }
        mbar_wait(bars + (KB_GO + v) * 8, sg & 1, 87);
        TR(4 * v)
        uint2 p[8];
#pragma unroll
        for (int k = 0; k < 8; k++) p[k] = ld_rlx64(src + k * 32768);
        const uint2 x0 = ld_rlx64(xin + t * 4);
        if (pv) finish(pv, psg);
        const uint32_t flip = lds32(sb + K_LN + 176 + (sg & 2) * 2);
        int it = 0;
#pragma unroll 1
        while (__builtin_expect(!__all_sync(~0u, (int)and3(and3(and_x(p[0].x, p[1].x, flip), and_x(p[2].x, p[3].x, flip), 1u),
                                                           and_x(p[4].x, p[5].x, flip), and_x(p[6].x, p[7].x, flip)) | (t & 1)), 0)) {
          give_up(++it, SPIN_LIMIT, 85);
#pragma unroll
          for (int k = 0; k < 8; k++) p[k] = ld_rlx64(src + k * 32768);
        }
        mbar_arrive_z(bars + (KB_OK + v) * 8, ln);
#define P8(h, f) (((h(p[0].f) + h(p[1].f)) + (h(p[2].f) + h(p[3].f))) + ((h(p[4].f) + h(p[5].f)) + (h(p[6].f) + h(p[7].f))))
        x = make_uint2(add_bf16x2(x0.x, pack_bf16(P8(bf_lo, x), P8(bf_hi, x))), add_bf16x2(x0.y, pack_bf16(P8(bf_lo, y), P8(bf_hi, y))));
#undef P8
        TRV(12 + v, it)
        TR(4 * v + 1)
        pv = v; psg = sg;
        if (v == 0 || (v == 2 && sg == NSEG - 1)) {
          finish(v, sg);
          sl ^= 64;
          const uint2 y = group_ln(x, rr, sl, sw, ln);
          if (v == 0) *(uint2*)(g_xs[1] + (sg * 4 + (me >> 3)) * 8192 + (t >> 4) * 1024 + (me & 7) * 128 + ((((t & 15) >> 1) ^ (me & 7)) << 4) + (t & 1) * 8) = y;
          sts32(sb + K_LN + 128, score_bits(rr));
          bar_arrive(KN_REL, 160);
          kprev = -1;
          if (__builtin_expect(v == 0 && sg == NSEG - 1, 0)) {
            sstar = records(NSEG - 1).w;
            const int nc = min(sstar, NSEG - 1 - DELTA);
#pragma unroll 1
            for (int s0 = 0; s0 < nc; s0 += 8) {
              uint2 r[8];
#pragma unroll
              for (int i = 0; i < 8; i++) r[i] = ld_rlx64(g_rows[1][2] + (min(s0 + i, nc - 1) * 32 + me) * DM + t * 4);
#pragma unroll
              for (int i = 0; i < 8; i++) *(uint2*)(prm.out + (min(s0 + i, nc - 1) * 32 + me) * DM + t * 4) = r[i];
            }
          }
        }
        TR(4 * v + 2)
      }
    }
  } else if (w < 16) {
    reg_dec<48>();
    const int t = tid - 384, nu = full ? 3 : 4;
    if (full) bar_sync(KN_INIT, 384);
    {
      const int j0 = (full ? me * 3 : 96 + (me - 32) * 4) * 16;
#pragma unroll 1
      for (int i = t; i < nu * 3072; i += 128) {
        const int u = i / 3072, r = i - u * 3072;
        const bf16* src = r < 2048 ? ((r & 2) ? prm.w_up : prm.w_gate) + (size_t)(r >> 2) * FF + j0 + u * 16 + (r & 1) * 8
                                   : prm.w_down + (size_t)(j0 + u * 16) * DM + (r - 2048) * 8;
        cp16(sb + K_W + i * 16, src);
      }
      asm volatile("cp.async.wait_all;" ::: "memory");
    }
#pragma unroll 1
    while (true) {
      bar_sync(KN_CAND, 160);
      const uint4 cand = lds128(sb + K_LN + 160);
      bar_arrive(KN_TAKEN, 160);
      const u64 k = (u64)cand.y << 32 | cand.x;
      const int sg = cand.z, ver = cand.w, tok = key_token(k);
      const bool owner = (tok & 31) == me;
      uint8_t* dst = g_patch + (size_t)(sg & (NSEG - 1)) * 8192;
      if (owner && ver == 0) {
        const uint8_t* src = g_xs[1] + (size_t)(tok >> 3) * 8192;
#pragma unroll
        for (int i = t; i < 512; i += 128) {
          const uint4 q = ld_rlx128(src + i * 16);
          if (((i >> 3) & 7) != (tok & 7)) *(uint4*)(dst + i * 16) = q;
        }
      }
      ffn_slice(sb, t, nu, g_rows[ver][1] + (size_t)tok * DM, sg);
      if (owner && w == 12) {
        const Row x = ffn_finish(ver, sg, k, lane);
        store_row(ver ? prm.out + (size_t)tok * DM : g_x2p + sg * DM, lane, x);
        if (ver == 0) {
          store_row_img(dst, tok & 7, lane, warp_ln(x));
          __syncwarp();
          if (lane == 0) st_release32(g_fl.patch[sg], 1);
          __syncwarp();
        }
      }
      if (ver) break;
    }
  } else {
    reg_dec<24>();
    if (w == 16) {
      u64 best = 0, mask = 0;
      bool first = true;
#pragma unroll 1
      for (int sg = 0; sg <= NSEG; sg++) {
        u64 k = wait_keys(sg < NSEG ? g_fl.key[0][sg] : g_fl.key[2][NSEG - 1], lane, 91);
        uint32_t ver = 0;
        if (sg == NSEG) {
          const int sstar = key_token(best) >> 5;
          u64 m = 0;
#pragma unroll 4
          for (int s2 = 0; s2 < NSEG; s2++) {
            u64 k2;
            asm volatile("ld.relaxed.gpu.global.u64 %0, [%1];" : "=l"(k2) : "l"(&g_fl.key[s2 < sstar ? 1 : 2][s2][lane]) : "memory");
            if (k2 > m) m = k2;
          }
          const uint32_t hi = __reduce_max_sync(~0u, (uint32_t)(m >> 32));
          k = (u64)hi << 32 | __reduce_max_sync(~0u, (uint32_t)(m >> 32) == hi ? (uint32_t)m : 0u);
          ver = (key_token(k) >> 5) < sstar ? 1 : 2;
        } else {
          const bool rec = k > best;
          if (rec) { best = k; if ((key_token(k) & 31) == me) mask |= 1ull << sg; }
          sts128(sb + K_LN + 144, make_uint4(sg + 1, (uint32_t)mask, (uint32_t)(mask >> 32), key_token(best) >> 5));
          if (!rec) continue;
        }
        if (!first) bar_sync(KN_TAKEN, 160);
        first = false;
        sts128(sb + K_LN + 160, make_uint4((uint32_t)k, (uint32_t)(k >> 32), sg, ver));
        bar_arrive(KN_CAND, 160);
      }
      bar_sync(KN_TAKEN, 160);
    } else if (!full) {
    } else if (w == 17) {
      FOR_UNITS {
        wait_count(&g_fl.oflag[v][sg][kb], 4, 84);
        mbar_wait(bars + (KB_EMPTY + (n & 1)) * 8, ((n >> 1) & 1) ^ 1, 83);
        TR(v)
        if (lane == 0) {
          fence_async_glb();
          mbar_expect_tx(bars + (KB_FULL + (n & 1)) * 8, 32768);
          bulk_g2s(sb + K_O + (n & 1) * 32768, g_O[v] + ((size_t)(sg & (OSLOTS - 1)) * 32 + kb * 4) * 8192, 32768, bars + (KB_FULL + (n & 1)) * 8);
        }
        __syncwarp();
      }
    } else if (w == 18) {
      FOR_UNITS {
        if (sg > 0) mbar_wait(bars + (KB_OK + v) * 8, (sg - 1) & 1, 90);
        bar_sync(KN_ST + (n & 1), 288);
        fence_async_smem();
        if (lane == 0) {
          bulk_s2g(g_part[v] + ((sg & 1) * 32 + me) * 8192, sb + K_ST + (n & 1) * 8192, 8192);
          asm volatile("cp.async.bulk.commit_group;" ::: "memory");
          mbar_arrive_z(bars + (KB_EMPTY + (n & 1)) * 8, 0);
          asm volatile("cp.async.bulk.wait_group.read 0;" ::: "memory");
        }
        __syncwarp();
        mbar_arrive_z(bars + (KB_ST + (n & 1)) * 8, lane);
        TR(v)
        const uint32_t tg = clk32() + GATE_R;
        if (v == 0 && sg > 0) mbar_wait(bars + KB_REL * 8, (sg - 1) & 1, 93);
        wait_clock(tg);
        mbar_arrive_z(bars + (KB_GO + v) * 8, lane);
      }
    } else {
#pragma unroll 1
      for (int i = 0; i <= NSEG; i++) {
        const int st = i, sg = min(i, NSEG - 1);
        (void)st;
        bar_sync(KN_REL, 160);
        const uint32_t ob = __shfl_sync(~0u, lds32(sb + K_LN + 128), 0);
        mbar_arrive_z(bars + KB_REL * 8, lane);
        if (lane == 0) st_release_u64(&g_fl.key[i < NSEG ? 0 : 2][sg][me], (u64)ob << 32 | (uint32_t)~(sg * 32 + me));
        __syncwarp();
        TR(0)
      }
    }
  }
}
#undef TRC

bool g_ready;

}

extern "C" void kernel_launch(void* const* d_in, const int* in_sizes, int n_in, void* d_out, int out_size) {
  (void)in_sizes; (void)n_in; (void)out_size;
  const bf16* x0 = (const bf16*)d_in[0];
  const bf16* mem0 = (const bf16*)d_in[1];
  const bf16* Wq = (const bf16*)d_in[2];
  const bf16* Wk = (const bf16*)d_in[3];
  const bf16* Wv = (const bf16*)d_in[4];
  const bf16* Wo = (const bf16*)d_in[5];
  if (!g_ready) {
    cudaFuncSetAttribute(worker_kernel, cudaFuncAttributeMaxDynamicSharedMemorySize, K_SMEM);
    cudaFuncSetAttribute(chain_kernel, cudaFuncAttributeMaxDynamicSharedMemorySize, C_SMEM);
    g_ready = true;
  }
  cudaStream_t st = cudaStreamPerThread;
  prep_kernel<<<NTOK / 8, 256, 0, st>>>(x0);
  chain_kernel<<<96, 512, C_SMEM, st>>>(Wq, Wk, Wv, Wo, mem0);
  cudaLaunchAttribute pdl[1];
  pdl[0].id = cudaLaunchAttributeProgrammaticStreamSerialization;
  pdl[0].val.programmaticStreamSerializationAllowed = 1;
  WorkerParams wp;
  wp.x0 = x0; wp.Wo = Wo; wp.w_r = (const bf16*)d_in[8]; wp.w_gate = (const bf16*)d_in[9]; wp.w_up = (const bf16*)d_in[10];
  wp.w_down = (const bf16*)d_in[11]; wp.out = (bf16*)d_out;
  cudaLaunchConfig_t cfg = {};
  cfg.gridDim = dim3(NWORK); cfg.blockDim = dim3(640); cfg.dynamicSmemBytes = K_SMEM; cfg.stream = st;
  cfg.attrs = pdl; cfg.numAttrs = 1;
  cudaLaunchKernelEx(&cfg, worker_kernel, wp);
}
```

```cpp
#include <cuda_runtime.h>
#include <cuda_bf16.h>
#include <stdint.h>

namespace {

typedef __nv_bfloat16 bf16;
typedef unsigned long long u64;

constexpr int NTOK = 2048, DM = 512, HD = 4096, NSEG = 64, FF = 1792;
#define DELTA 4
constexpr int NSTEP = NSEG + DELTA;
constexpr int SPIN_LIMIT = 40000;
constexpr int MBAR_LIMIT = 20000;
constexpr int NWORK = 36;
constexpr int OSLOTS = 8;

__device__ __align__(1024) uint8_t g_xs[2][NSEG * 32768];
__device__ __align__(1024) uint8_t g_patch[NSEG * 8192];
__device__ __align__(1024) uint8_t g_O[3][OSLOTS * 32 * 8192];
__device__ __align__(1024) uint8_t g_part[3][2 * 32 * 8192];
__device__ __align__(1024) bf16 g_rows[3][3][NTOK * DM];
__device__ __align__(1024) bf16 g_x2p[NSEG * DM];
__device__ __align__(65536) uint32_t g_M[4 * 16384];
__device__ __align__(65536) uint32_t g_P[96 * 4096];
struct Flags {
  uint32_t pol[96];
  uint32_t stamp[96];
  uint32_t oflag[3][NSEG][8];
  uint32_t ffncnt[NSEG + 1][8];
  uint32_t patch[NSEG][8];
  u64 key[3][NSEG][32];
  float upd[NSEG + 1][DM];
};
__device__ __align__(1024) Flags g_fl;
#define TR(e)
#define TRV(e, v)
#define TG(i)
#define HD(e)
#define TRDUMP
#define TREXTRA 0

#define STAT(e, v)
#define STATC(n)
#define STATDUMP
__device__ __forceinline__ uint32_t smem_u32(const void* p) { return (uint32_t)__cvta_generic_to_shared(p); }
__device__ __forceinline__ uint32_t pack_bf16(float lo, float hi) {
  uint32_t r;
  asm("cvt.rn.bf16x2.f32 %0, %1, %2;" : "=r"(r) : "f"(hi), "f"(lo));
  return r;
}
__device__ __forceinline__ float bf_lo(uint32_t v) { return __uint_as_float(v << 16); }
__device__ __forceinline__ float bf_hi(uint32_t v) { return __uint_as_float(v & 0xffff0000u); }
__device__ __forceinline__ float ex2_fast(float x) { float y; asm("ex2.approx.ftz.f32 %0, %1;" : "=f"(y) : "f"(x)); return y; }
__device__ __forceinline__ float rcp_fast(float x) { float y; asm("rcp.approx.ftz.f32 %0, %1;" : "=f"(y) : "f"(x)); return y; }
__device__ __forceinline__ float round_bf16(float x) { return __bfloat162float(__float2bfloat16_rn(x)); }
__device__ __forceinline__ uint32_t clk32() { uint32_t t; asm volatile("mov.u32 %0, %%clock;" : "=r"(t) :: "memory"); return t; }

__device__ __forceinline__ void mma16816(float (&d)[4], uint32_t a0, uint32_t a1, uint32_t a2, uint32_t a3,
                                         uint32_t b0, uint32_t b1) {
  asm("mma.sync.aligned.m16n8k16.row.col.f32.bf16.bf16.f32 {%0,%1,%2,%3}, {%4,%5,%6,%7}, {%8,%9}, {%0,%1,%2,%3};"
      : "+f"(d[0]), "+f"(d[1]), "+f"(d[2]), "+f"(d[3])
      : "r"(a0), "r"(a1), "r"(a2), "r"(a3), "r"(b0), "r"(b1));
}
__device__ __forceinline__ void ldsm4t(uint32_t (&r)[4], uint32_t addr) {
  asm volatile("ldmatrix.sync.aligned.m8n8.x4.trans.shared.b16 {%0,%1,%2,%3}, [%4];"
               : "=r"(r[0]), "=r"(r[1]), "=r"(r[2]), "=r"(r[3]) : "r"(addr) : "memory");
}
__device__ __forceinline__ void stsm4(uint32_t addr, uint32_t a, uint32_t b, uint32_t c, uint32_t d) {
  asm volatile("stmatrix.sync.aligned.m8n8.x4.shared.b16 [%0], {%1,%2,%3,%4};" ::"r"(addr), "r"(a), "r"(b), "r"(c), "r"(d) : "memory");
}
__device__ __forceinline__ void stsm4t(uint32_t addr, uint32_t a, uint32_t b, uint32_t c, uint32_t d) {
  asm volatile("stmatrix.sync.aligned.m8n8.x4.trans.shared.b16 [%0], {%1,%2,%3,%4};" ::"r"(addr), "r"(a), "r"(b), "r"(c), "r"(d) : "memory");
}
__device__ __forceinline__ uint4 lds128(uint32_t a) {
  uint4 v; asm volatile("ld.shared.v4.b32 {%0,%1,%2,%3}, [%4];" : "=r"(v.x), "=r"(v.y), "=r"(v.z), "=r"(v.w) : "r"(a) : "memory"); return v;
}
__device__ __forceinline__ uint32_t lds32(uint32_t a) { uint32_t v; asm volatile("ld.shared.b32 %0, [%1];" : "=r"(v) : "r"(a) : "memory"); return v; }
__device__ __forceinline__ void sts32(uint32_t a, uint32_t x) { asm volatile("st.shared.b32 [%0], %1;" ::"r"(a), "r"(x) : "memory"); }
__device__ __forceinline__ void sts128(uint32_t a, uint4 v) {
  asm volatile("st.shared.v4.b32 [%0], {%1,%2,%3,%4};" ::"r"(a), "r"(v.x), "r"(v.y), "r"(v.z), "r"(v.w) : "memory");
}
__device__ __forceinline__ void cp16(uint32_t dst, const void* src) {
  asm volatile("cp.async.cg.shared.global [%0], [%1], 16;" ::"r"(dst), "l"(src) : "memory");
}
__device__ __forceinline__ void mbar_init(uint32_t mbar, uint32_t cnt) {
  asm volatile("mbarrier.init.shared.b64 [%0], %1;" ::"r"(mbar), "r"(cnt) : "memory");
}
__device__ __forceinline__ void mbar_expect_tx(uint32_t mbar, uint32_t bytes) {
  asm volatile("mbarrier.arrive.expect_tx.shared.b64 _, [%0], %1;" ::"r"(mbar), "r"(bytes) : "memory");
}
__device__ __forceinline__ void mbar_arrive_z(uint32_t mbar, uint32_t z) {
  asm volatile("{ .reg .pred p; setp.eq.u32 p, %1, 0; @p mbarrier.arrive.shared.b64 _, [%0]; }" ::"r"(mbar), "r"(z) : "memory");
}
__device__ __forceinline__ void mbar_expect_tx_z(uint32_t mbar, uint32_t bytes, uint32_t z) {
  asm volatile("{ .reg .pred p; setp.eq.u32 p, %2, 0; @p mbarrier.arrive.expect_tx.shared.b64 _, [%0], %1; }" ::"r"(mbar), "r"(bytes), "r"(z) : "memory");
}
__device__ __forceinline__ void mbar_arrive_remote_z(uint32_t mbar, uint32_t z) {
  asm volatile("{ .reg .pred p; setp.eq.u32 p, %1, 0; @p mbarrier.arrive.shared::cluster.b64 _, [%0]; }" ::"r"(mbar), "r"(z) : "memory");
}
__device__ __forceinline__ bool mbar_try(uint32_t mbar, uint32_t par) {
  uint32_t ok;
  asm volatile("{ .reg .pred p; mbarrier.try_wait.parity.shared::cta.b64 p, [%1], %2; selp.u32 %0, 1, 0, p; }"
               : "=r"(ok) : "r"(mbar), "r"(par) : "memory");
  return ok;
}
__device__ __forceinline__ void fail(int) { __trap(); }
__device__ __forceinline__ void give_up(int it, int limit, int code) { if (it > limit) fail(code); }
__device__ __forceinline__ void mbar_wait(uint32_t mbar, uint32_t par, int code) {
  asm volatile("{ .reg .pred p; .reg .b32 n; mov.b32 n, %2;\n"
               "W: mbarrier.try_wait.parity.shared::cta.b64 p, [%0], %1; @p bra D;\n"
               "add.s32 n, n, -1; setp.eq.s32 p, n, 0; @p trap; bra W;\n"
               "D: }" ::"r"(mbar), "r"(par), "n"(MBAR_LIMIT) : "memory");
}
__device__ __forceinline__ void mbar_gate(uint32_t mbar, uint32_t par) {
  const uint32_t t0 = clk32();
  while (!mbar_try(mbar, par) && clk32() - t0 < 20000) {}
}
__device__ __forceinline__ void bulk_g2s(uint32_t dst, const void* src, uint32_t bytes, uint32_t mbar) {
  asm volatile("cp.async.bulk.shared::cluster.global.mbarrier::complete_tx::bytes [%0], [%1], %2, [%3];"
               ::"r"(dst), "l"(src), "r"(bytes), "r"(mbar) : "memory");
}
__device__ __forceinline__ void bulk_s2r(uint32_t dst, uint32_t src, uint32_t bytes, uint32_t mbar) {
  asm volatile("cp.async.bulk.shared::cluster.shared::cta.mbarrier::complete_tx::bytes [%0], [%1], %2, [%3];"
               ::"r"(dst), "r"(src), "r"(bytes), "r"(mbar) : "memory");
}
__device__ __forceinline__ void bulk_s2g(void* dst, uint32_t src, uint32_t bytes) {
  asm volatile("cp.async.bulk.global.shared::cta.bulk_group [%0], [%1], %2;" ::"l"(dst), "r"(src), "r"(bytes) : "memory");
}
__device__ __forceinline__ void fence_async_smem() { asm volatile("fence.proxy.async.shared::cta;" ::: "memory"); }
__device__ __forceinline__ void fence_async_glb() { asm volatile("fence.proxy.async.global;" ::: "memory"); }
__device__ __forceinline__ void bar_sync(int id, int n) { asm volatile("bar.sync %0, %1;" ::"r"(id), "r"(n) : "memory"); }
__device__ __forceinline__ void bar_arrive(int id, int n) { asm volatile("bar.arrive %0, %1;" ::"r"(id), "r"(n) : "memory"); }
__device__ __forceinline__ void cluster_sync() { asm volatile("barrier.cluster.arrive.release; barrier.cluster.wait.acquire;" ::: "memory"); }
__device__ __forceinline__ uint32_t mapa_u32(uint32_t a, uint32_t r) {
  uint32_t o;
  asm("mapa.shared::cluster.u32 %0, %1, %2;" : "=r"(o) : "r"(a), "r"(r));
  return o;
}
template <int OFF>
__device__ __forceinline__ void st_async32(uint32_t a, uint32_t x, uint32_t mbar) {
  asm volatile("st.async.weak.shared::cluster.mbarrier::complete_tx::bytes.b32 [%0 + %3], %1, [%2];" ::"r"(a), "r"(x), "r"(mbar), "n"(OFF) : "memory");
}
__device__ __forceinline__ uint4 ld_rlx128(const void* p) {
  uint4 v;
  asm volatile("ld.relaxed.gpu.global.v4.u32 {%0,%1,%2,%3}, [%4];" : "=r"(v.x), "=r"(v.y), "=r"(v.z), "=r"(v.w) : "l"(p) : "memory");
  return v;
}
__device__ __forceinline__ uint2 ld_rlx64(const void* p) {
  uint2 v; asm volatile("ld.relaxed.gpu.global.v2.u32 {%0,%1}, [%2];" : "=r"(v.x), "=r"(v.y) : "l"(p) : "memory"); return v;
}
__device__ __forceinline__ uint32_t ld_rlx32(const void* p) {
  uint32_t v; asm volatile("ld.relaxed.gpu.global.u32 %0, [%1];" : "=r"(v) : "l"(p) : "memory"); return v;
}
__device__ __forceinline__ void st_rlx32(void* p, uint32_t a) { asm volatile("st.relaxed.gpu.global.u32 [%0], %1;" ::"l"(p), "r"(a) : "memory"); }
__device__ __forceinline__ void red_release(uint32_t* p) { asm volatile("red.release.gpu.global.add.u32 [%0], 1;" ::"l"(p) : "memory"); }
__device__ __forceinline__ void st_release32(void* p, uint32_t a) { asm volatile("st.release.gpu.global.u32 [%0], %1;" ::"l"(p), "r"(a) : "memory"); }
__device__ __forceinline__ void st_release_u64(void* p, u64 a) { asm volatile("st.release.gpu.global.u64 [%0], %1;" ::"l"(p), "l"(a) : "memory"); }
__device__ __forceinline__ void wait_count(const uint32_t* p, uint32_t val, int code) {
  int it = 0;
  while (ld_rlx32(p) < val) {
    give_up(++it, SPIN_LIMIT, code);
    __nanosleep(40);
  }
}
__device__ __forceinline__ u64 wait_keys(const u64* keys, int lane, int code) {
  u64 k;
  int it = 0;
  while (true) {
    asm volatile("ld.relaxed.gpu.global.u64 %0, [%1];" : "=l"(k) : "l"(keys + lane) : "memory");
    if (__all_sync(~0u, k != 0)) break;
    give_up(++it, SPIN_LIMIT, code);
    __nanosleep(100);
  }
  const uint32_t hi = __reduce_max_sync(~0u, (uint32_t)(k >> 32));
  const uint32_t lo = __reduce_max_sync(~0u, (uint32_t)(k >> 32) == hi ? (uint32_t)k : 0u);
  return (u64)hi << 32 | lo;
}
__device__ __forceinline__ int key_token(u64 k) { return (int)(~(uint32_t)k) & (NTOK - 1); }
__device__ __forceinline__ float key_score(u64 k) {
  const uint32_t ob = (uint32_t)(k >> 32);
  return __uint_as_float((ob & 0x80000000u) ? (ob & 0x7fffffffu) : ~ob);
}

__device__ __forceinline__ uint64_t mk_desc(uint32_t saddr, uint32_t lbo, uint32_t sbo, uint32_t sw) {
  return (uint64_t)((saddr & 0x3FFFF) >> 4) | (uint64_t)(lbo >> 4) << 16 | (uint64_t)(sbo >> 4) << 32 | (uint64_t)sw << 62;
}
template <int N> __device__ __forceinline__ void reg_inc() { asm volatile("setmaxnreg.inc.sync.aligned.u32 %0;" ::"n"(N)); }
template <int N> __device__ __forceinline__ void reg_dec() { asm volatile("setmaxnreg.dec.sync.aligned.u32 %0;" ::"n"(N)); }
__device__ __forceinline__ void wg_fence() { asm volatile("wgmma.fence.sync.aligned;" ::: "memory"); }
__device__ __forceinline__ void wg_commit() { asm volatile("wgmma.commit_group.sync.aligned;" ::: "memory"); }
template <int N> __device__ __forceinline__ void wg_wait() { asm volatile("wgmma.wait_group.sync.aligned %0;" ::"n"(N) : "memory"); }
template <int N> __device__ __forceinline__ void acc_fence(float (&d)[N]) {
#pragma unroll
  for (int i = 0; i < N; i++) asm volatile("" : "+f"(d[i]) :: "memory");
}
#define O4(d, i) "+f"(d[i]), "+f"(d[i + 1]), "+f"(d[i + 2]), "+f"(d[i + 3])
template <int TB, int ACC>
__device__ __forceinline__ void wg_rs8(float (&d)[4], const uint32_t (&a)[4], uint64_t db) {
  asm volatile("wgmma.mma_async.sync.aligned.m64n8k16.f32.bf16.bf16 {%0,%1,%2,%3}, {%4,%5,%6,%7}, %8, %9, 1, 1, %10;"
               : O4(d, 0) : "r"(a[0]), "r"(a[1]), "r"(a[2]), "r"(a[3]), "l"(db), "n"(ACC), "n"(TB));
}
template <int TB, int ACC>
__device__ __forceinline__ void wg_rs24(float (&d)[12], const uint32_t (&a)[4], uint64_t db) {
  asm volatile("wgmma.mma_async.sync.aligned.m64n24k16.f32.bf16.bf16 {%0,%1,%2,%3,%4,%5,%6,%7,%8,%9,%10,%11}, {%12,%13,%14,%15}, %16, %17, 1, 1, %18;"
               : O4(d, 0), O4(d, 4), O4(d, 8) : "r"(a[0]), "r"(a[1]), "r"(a[2]), "r"(a[3]), "l"(db), "n"(ACC), "n"(TB));
}
template <int TB, int ACC>
__device__ __forceinline__ void wg_rs32(float (&d)[16], const uint32_t (&a)[4], uint64_t db) {
  asm volatile("wgmma.mma_async.sync.aligned.m64n32k16.f32.bf16.bf16 {%0,%1,%2,%3,%4,%5,%6,%7,%8,%9,%10,%11,%12,%13,%14,%15}, {%16,%17,%18,%19}, %20, %21, 1, 1, %22;"
               : O4(d, 0), O4(d, 4), O4(d, 8), O4(d, 12) : "r"(a[0]), "r"(a[1]), "r"(a[2]), "r"(a[3]), "l"(db), "n"(ACC), "n"(TB));
}
template <int ACC>
__device__ __forceinline__ void wg_rs64(float (&d)[32], uint32_t a0, uint32_t a1, uint32_t a2, uint32_t a3, uint64_t db) {
  asm volatile("wgmma.mma_async.sync.aligned.m64n64k16.f32.bf16.bf16 {%0,%1,%2,%3,%4,%5,%6,%7,%8,%9,%10,%11,%12,%13,%14,%15,"
               "%16,%17,%18,%19,%20,%21,%22,%23,%24,%25,%26,%27,%28,%29,%30,%31}, {%32,%33,%34,%35}, %36, %37, 1, 1, 0;"
               : O4(d, 0), O4(d, 4), O4(d, 8), O4(d, 12), O4(d, 16), O4(d, 20), O4(d, 24), O4(d, 28)
               : "r"(a0), "r"(a1), "r"(a2), "r"(a3), "l"(db), "n"(ACC));
}
template <int ACC>
__device__ __forceinline__ void wg_ss24(float (&d)[12], uint64_t da, uint64_t db) {
  asm volatile("wgmma.mma_async.sync.aligned.m64n24k16.f32.bf16.bf16 {%0,%1,%2,%3,%4,%5,%6,%7,%8,%9,%10,%11}, %12, %13, %14, 1, 1, 1, 0;"
               : O4(d, 0), O4(d, 4), O4(d, 8) : "l"(da), "l"(db), "n"(ACC));
}
template <int ACC>
__device__ __forceinline__ void wg_ss40(float (&d)[20], uint64_t da, uint64_t db) {
  asm volatile("wgmma.mma_async.sync.aligned.m64n40k16.f32.bf16.bf16 {%0,%1,%2,%3,%4,%5,%6,%7,%8,%9,%10,%11,%12,%13,%14,%15,%16,%17,%18,%19}, %20, %21, %22, 1, 1, 1, 1;"
               : O4(d, 0), O4(d, 4), O4(d, 8), O4(d, 12), O4(d, 16) : "l"(da), "l"(db), "n"(ACC));
}

struct Row { uint32_t w[8]; };
__device__ __forceinline__ uint32_t add_bf16x2(uint32_t a, uint32_t b) {
  uint32_t d; asm("add.rn.bf16x2 %0, %1, %2;" : "=r"(d) : "r"(a), "r"(b)); return d;
}
__device__ __forceinline__ Row warp_ln(const Row& r, float& extra) {
  float x[16];
#pragma unroll
  for (int i = 0; i < 8; i++) { x[2 * i] = bf_lo(r.w[i]); x[2 * i + 1] = bf_hi(r.w[i]); }
  float m = (((x[0] + x[1]) + (x[2] + x[3])) + ((x[4] + x[5]) + (x[6] + x[7]))) + (((x[8] + x[9]) + (x[10] + x[11])) + ((x[12] + x[13]) + (x[14] + x[15])));
  m *= (1.f / 16);
  float v0 = 0.f, v1 = 0.f;
#pragma unroll
  for (int i = 0; i < 16; i += 2) { const float d0 = x[i] - m, d1 = x[i + 1] - m; v0 = fmaf(d0, d0, v0); v1 = fmaf(d1, d1, v1); }
  float v = v0 + v1;
#pragma unroll
  for (int o = 1; o <= 16; o <<= 1) {
    const float mo = __shfl_xor_sync(~0u, m, o), vo = __shfl_xor_sync(~0u, v, o);
    extra += __shfl_xor_sync(~0u, extra, o);
    const float d = mo - m;
    v = fmaf(d * d, 8.f * o, v + vo);
    m = 0.5f * (m + mo);
  }
  const float var = fmaf(v, 1.f / DM, 1e-5f);
  float rs = rsqrtf(var);
  rs = rs * fmaf(-0.5f * var * rs, rs, 1.5f);
  Row y;
#pragma unroll
  for (int i = 0; i < 8; i++) y.w[i] = pack_bf16((x[2 * i] - m) * rs, (x[2 * i + 1] - m) * rs);
  return y;
}
__device__ __forceinline__ Row warp_ln(const Row& r) { float e = 0.f; return warp_ln(r, e); }
__device__ __forceinline__ Row load_row(const bf16* p, int lane) {
  Row r;
#pragma unroll
  for (int q = 0; q < 4; q++) { const uint2 v = ld_rlx64(p + lane * 4 + q * 128); r.w[2 * q] = v.x; r.w[2 * q + 1] = v.y; }
  return r;
}
__device__ __forceinline__ void store_row(bf16* p, int lane, const Row& r) {
#pragma unroll
  for (int q = 0; q < 4; q++) *(uint2*)(p + lane * 4 + q * 128) = make_uint2(r.w[2 * q], r.w[2 * q + 1]);
}
__device__ __forceinline__ void store_row_img(uint8_t* grp, int rr, int lane, const Row& r) {
  uint8_t* p = grp + (lane >> 4) * 1024 + rr * 128 + ((((lane & 15) >> 1) ^ rr) << 4) + (lane & 1) * 8;
#pragma unroll
  for (int q = 0; q < 4; q++) *(uint2*)(p + q * 2048) = make_uint2(r.w[2 * q], r.w[2 * q + 1]);
}

__global__ void __launch_bounds__(256) prep_kernel(const bf16* __restrict__ x0) {
  const int lane = threadIdx.x & 31, row = blockIdx.x * 8 + (threadIdx.x >> 5);
  const Row r = load_row(x0 + (size_t)row * DM, lane);
  const int gt = blockIdx.x * 256 + threadIdx.x, nt = gridDim.x * 256;
  uint4* M = (uint4*)g_M;
  for (int i = gt; i < 4 * 16384 / 4; i += nt) M[i] = make_uint4(~0u, ~0u, ~0u, ~0u);
  uint4* P = (uint4*)g_P;
  for (int i = gt; i < 96 * 4096 / 4; i += nt) P[i] = make_uint4(0, 0, 0, 0);
  uint4* F = (uint4*)&g_fl;
  for (int i = gt; i < (int)(sizeof(Flags) / 16); i += nt) F[i] = make_uint4(0, 0, 0, 0);
  store_row_img(g_xs[0] + (size_t)blockIdx.x * 8192, row & 7, lane, warp_ln(r));
}

constexpr int W_STRIDE = 272;
constexpr int C_WO = 0;
constexpr int C_X = 49152;
constexpr int C_M = C_X + 9 * 8192;
constexpr int C_Q = C_M + 24576;
constexpr int C_K = C_Q + 10240, C_V = C_K + 10240;
constexpr int C_SA = C_V + 10240, C_SB = C_SA + 8192, C_SP = C_SB + 8192;
constexpr int C_O = C_SP + 2048;
constexpr int C_OT = C_O + 6144;
constexpr int C_BAR = C_OT + 8192;
constexpr int C_SMEM = C_BAR + 256 + 1024 + TREXTRA;
static_assert(C_X + 512 * W_STRIDE <= C_BAR, "staging");
enum { B_M0 = 0, B_M1, B_M2, B_R, B_X = B_R + 4, B_O, B_T, B_F, B_XL1, B_XL2, B_XL3, B_P1, B_P2, B_P3, B_OT, B_XF, B_NUM };
constexpr int C_INFO = C_BAR + 160, C_POL = C_BAR + 192;
enum { NB_ALL = 0, NB_M0, NB_PV, NB_W0, NB_TA, NB_X1, NB_M1, NB_M2, NB_RD };
constexpr float SCALE_LOG2E = 0.08838834764831845f * 1.4426950408889634f;
#define N0STEPS 9
#define N2STEPS 12
#define OGATE 3
#define OEARLY 1
#define SHIPLATE 0
#define XGATE 3
#define SHIP 1024
#define GATE_P 2700
#define GATE_W 200
#define GATE_G 200
#define GATE_M 3850
#define HOLE0 29
#define HOLE1 32
#define HOLE2 32
__device__ __forceinline__ uint32_t gtime() { uint32_t t; asm volatile("mov.u32 %0, %%globaltimer_lo;" : "=r"(t) :: "memory"); return t; }
__device__ __forceinline__ void wait_clock(uint32_t t) { while ((int)(clk32() - t) < 0) {} }
__device__ __forceinline__ bool bar_or(int id, int n, uint32_t v) {
  uint32_t r;
  asm volatile("{ .reg .pred p, q; setp.ne.u32 p, %1, 0; bar.red.or.pred q, %2, %3, p; vote.sync.any.pred q, q, 0xffffffff; selp.u32 %0, 1, 0, q; }"
               : "=r"(r) : "r"(v), "r"(id), "r"(n) : "memory");
  return r;
}
__device__ __forceinline__ void bar_sync_z(int id, int n, uint32_t z) {
  asm volatile("{ .reg .pred p; setp.eq.u32 p, %2, 0; @p bar.sync %0, %1; }" ::"r"(id), "r"(n), "r"(z) : "memory");
}

__device__ __forceinline__ uint32_t probe_polarity(uint32_t* p) {
  uint32_t best[2] = {~0u, ~0u};
#pragma unroll 1
  for (int rep = 0; rep < 4; rep++) {
#pragma unroll
    for (int pg = 0; pg < 2; pg++) {
      uint32_t t0, t1, v;
      asm volatile("mov.u32 %0, %%clock;" : "=r"(t0) :: "memory");
      asm volatile("atom.relaxed.gpu.global.add.u32 %0, [%1], 0;" : "=r"(v) : "l"(p + pg * 1024) : "memory");
      asm volatile("{ .reg .pred p; setp.ne.u32 p, %1, 0x13572468; mov.u32 %0, 0; @p mov.u32 %0, %%clock; }" : "=r"(t1) : "r"(v) : "memory");
      if (rep > 0) best[pg] = min(best[pg], t1 - t0);
    }
  }
  return best[1] < best[0] ? 1u : 0u;
}
__device__ __forceinline__ uint32_t ppage(uint32_t lp, uint32_t pol) { return lp ? 3 - pol : pol; }
__device__ __forceinline__ uint32_t and_x(uint32_t a, uint32_t b, uint32_t m) {
  uint32_t d; asm("lop3.b32 %0, %1, %2, %3, 0x42;" : "=r"(d) : "r"(a), "r"(b), "r"(m)); return d;
}
__device__ __forceinline__ uint32_t and3(uint32_t a, uint32_t b, uint32_t c) {
  uint32_t d; asm("lop3.b32 %0, %1, %2, %3, 0x80;" : "=r"(d) : "r"(a), "r"(b), "r"(c)); return d;
}

template <int N> struct IC { static constexpr int value = N; };
template <class F> __device__ __forceinline__ void static_for2(F f) { f(IC<0>()); f(IC<1>()); }
template <class F> __device__ __forceinline__ void static_for3(F f) { f(IC<0>()); f(IC<1>()); f(IC<2>()); }
__device__ __forceinline__ void load_wfrags(uint32_t (&wA)[32][4], uint32_t stage, int w, int lane) {
  const int mi = lane >> 3, r = lane & 7;
#pragma unroll
  for (int ks = 0; ks < 32; ks++) ldsm4t(wA[ks], stage + (ks * 16 + (mi >> 1) * 8 + r) * W_STRIDE + (w * 16 + (mi & 1) * 8) * 2);
}
template <int K0, int K1>
__device__ __forceinline__ void tok_seq(float (&d)[16], const uint32_t (&wA)[32][4], uint64_t desc, uint32_t wave) {
#pragma unroll
  for (int k = K0; k < K1; k++) {
    const int ks = k & 31;
    constexpr int HM0 = 1, HM1 = 2, HM2 = 4;
    const int hm = (k == HOLE0 ? HM0 : 0) | (k == HOLE1 ? HM1 : 0) | (k == HOLE2 ? HM2 : 0);
    if (hm) bar_sync_z(NB_RD, 384, ((hm >> wave) & 1) ^ 1);
    if (ks == 0) wg_rs32<0, 0>(d, wA[ks], desc);
    else wg_rs32<0, 1>(d, wA[ks], desc + (ks >> 2) * 64 + (ks & 3) * 2);
  }
}
template <int K0, int K1>
__device__ __forceinline__ void mem_part(float (&d)[12], const uint32_t (&wA)[32][4], uint64_t desc) {
#pragma unroll
  for (int ks = K0; ks < K1; ks++) {
    if (ks == 0) wg_rs24<1, 0>(d, wA[ks], desc);
    else wg_rs24<1, 1>(d, wA[ks], desc + ks * 48);
  }
}
__device__ __forceinline__ void out_tile(float (&d)[12], uint64_t da, uint64_t db) {
#pragma unroll
  for (int i = 0; i < 8; i++) { if (i == 0) wg_ss24<0>(d, da, db); else wg_ss24<1>(d, da + i * 128, db + (i >> 1) * 32 + (i & 1) * 2); }
}
__device__ __forceinline__ void tok_pack(uint32_t (&p)[8], const float (&d)[16]) {
#pragma unroll
  for (int i = 0; i < 8; i++) p[i] = pack_bf16(d[2 * i], d[2 * i + 1]);
}
__device__ __forceinline__ void tok_store(uint32_t dst, const uint32_t (&p)[8]) {
  stsm4(dst, p[0], p[1], p[2], p[3]);
  stsm4(dst + 4096, p[4], p[5], p[6], p[7]);
}
template <class T> __device__ __forceinline__ T keep(T v) { asm volatile("" : "+r"(v)); return v; }
__device__ __forceinline__ uint32_t pin(uint32_t v) { return __shfl_sync(~0u, v, threadIdx.x & 31); }

#define TRC blockIdx.x
#define TRS (C_BAR + 256)
__device__ __forceinline__ void chain_proj(const uint32_t sb, const int w, const int lane_, const uint32_t rank) {
  uint32_t wA[32][4];
  load_wfrags(wA, sb + C_X, w, lane_);
  bar_sync(NB_ALL, 512);
  bar_sync(NB_ALL, 512);
  cluster_sync();
  const int lane = pin(lane_);
  const uint32_t bars = sb + C_BAR;
  const uint32_t quad = pin(sb + (lane_ >> 4) * 2048 + (lane_ & 15) * 16);
  const uint32_t own = C_Q + rank * 10240;
  const uint64_t dX1 = mk_desc(sb + C_X, 16, 8192, 1), dX2 = dX1 + 2048, dX3 = dX1 + 4096;
  const uint64_t dM = mk_desc(sb + C_M, 128, 256, 0);
  const uint32_t r1 = rank == 0 ? 1 : 0, r2 = rank == 2 ? 1 : 2;
  const uint32_t xa = pin(sb + own + 8192 + w * 256 + lane_ * 4);
  const uint32_t a1x = pin(mapa_u32(xa, r1)), a2x = pin(mapa_u32(xa, r2));
  const uint32_t b1x = pin(mapa_u32(bars + B_X * 8, r1)), b2x = pin(mapa_u32(bars + B_X * 8, r2));
  const uint32_t wave = rank == 2 ? 0 : rank + 1;
  uint32_t npatch = 0;
  constexpr int K3 = 32 - N0STEPS - N2STEPS;
  float a[16];
  bar_sync(NB_X1, 288);
  wg_fence();
  tok_seq<32, 32 + K3>(a, wA, dX1, 3);
  wg_commit();
  wg_wait<0>();
#pragma unroll 1
  for (int st = 0; st < NSTEP; st++) {
    uint32_t pk[8];
    wg_fence();
    tok_seq<32 + K3, 32 + K3 + N0STEPS>(a, wA, dX1, 3);
    TR(0)
    bar_sync(NB_PV, 384);
    tok_seq<32 + K3 + N0STEPS, 64>(a, wA, dX1, 3);
    wg_commit();
    wg_wait<0>();
    acc_fence(a);
    mbar_arrive_z(bars + B_XF * 8, lane);
    tok_pack(pk, a);
    TR(1)
    bar_sync(NB_W0, 416);
    tok_store(quad + w * 256 + (rank == 0 ? own : C_SA), pk);
    __syncwarp();
    mbar_arrive_z(bars + B_P2 * 8, lane);
    wg_fence();
    tok_seq<0, 32>(a, wA, dX2, wave);
    wg_commit();
    const uint32_t info = lds32(sb + C_INFO + (st & 1) * 4);
    TR(2)
    wg_wait<0>();
    acc_fence(a);
    TR(3)
    tok_pack(pk, a);
    tok_store(quad + w * 256 + (rank == 0 ? C_SA : own), pk);
    if (rank == 2) tok_store(quad + w * 256 + C_SB, pk);
    __syncwarp();
    mbar_arrive_z(bars + B_P1 * 8, lane);
    if (__builtin_expect(info & 4, 0)) {
      float a3[4];
      mbar_wait(bars + B_XL3 * 8, npatch & 1, 32);
      npatch++;
      wg_fence();
#pragma unroll
      for (int ks = 0; ks < 32; ks++) {
        if (ks == 0) wg_rs8<0, 0>(a3, wA[ks], dX3);
        else wg_rs8<0, 1>(a3, wA[ks], dX3 + (ks >> 2) * 64 + (ks & 3) * 2);
      }
      wg_commit();
      wg_wait<0>();
      acc_fence(a3);
      const uint32_t dst = sb + (rank == 2 ? own + (info & 3) * 2048 : C_SP) + w * 256 + lane * 4;
      sts32(dst, pack_bf16(a3[0], a3[1])); sts32(dst + 128, pack_bf16(a3[2], a3[3]));
      __syncwarp();
      mbar_arrive_z(bars + B_P3 * 8, lane);
    }
    TR(4)
    bar_sync(NB_X1, 288);
    wg_fence();
    tok_seq<32, 32 + K3>(a, wA, dX1, wave);
    TR(6)
    {
      float am[12];
      bar_sync(NB_M0, 384);
      mem_part<0, 10>(am, wA, dM);
      TR(7)
      bar_sync(NB_M1, 384);
      mem_part<10, 21>(am, wA, dM);
      const bool redo = bar_or(NB_M2, 384, 0);
      mem_part<21, 32>(am, wA, dM);
      wg_commit();
      wg_wait<0>();
      if (__builtin_expect(redo, 0)) {
        bar_sync(NB_M0, 384);
        wg_fence();
        mem_part<0, 32>(am, wA, dM);
        wg_commit();
        wg_wait<0>();
      }
      acc_fence(am);
      TR(8)
      const uint32_t x00 = pack_bf16(am[0], am[1]), x01 = pack_bf16(am[2], am[3]), x10 = pack_bf16(am[4], am[5]), x11 = pack_bf16(am[6], am[7]);
      uint32_t x20 = pack_bf16(am[8], am[9]), x21 = pack_bf16(am[10], am[11]);
      if (info & 4) { x20 = x10; x21 = x11; }
      st_async32<0>(a1x, rank == 0 ? x10 : x00, b1x); st_async32<0>(a2x, rank == 2 ? x10 : x20, b2x);
      st_async32<128>(a1x, rank == 0 ? x11 : x01, b1x); st_async32<128>(a2x, rank == 2 ? x11 : x21, b2x);
      sts32(xa, rank == 0 ? x00 : rank == 2 ? x20 : x10); sts32(xa + 128, rank == 0 ? x01 : rank == 2 ? x21 : x11);
      __syncwarp();
      mbar_arrive_z(bars + B_X * 8, lane);
      if (w == 7) {
        const uint32_t stamp = (gtime() & ~31u) | ((st + 1) & 31);
        asm volatile("{ .reg .pred p; setp.eq.u32 p, %2, 0; @p st.relaxed.gpu.global.u32 [%0], %1; }" ::"l"(&g_fl.stamp[blockIdx.x]), "r"(stamp), "r"(lane) : "memory");
      }
    }
    TR(9)
  }
}

__device__ __forceinline__ void chain_mem(const uint32_t sb, const int w, const int lane_, const uint32_t rank, const int h,
                                          const bf16* __restrict__ mem0) {
  const int lane = pin(lane_);
  const int wave = rank == 2 ? 0 : rank + 1;
  const int c = w - 8, t = c * 32 + lane, b = wave * 32 + h;
  const uint32_t bars = sb + C_BAR;
  uint32_t pgbits = 0;
  {
    uint32_t pol = 1;
    const int tl = lane / 3, u = ((tl * 3 + rank) * 4 + c) * 3 + (lane - tl * 3);
    if (lane < 9 && u < 96) {
      int it = 0;
      while ((pol = ld_rlx32(&g_fl.pol[u])) == 0) give_up(++it, SPIN_LIMIT, 40);
    }
    pgbits = __reduce_or_sync(~0u, lane < 9 ? ppage(h >> 4, (pol - 1) & 1) << (2 * lane) : 0u);
  }
  const int wi = (lane & 1) * 2 + (lane >> 4), cq = (lane >> 2) & 3;
  bar_sync(NB_ALL, 512);
#pragma unroll 1
  for (int i = t; i < 2048; i += 128) {
    const unsigned short* mp = (const unsigned short*)mem0 + 2 * (i & 3) * DM + (i >> 2);
    const uint32_t v = (uint32_t)mp[0] | (uint32_t)mp[DM] << 16;
    const uint32_t a = sb + C_M + (i >> 6) * 768 + (i & 63) * 4;
    sts32(a, v); sts32(a + 256, v); sts32(a + 512, v);
  }
  fence_async_smem();
  mbar_expect_tx_z(bars + B_X * 8, 4096, t); mbar_expect_tx_z(bars + B_O * 8, 4096, t);
  bar_sync(NB_ALL, 512);
  cluster_sync();
  bar_arrive(NB_PV, 384); bar_arrive(NB_W0, 416); bar_arrive(NB_M0, 384); bar_arrive(NB_M1, 384);
  bar_arrive(NB_RD, 384);

  const int mi = lane >> 3;
  const uint32_t l16 = pin(sb + lane * 16);
  const uint32_t r1 = rank == 2 ? 0 : rank + 1, r2 = rank == 0 ? 2 : rank - 1;
  const uint32_t oa = pin(sb + C_O + rank * 2048 + (lane >> 2) * 64 + (((lane & 3) ^ (lane >> 3)) << 4));
  const uint32_t a1 = mapa_u32(oa, r1), b1 = mapa_u32(bars + B_O * 8, r1), a2 = mapa_u32(oa, r2), b2 = mapa_u32(bars + B_O * 8, r2);
  const uint64_t dWo = mk_desc(sb + C_WO, 8192, 1024, 1), dO = mk_desc(sb + C_O, 16, 2048, 2);
  const uint64_t dQ = mk_desc(sb + C_Q, 128, 2048, 0), dK = mk_desc(sb + C_K, 128, 2048, 0);
  const uint64_t dV = mk_desc(sb + C_V, 2048, 128, 0), dVm = mk_desc(sb + C_V + 8192, 0, 128, 0);
  const int lim = pin(c < 2 ? 16 * c + (lane >> 2) - 2 * (lane & 3) : 64);
  uint8_t* Pw = (uint8_t*)g_P + (rank * 4 + c) * 3 * 16384 + (h & 15) * 256 + lane * 4;
  const uint32_t polP = lds32(sb + C_POL + 16);
  const uint8_t* Pr0 = (const uint8_t*)g_P + b * 16384 + ((lane >> 4) * 4 + (lane & 3)) * 256 + c * 64 + cq * 16 + ppage(0, polP) * 4096;
  const uint8_t* Pr1 = Pr0 + (3 - 2 * polP) * 4096;
  uint8_t* Mw = (uint8_t*)g_M + (b >> 5) * 16384 + ((lane & 2) ? 4096 : 12288) + (b & 31) * 256 + c * 64 + cq * 16 + wi * 4;
  uint32_t nretry = 0;
  const uint32_t gate_p = GATE_P + wave * GATE_W;

  (void)bar_or(NB_M2, 384, 0);
#pragma unroll 1
  for (int st = 0;; st++) {
    mbar_wait(bars + B_T * 8, st & 1, 42);
    STAT(10, clk32())
    mbar_wait(bars + B_X * 8, st & 1, 41);
    STAT(11, clk32())
    fence_async_smem();
    TR(0)
    {
      float s[20];
      wg_fence();
#pragma unroll
      for (int i = 0; i < 8; i++) { if (i == 0) wg_ss40<0>(s, dQ, dK); else wg_ss40<1>(s, dQ + i * 16, dK + i * 16); }
      wg_commit();
      wg_wait<0>();
      acc_fence(s);
      TR(1)
#pragma unroll
      for (int j = 0; j < 4; j++) {
        if (lim < 8 * j) s[4 * j] = -INFINITY;
        if (lim < 8 * j + 1) s[4 * j + 1] = -INFINITY;
        if (lim < 8 * j - 8) s[4 * j + 2] = -INFINITY;
        if (lim < 8 * j - 7) s[4 * j + 3] = -INFINITY;
      }
      float m0 = fmaxf(fmaxf(fmaxf(s[0], s[1]), fmaxf(s[4], s[5])), fmaxf(fmaxf(s[8], s[9]), fmaxf(s[12], s[13])));
      float m1 = fmaxf(fmaxf(fmaxf(s[2], s[3]), fmaxf(s[6], s[7])), fmaxf(fmaxf(s[10], s[11]), fmaxf(s[14], s[15])));
      m0 = fmaxf(m0, fmaxf(s[16], s[17])); m1 = fmaxf(m1, fmaxf(s[18], s[19]));
      m0 = fmaxf(m0, __shfl_xor_sync(~0u, m0, 1)); m1 = fmaxf(m1, __shfl_xor_sync(~0u, m1, 1));
      m0 = fmaxf(m0, __shfl_xor_sync(~0u, m0, 2)); m1 = fmaxf(m1, __shfl_xor_sync(~0u, m1, 2));
      m0 *= -SCALE_LOG2E; m1 *= -SCALE_LOG2E;
      uint32_t p[10];
      float l0 = 0.f, l1 = 0.f;
#pragma unroll
      for (int k = 0; k < 10; k++) {
        const float e0 = ex2_fast(fmaf(s[2 * k], SCALE_LOG2E, (k & 1) ? m1 : m0)), e1 = ex2_fast(fmaf(s[2 * k + 1], SCALE_LOG2E, (k & 1) ? m1 : m0));
        p[k] = pack_bf16(e0, e1);
        if (k & 1) l1 += e0 + e1; else l0 += e0 + e1;
      }
      asm volatile("" : "+f"(l0), "+f"(l1));
      float oA[32], oB[32];
      wg_fence();
      wg_rs64<0>(oA, p[0], p[1], p[2], p[3], dV); wg_rs64<1>(oA, p[4], p[5], p[6], p[7], dV + 256); wg_rs64<1>(oA, p[8], p[9], 0, 0, dVm);
      wg_commit();
      wg_rs64<0>(oB, p[0], p[1], p[2], p[3], dV + 64); wg_rs64<1>(oB, p[4], p[5], p[6], p[7], dV + 320); wg_rs64<1>(oB, p[8], p[9], 0, 0, dVm + 64);
      wg_commit();
      l0 += __shfl_xor_sync(~0u, l0, 1); l1 += __shfl_xor_sync(~0u, l1, 1);
      l0 += __shfl_xor_sync(~0u, l0, 2); l1 += __shfl_xor_sync(~0u, l1, 2);
      const float i0 = rcp_fast(l0), i1 = rcp_fast(l1);
      const bool mrows = c == 2 && st < NSTEP - 1;
      auto send = [&](const float (&o)[32], auto hc) {
        constexpr int H = decltype(hc)::value;
        static_for2([&](auto bc) {
          constexpr int B = decltype(bc)::value, J = 16 * B;
          asm volatile("st.async.weak.shared::cluster.mbarrier::complete_tx::bytes.v4.b32 [%0 + %9], {%5,%6,%7,%8}, [%1];\n"
                       "st.async.weak.shared::cluster.mbarrier::complete_tx::bytes.v4.b32 [%2 + %9], {%5,%6,%7,%8}, [%3];\n"
                       "st.shared.v4.b32 [%4 + %9], {%5,%6,%7,%8};"
                       ::"r"(a1), "r"(b1), "r"(a2), "r"(b2), "r"(oa), "r"(pack_bf16(o[J] * i0, o[J + 1] * i0)), "r"(pack_bf16(o[J + 4] * i0, o[J + 5] * i0)),
                         "r"(pack_bf16(o[J + 8] * i0, o[J + 9] * i0)), "r"(pack_bf16(o[J + 12] * i0, o[J + 13] * i0)), "n"(H * 1024 + B * 512) : "memory");
        });
      };
      auto keep_tok = [&](const float (&o)[32], int H) {
        const uint32_t ta = l16 + C_OT + c * 4096 + H * 1024;
#pragma unroll
        for (int k = 0; k < 4; k++) {
          const int J = (k & 1) * 16 + (k >> 1) * 2;
          const float iv = (k >> 1) ? i1 : i0;
          stsm4(ta + (k & 1) * 512 + (k >> 1) * 2048, pack_bf16(o[J] * iv, o[J + 1] * iv), pack_bf16(o[J + 4] * iv, o[J + 5] * iv),
                pack_bf16(o[J + 8] * iv, o[J + 9] * iv), pack_bf16(o[J + 12] * iv, o[J + 13] * iv));
        }
      };
      wg_wait<1>();
      acc_fence(oA);
      if (mrows) send(oA, IC<0>());
      wg_wait<0>();
      acc_fence(oB);
      if (st < NSTEP - 1) bar_arrive(NB_PV, 384);
      if (mrows) {
        send(oB, IC<1>());
        __syncwarp();
        mbar_arrive_z(bars + B_O * 8, lane);
      } else if (c < 2) {
        keep_tok(oA, 0);
        keep_tok(oB, 1);
        __syncwarp();
        mbar_arrive_z(bars + B_OT * 8, lane);
      }
      TR(2)
      if (st == NSTEP - 1) break;
      mbar_expect_tx_z(bars + B_X * 8, 4096, t);
    }
    uint32_t tref;
    {
      const uint32_t tag = (st & 1) ^ 1;
      float oc0[12], oc1[12], oc2[12];
      mbar_wait(bars + B_O * 8, st & 1, 43);
      fence_async_smem();
      TR(3)
      wg_fence();
      out_tile(oc0, dWo, dO);
      wg_commit();
      out_tile(oc1, dWo + 1024, dO);
      wg_commit();
      asm volatile("" : "+r"(pgbits));
      auto put = [&](const float (&oc)[12], auto tlc) {
        constexpr int TL = decltype(tlc)::value;
        static_for3([&](auto jc) {
          constexpr int j = decltype(jc)::value;
          uint8_t* p = Pw + ((pgbits >> (2 * (TL * 3 + j))) & 3) * 4096;
          asm volatile("st.relaxed.gpu.global.u32 [%0 + %3], %1; st.relaxed.gpu.global.u32 [%0 + %3 + 128], %2;" ::"l"(p),
                       "r"((pack_bf16(oc[4 * j], oc[4 * j + 1]) & ~1u) | tag), "r"((pack_bf16(oc[4 * j + 2], oc[4 * j + 3]) & ~1u) | tag),
                       "n"((TL * 36 + j) * 16384) : "memory");
        });
      };
      wg_wait<1>();
      acc_fence(oc0);
      put(oc0, IC<0>());
      sts32(sb + C_INFO + 24, clk32());
      TR(4)
      wg_wait<0>();
      if (rank != 2) {
        wg_fence();
        out_tile(oc2, dWo + 2048, dO);
        wg_commit();
        acc_fence(oc1);
        put(oc1, IC<1>());
        bar_sync(NB_TA, 160);
        TR(5)
        wg_wait<0>();
        bar_arrive(NB_W0, 416);
        acc_fence(oc2);
        put(oc2, IC<2>());
      } else {
        bar_arrive(NB_W0, 416);
        acc_fence(oc1);
        put(oc1, IC<1>());
        bar_sync(NB_TA, 160);
      }
      tref = __shfl_sync(~0u, lds32(sb + C_INFO + 12), 0);
      mbar_arrive_remote_z(((t & 1) ? b2 : b1) + (B_F - B_O) * 8, t >> 1);
      mbar_expect_tx_z(bars + B_O * 8, 4096, t);
      TR(6)
    }
    const int sn = (st + 1) & 3;
    {
      const uint32_t flip = (st & 1) ? ~0u : 0u;
      const bool u16 = lane & 16;
      uint8_t* mw = Mw + sn * 65536;
      asm volatile("" : "+l"(mw));
      const uint32_t bs = (lane & 4) ? 0x3f800000u : 0x00003f80u, bs0 = (lane & 8) ? 0u : bs, bs1 = (lane & 8) ? bs : 0u;
      const bool early = st < DELTA && b % 3 != 0;
      uint32_t m0word = 0;
      if (__builtin_expect(early, 0)) {
        const unsigned short* mp = (const unsigned short*)mem0 + ((lane & 1) * 4 + (lane >> 4) * 2) * DM + b / 3 * 16 + c * 4 + ((lane >> 2) & 3);
        m0word = (uint32_t)mp[0] | (uint32_t)mp[DM] << 16;
      }
      STATC(c_rdy)
      wait_clock(tref + gate_p);
      TR(7)
      uint32_t mword;
      int it = 0;
      bool all;
#pragma unroll 1
      do {
        const uint4 q0 = ld_rlx128(Pr0), q1 = ld_rlx128(Pr0 + 2048), q2 = ld_rlx128(Pr1), q3 = ld_rlx128(Pr1 + 2048);
        float d0[4] = {0.f, 0.f, 0.f, 0.f}, d1[4] = {0.f, 0.f, 0.f, 0.f};
        mma16816(d0, q0.x, q0.y, q0.z, q0.w, bs0, bs1);
        mma16816(d1, q1.x, q1.y, q1.z, q1.w, bs0, bs1);
        mma16816(d0, q2.x, q2.y, q2.z, q2.w, bs0, bs1);
        mma16816(d1, q3.x, q3.y, q3.z, q3.w, bs0, bs1);
        all = __all_sync(~0u, (int)and3(and_x(q0.x, q1.x, flip), and_x(q2.x, q3.x, flip), 1u));
        const float a0 = d0[0] + d1[0], a1 = d0[1] + d1[1], a2 = d0[2] + d1[2], a3 = d0[3] + d1[3];
        mword = pack_bf16((u16 ? a2 : a0) + __shfl_xor_sync(~0u, u16 ? a0 : a2, 16), (u16 ? a3 : a1) + __shfl_xor_sync(~0u, u16 ? a1 : a3, 16));
        asm volatile("{ .reg .pred p; setp.ne.u32 p, %2, 0; @p st.relaxed.gpu.global.u32 [%0], %1; }" ::"l"(mw), "r"(early ? m0word : mword), "r"((uint32_t)all) : "memory");
      } while (__builtin_expect(!all, 0) && ++it < SPIN_LIMIT);
      bar_arrive(NB_RD, 384);
      STATC(c_mst)
      STAT(0, lds32(sb + C_INFO + 24) - tref) STAT(1, c_rdy - tref) STAT(2, c_mst - tref) STAT(3, tref) STAT(4, it)
      if (!all) fail(44);
      TRV(14, it)
    }
    TR(9)
    {
      const uint32_t ma = l16 + C_M + c * 2048 + mi * 4;
      auto scan = [&](uint32_t m, uint32_t a) { return __vimax3_u32(__vimax3_u32(m, lds32(a), lds32(a + 512)), lds32(a + 1024), lds32(a + 1536)); };
      mbar_wait(bars + B_M0 * 8, (st + 1) & 1, 45);
      bar_arrive(NB_M0, 384);
      STATC(c_g0)
      TR(10)
      uint32_t m = scan(0, ma);
      mbar_wait(bars + B_M1 * 8, (st + 1) & 1, 46);
      bar_arrive(NB_M1, 384);
      STATC(c_g1)
      TR(11)
      m = scan(m, ma + 8192);
      mbar_wait(bars + B_M2 * 8, (st + 1) & 1, 47);
      STATC(c_g2)
      TR(12)
      int it = 0;
      const bool redo = bar_or(NB_M2, 384, scan(m, ma + 16384) == ~0u);
      if (__builtin_expect(redo, 0)) {
#pragma unroll 1
        for (int g = 0; g < 3;) {
          if (!__any_sync(~0u, scan(0, ma + g * 8192) == ~0u)) { g++; continue; }
          give_up(++it, SPIN_LIMIT, 48);
          if (lane == 0) {
            mbar_expect_tx(bars + (B_R + c) * 8, 2048);
            bulk_g2s(sb + C_M + g * 8192 + c * 2048, (const uint8_t*)g_M + sn * 65536 + (lds32(sb + C_POL + sn * 4) ? 4096 : 12288) + g * 16384 + c * 2048,
                     2048, bars + (B_R + c) * 8);
          }
          __syncwarp();
          mbar_wait(bars + (B_R + c) * 8, nretry++ & 1, 49);
        }
        bar_arrive(NB_M0, 384);
      }
      STAT(5, c_g0 - tref) STAT(7, c_g1 - tref) STAT(8, c_g2 - tref)
      STAT(9, clk32() - tref) STAT(6, it + redo * 256)
      TR(13)
      TRV(15, it)
      st_rlx32(Mw + (st & 3) * 65536, ~0u);
    }
  }
}

__device__ __forceinline__ void chain_dma(const uint32_t sb, const int w, const int lane, const uint32_t rank, const int h) {
  const uint32_t bars = sb + C_BAR;
  bar_sync(NB_ALL, 512);
  if (w == 12) { HD(3) }
  bar_sync(NB_ALL, 512);
  if (w == 12) { HD(4) }
  cluster_sync();
  if (w == 12) { HD(5) }
  if (w == 12) {
    u64 best = 0;
    uint32_t npatch = 0;
#pragma unroll 1
    for (int st = -1; st < NSTEP; st++) {
      const int sg = st - DELTA;
      uint32_t info = 0;
      if (st >= 0) {
        if (sg >= 0) {
          const u64 k = wait_keys(g_fl.key[0][sg], lane, 50);
          if (k > best) { best = k; info = 4 | ((key_token(k) >> 3) & 3); }
        }
        TR(0)
        if (st > 0) mbar_wait(bars + B_P1 * 8, (st - 1) & 1, 51);
        sts32(sb + C_INFO + (st & 1) * 4, info);
        if (sg >= 0) {
          if (XGATE == 3) mbar_wait(bars + B_X * 8, (st - 1) & 1, 58);
          else if ((int)lds32(sb + C_INFO + 8) < st - 1) mbar_gate(bars + (B_M0 + XGATE) * 8, (st - 1) & 1);
          TR(1)
          if (lane == 0) {
            fence_async_glb();
            mbar_expect_tx(bars + B_XL2 * 8, 32768);
            bulk_g2s(sb + C_X + 32768, g_xs[1] + (size_t)sg * 32768, 32768, bars + B_XL2 * 8);
          }
          __syncwarp();
          mbar_wait(bars + B_XL2 * 8, sg & 1, 52);
        }
        TR(2)
        bar_arrive(NB_W0, 416);
        mbar_wait(bars + B_XF * 8, st & 1, 53);
      }
      if (st + 1 < NSEG) {
        if (lane == 0) {
          mbar_expect_tx(bars + B_XL1 * 8, 32768);
          bulk_g2s(sb + C_X, g_xs[0] + (size_t)(st + 1) * 32768, 32768, bars + B_XL1 * 8);
        }
        __syncwarp();
        mbar_wait(bars + B_XL1 * 8, (st + 1) & 1, 57);
      }
      TR(3)
      if (st < 1) { HD(7 + st) }
      bar_arrive(NB_X1, 288);
      if (__builtin_expect(info, 0)) {
        if (npatch > 0) mbar_wait(bars + B_P3 * 8, (npatch - 1) & 1, 55);
        npatch++;
        wait_count(g_fl.patch[sg], 1, 56);
        if (lane == 0) {
          fence_async_glb();
          mbar_expect_tx(bars + B_XL3 * 8, 8192);
          bulk_g2s(sb + C_X + 65536, g_patch + (size_t)sg * 8192, 8192, bars + B_XL3 * 8);
        }
        __syncwarp();
      }
    }
  } else if (w == 13) {
    constexpr uint32_t NP = 8192 / SHIP;
    const uint32_t o = (lane >> 1) * SHIP, own = sb + C_Q + rank * 10240, bt = bars + B_T * 8;
    const uint32_t d2 = 1 + (lane & 1);
    const uint32_t src2 = (rank == 0 ? sb + C_SA : rank == 1 ? own : sb + C_SB) + o;
    const uint32_t skip = (lane & 1) ? 4 | (o >> 11) : 8;
    uint32_t npatch = 0;
#pragma unroll 1
    for (int st = 0; st < NSTEP; st++) {
      mbar_wait(bars + (SHIPLATE ? B_P1 : B_P2) * 8, st & 1, 62);
      fence_async_smem();
      if (st > 0) mbar_wait(bars + B_F * 8, (st - 1) & 1, 60);
      const uint32_t info = lds32(sb + C_INFO + (st & 1) * 4);
      TR(2)
      if (st < NSEG && rank != 0 && lane < 2 * NP && d2 == 1) bulk_s2r(mapa_u32(own + o, 0), sb + C_SA + o, SHIP, mapa_u32(bt, 0));
      __syncwarp();
      TR(3)
      mbar_wait(bars + B_P1 * 8, st & 1, 61);
      fence_async_smem();
      TR(0)
      if (st >= DELTA && lane < 2 * NP && d2 != rank && info != skip) bulk_s2r(mapa_u32(own + o, d2), src2, SHIP, mapa_u32(bt, d2));
      __syncwarp();
      TR(1)
      if (__builtin_expect(info, 0)) {
        mbar_wait(bars + B_P3 * 8, npatch & 1, 63);
        npatch++;
        fence_async_smem();
        if (rank != 2 && lane == 0) bulk_s2r(mapa_u32(own + (info & 3) * 2048, 2), sb + C_SP, 2048, mapa_u32(bt, 2));
        __syncwarp();
      }
    }
  } else if (w == 14) {
    const int s0 = rank == 0 ? 0 : DELTA;
    mbar_expect_tx_z(bars + B_T * 8, s0 == 0 ? 16384 : 0, lane);
#pragma unroll 1
    for (int st = 0; st < NSTEP; st++) {
      const int sg = st - s0;
      const bool act = (unsigned)sg < (unsigned)NSEG;
      mbar_wait(bars + B_OT * 8, st & 1, 70);
      fence_async_smem();
      if (OGATE >= 0 && st < NSTEP - 1 && (rank != 0 || !OEARLY)) mbar_wait(bars + (OGATE > 0 ? B_M0 + OGATE - 1 : B_F) * 8, (st + (OGATE > 0)) & 1, 71);
      TR(0)
      if (lane == 0) {
        if (act) bulk_s2g(g_O[rank] + ((size_t)(sg & (OSLOTS - 1)) * 32 + h) * 8192, sb + C_OT, 8192);
        asm volatile("cp.async.bulk.commit_group;" ::: "memory");
        asm volatile("cp.async.bulk.wait_group.read 0;" ::: "memory");
        mbar_expect_tx(bars + B_T * 8, (unsigned)(sg + 1) < (unsigned)NSEG ? 16384 : 0);
        asm volatile("cp.async.bulk.wait_group 0;" ::: "memory");
        if (act) red_release(&g_fl.oflag[rank][sg][h >> 2]);
      }
      __syncwarp();
      TR(1)
    }
  } else {
    mbar_arrive_z(bars + B_M0 * 8, lane); mbar_arrive_z(bars + B_M1 * 8, lane); mbar_arrive_z(bars + B_M2 * 8, lane);
    const uint32_t gate_g = GATE_G, gate_m = GATE_M;
#pragma unroll 1
    for (int st = 0; st < NSTEP; st++) {
      mbar_wait(bars + B_M2 * 8, st & 1, 74);
      sts32(sb + C_INFO + 8, st);
      if (st == NSTEP - 1) break;
      mbar_wait(bars + B_X * 8, st & 1, 75);
      if (st < 4) { HD(8 + st) }
      if (st == NSTEP - 2) { HD(12) }
      const uint32_t now = gtime() & ~31u, tag = (st + 1) & 31;
      uint32_t s0, s1, s2;
      int it = 0;
#pragma unroll 1
      do {
        s0 = ld_rlx32(&g_fl.stamp[lane]) ^ tag; s1 = ld_rlx32(&g_fl.stamp[32 + lane]) ^ tag; s2 = ld_rlx32(&g_fl.stamp[64 + lane]) ^ tag;
        give_up(it++, SPIN_LIMIT, 76);
      } while (__any_sync(~0u, ((s0 | s1 | s2) & 31) != 0));
      const uint32_t tref = now + __reduce_max_sync(~0u, __vimax3_s32((int)(s0 - now), (int)(s1 - now), (int)(s2 - now)));
      const uint32_t g0 = gtime();
      uint32_t g1, c1;
      it = 0;
      do { g1 = gtime(); c1 = clk32(); } while (g1 == g0 && ++it < 64);
      c1 -= (g1 - tref) * 7 / 4;
      sts32(sb + C_INFO + 12, c1);
      TR(0)
      bar_arrive(NB_TA, 160);
      const int sn = (st + 1) & 3;
      const uint8_t* src = (const uint8_t*)g_M + sn * 65536 + (lds32(sb + C_POL + sn * 4) ? 4096 : 12288);
      c1 += gate_m;
      const int d = (int)(c1 - 600 - clk32());
      if (d > 0) __nanosleep(d / 4);
#pragma unroll 1
      for (int g = 0; g < 3; g++) {
        mbar_expect_tx_z(bars + (B_M0 + g) * 8, 8192, lane);
        wait_clock(c1 + g * gate_g);
        if (lane == 0) bulk_g2s(sb + C_M + g * 8192, src + g * 16384, 8192, bars + (B_M0 + g) * 8);
        __syncwarp();
        TR(1 + g)
      }
    }
  }
}

__global__ void __cluster_dims__(3, 1, 1) __launch_bounds__(512, 1)
chain_kernel(const bf16* __restrict__ Wq, const bf16* __restrict__ Wk, const bf16* __restrict__ Wv,
             const bf16* __restrict__ Wo, const bf16* __restrict__ mem0) {
  extern __shared__ __align__(1024) uint8_t smem_raw[];
  const uint32_t sb = (smem_u32(smem_raw) + 1023) & ~1023u;
  const int tid = threadIdx.x, lane = tid & 31;
  const int w = __shfl_sync(~0u, tid >> 5, 0);
  uint32_t rank;
  asm volatile("mov.u32 %0, %%cluster_ctarank;" : "=r"(rank));
  const int h = blockIdx.x / 3;
  asm volatile("griddepcontrol.launch_dependents;" ::: "memory");
  TG(0)
  if (tid == 0) {
    const uint32_t bars = sb + C_BAR;
    mbar_init(bars + B_M0 * 8, 1); mbar_init(bars + B_M1 * 8, 1); mbar_init(bars + B_M2 * 8, 1);
    for (int i = 0; i < 4; i++) mbar_init(bars + (B_R + i) * 8, 1);
    mbar_init(bars + B_X * 8, 9); mbar_init(bars + B_O * 8, 2); mbar_init(bars + B_T * 8, 1); mbar_init(bars + B_F * 8, 2);
    mbar_init(bars + B_XL1 * 8, 1); mbar_init(bars + B_XL2 * 8, 1); mbar_init(bars + B_XL3 * 8, 1);
    mbar_init(bars + B_P1 * 8, 8); mbar_init(bars + B_P2 * 8, 8); mbar_init(bars + B_P3 * 8, 8); mbar_init(bars + B_OT * 8, 2); mbar_init(bars + B_XF * 8, 8);
    asm volatile("fence.mbarrier_init.release.cluster;" ::: "memory");
  }
  {
    const bf16* W1 = (rank == 0 ? Wq : rank == 1 ? Wk : Wv) + h * 128;
#pragma unroll 4
    for (int cidx = tid; cidx < 512 * 16; cidx += 512) {
      const int d = cidx >> 4, q = cidx & 15;
      cp16(sb + C_X + d * W_STRIDE + q * 16, W1 + (size_t)d * HD + q * 8);
    }
    const int nt = rank == 2 ? 2 : 3;
    for (int cidx = tid; cidx < nt * 1024; cidx += 512) {
      const int tl = cidx >> 10, e = (cidx >> 3) & 127, q = cidx & 7;
      const int es = (e & ~30) | ((e & 6) << 2) | ((e >> 2) & 6);
      cp16(sb + C_WO + tl * 16384 + e * 128 + ((q ^ (e & 7)) << 4), Wo + (size_t)(h * 128 + es) * DM + (tl * 3 + rank) * 64 + q * 8);
    }
    asm volatile("cp.async.commit_group;" ::: "memory");
    if (w == 0) { HD(0) }
    if (lane == 0) {
      if (w < 4) sts32(sb + C_POL + w * 4, probe_polarity(g_M + w * 16384 + (blockIdx.x & 31) * 32));
      else if (w == 4) {
        const int u = (rank == 2 ? 0 : rank + 1) * 32 + h;
        const uint32_t pol = probe_polarity(g_P + u * 4096);
        sts32(sb + C_POL + 16, pol);
        st_rlx32(&g_fl.pol[u], pol + 1);
      }
    }
    if (w == 0) { HD(1) }
    asm volatile("cp.async.wait_group 0;" ::: "memory");
    fence_async_smem();
    __syncthreads();
    if (w == 0) { HD(2) }
  }
  if (w < 8) {
    reg_inc<184>();
    chain_proj(sb, w, lane, rank);
    TG(1)
    TRDUMP
    cluster_sync();
  } else if (w < 12) {
    reg_dec<120>();
    chain_mem(sb, w, lane, rank, h, mem0);
    STATDUMP
    TRDUMP
    cluster_sync();
  } else {
    reg_dec<24>();
    chain_dma(sb, w, lane, rank, h);
    TRDUMP
    cluster_sync();
  }
}
#undef TRC
#undef TRS

constexpr int K_BAR = 0, K_LN = 128, K_FH = 320, K_FS = 512, K_FY = 2048;
constexpr int K_W = 3072;
constexpr int K_O = K_W + 3 * 49152;
constexpr int K_ST = K_O + 65536;
constexpr int K_SMEM = K_ST + 16384;
static_assert(K_SMEM <= 232448 && 512 * W_STRIDE <= 3 * 49152, "shared memory");
enum { KB_FULL = 0, KB_EMPTY = 2, KB_OK = 4, KB_GO = 7, KB_ST = 10, KB_REL = 12 };
enum { KN_ST = 1, KN_ST1, KN_REL, KN_FFN, KN_INIT, KN_RES, KN_CAND, KN_TAKEN };
#define GATE_R 450
struct WorkerParams {
  const bf16 *x0, *Wo, *w_r, *w_gate, *w_up, *w_down;
  bf16* out;
};
#define TRC (96 + blockIdx.x)
#define FT(e)
#define FOR_UNITS _Pragma("unroll 1") for (int st = 0, n = 0; st < NSTEP; st++) \
                  _Pragma("unroll 1") for (int v = st < NSEG ? 0 : 1, sg = v ? st - DELTA : st; v < (st >= DELTA ? 3 : 1); v++, n++, sg = st - DELTA)

__device__ __forceinline__ void ffn_slice(uint32_t sb, int t, int nu, const bf16* yrow, int ev) {
  const int lane = t & 31, c = t >> 5;
  FT(1)
  const uint32_t sg_ = sb + (nu == 3 ? K_FS : K_ST), sh = sb + K_FH;
  {
    const uint2 r = ld_rlx64(yrow + t * 4);
    asm volatile("st.shared.v2.b32 [%0], {%1,%2};" ::"r"(sb + K_FY + t * 8), "r"(r.x), "r"(r.y) : "memory");
    __syncwarp();
  }
  const uint32_t sy = sb + K_FY + (t >> 2) * 32;
  FT(2)
#pragma unroll 1
  for (int u = 0; u < nu; u++) {
    float g[8];
#pragma unroll
    for (int i = 0; i < 8; i++) g[i] = 0.f;
    const uint32_t wa = sb + K_W + u * 49152 + c * 8192 + lane * 16;
    auto fma8 = [&](float y, const uint4& a) {
      g[0] += y * bf_lo(a.x); g[1] += y * bf_hi(a.x); g[2] += y * bf_lo(a.y); g[3] += y * bf_hi(a.y);
      g[4] += y * bf_lo(a.z); g[5] += y * bf_hi(a.z); g[6] += y * bf_lo(a.w); g[7] += y * bf_hi(a.w);
    };
    uint4 a0 = lds128(wa), a1 = lds128(wa + 512);
    uint32_t y0 = lds32(sy);
#pragma unroll 1
    for (int i = 0; i < 16; i += 4) {
      const uint4 b0 = lds128(wa + (i + 2) * 512), b1 = lds128(wa + (i + 3) * 512);
      const uint32_t y1 = lds32(sy + i * 2 + 4);
      fma8(bf_lo(y0), a0); fma8(bf_hi(y0), a1);
      a0 = lds128(wa + (i + 4) * 512); a1 = lds128(wa + (i + 5) * 512);
      y0 = lds32(sy + i * 2 + 8);
      fma8(bf_lo(y1), b0); fma8(bf_hi(y1), b1);
    }
#pragma unroll
    for (int i = 0; i < 4; i++) g[i] = ((lane & 16) ? g[4 + i] : g[i]) + __shfl_xor_sync(~0u, (lane & 16) ? g[i] : g[4 + i], 16);
#pragma unroll
    for (int i = 0; i < 2; i++) g[i] = ((lane & 8) ? g[2 + i] : g[i]) + __shfl_xor_sync(~0u, (lane & 8) ? g[i] : g[2 + i], 8);
    g[0] = ((lane & 4) ? g[1] : g[0]) + __shfl_xor_sync(~0u, (lane & 4) ? g[0] : g[1], 4);
    sts32(sg_ + u * 512 + c * 128 + ((lane & 3) * 8 + (lane >> 2)) * 4, __float_as_uint(g[0]));
  }
  FT(3)
  bar_sync(KN_FFN, 128);
  {
    const uint32_t pa = sg_ + c * 512 + lane * 4;
    const float gt = round_bf16((__uint_as_float(lds32(pa)) + __uint_as_float(lds32(pa + 128))) + (__uint_as_float(lds32(pa + 256)) + __uint_as_float(lds32(pa + 384))));
    const float up = __shfl_xor_sync(~0u, gt, 16);
    if (lane < 16 && c < nu) sts32(sh + (c * 16 + lane) * 4, __float_as_uint(round_bf16(round_bf16(gt / (1.f + __expf(-gt))) * up)));
  }
  bar_sync(KN_FFN, 128);
  FT(4)
  float a0 = 0.f, a1 = 0.f, a2 = 0.f, a3 = 0.f;
#pragma unroll 1
  for (int u = 0; u < 2 * nu; u++) {
    const uint32_t wa = sb + K_W + (u >> 1) * 49152 + 32768 + (u & 1) * 8192 + t * 8;
    const uint4 h0 = lds128(sh + u * 32), h1 = lds128(sh + u * 32 + 16);
    const uint32_t hv[8] = {h0.x, h0.y, h0.z, h0.w, h1.x, h1.y, h1.z, h1.w};
    uint2 d[8];
#pragma unroll
    for (int k = 0; k < 8; k++) asm volatile("ld.shared.v2.b32 {%0,%1}, [%2];" : "=r"(d[k].x), "=r"(d[k].y) : "r"(wa + k * 1024) : "memory");
#pragma unroll
    for (int k = 0; k < 8; k++) {
      const float hf = __uint_as_float(hv[k]);
      a0 += hf * bf_lo(d[k].x); a1 += hf * bf_hi(d[k].x); a2 += hf * bf_lo(d[k].y); a3 += hf * bf_hi(d[k].y);
    }
  }
  FT(5)
  asm volatile("red.relaxed.gpu.global.add.v4.f32 [%0], {%1,%2,%3,%4};" ::"l"(&g_fl.upd[ev][t * 4]), "f"(a0), "f"(a1), "f"(a2), "f"(a3) : "memory");
  bar_sync(KN_FFN, 128);
  if (t == 96) red_release(g_fl.ffncnt[ev]);
  __syncwarp();
}
__device__ __forceinline__ Row ffn_finish(int ver, int ev, u64 key, int lane) {
  const int tok = key_token(key);
  Row x = load_row(g_rows[ver][0] + (size_t)tok * DM, lane);
  const Row y = load_row(g_rows[ver][1] + (size_t)tok * DM, lane);
  const float sig = round_bf16(1.f / (1.f + __expf(-key_score(key))));
  wait_count(g_fl.ffncnt[ev], NWORK, 80);
#pragma unroll
  for (int q = 0; q < 4; q++) {
    const uint4 u = ld_rlx128(&g_fl.upd[ev][q * 128 + lane * 4]);
    const uint32_t a = pack_bf16(__uint_as_float(u.x), __uint_as_float(u.y)), b = pack_bf16(__uint_as_float(u.z), __uint_as_float(u.w));
    x.w[2 * q] = add_bf16x2(x.w[2 * q], add_bf16x2(y.w[2 * q], pack_bf16(bf_lo(a) * sig, bf_hi(a) * sig)));
    x.w[2 * q + 1] = add_bf16x2(x.w[2 * q + 1], add_bf16x2(y.w[2 * q + 1], pack_bf16(bf_lo(b) * sig, bf_hi(b) * sig)));
  }
  return x;
}
__device__ __forceinline__ uint2 group_ln(uint2 r, float& e, uint32_t sl, uint32_t sw, int lane) {
  const float x0 = bf_lo(r.x), x1 = bf_hi(r.x), x2 = bf_lo(r.y), x3 = bf_hi(r.y);
  const float s = (x0 + x1) + (x2 + x3), q = fmaf(x0, x0, x1 * x1) + fmaf(x2, x2, x3 * x3);
  const bool u16 = lane & 16, u8 = lane & 8;
  const float a = (u16 ? q : s) + __shfl_xor_sync(~0u, u16 ? s : q, 16), b = e + __shfl_xor_sync(~0u, e, 16);
  float v = (u8 ? b : a) + __shfl_xor_sync(~0u, u8 ? a : b, 8);
  v += __shfl_xor_sync(~0u, v, 4); v += __shfl_xor_sync(~0u, v, 2); v += __shfl_xor_sync(~0u, v, 1);
  sts32(sl + sw, __float_as_uint(v));
  bar_sync(KN_RES, 128);
  const uint4 ss = lds128(sl), qq = lds128(sl + 32), ee = lds128(sl + 16);
  const float m = ((__uint_as_float(ss.x) + __uint_as_float(ss.y)) + (__uint_as_float(ss.z) + __uint_as_float(ss.w))) * (1.f / DM);
  const float m2 = ((__uint_as_float(qq.x) + __uint_as_float(qq.y)) + (__uint_as_float(qq.z) + __uint_as_float(qq.w))) * (1.f / DM);
  e = (__uint_as_float(ee.x) + __uint_as_float(ee.y)) + (__uint_as_float(ee.z) + __uint_as_float(ee.w));
  float rs;
  asm("rsqrt.approx.ftz.f32 %0, %1;" : "=f"(rs) : "f"(fmaxf(fmaf(-m, m, m2), 0.f) + 1e-5f));
  return make_uint2(pack_bf16((x0 - m) * rs, (x1 - m) * rs), pack_bf16((x2 - m) * rs, (x3 - m) * rs));
}
__device__ __forceinline__ uint32_t score_bits(float r) {
  const uint32_t b = pack_bf16(0.f, r);
  return (b & 0x80000000u) ? ~b : (b | 0x80000000u);
}

__global__ void __launch_bounds__(640, 1) worker_kernel(const __grid_constant__ WorkerParams prm) {
  extern __shared__ __align__(1024) uint8_t smem_raw[];
  const uint32_t sb = smem_u32(smem_raw);
  const int tid = threadIdx.x, lane = tid & 31;
  const int w = __shfl_sync(~0u, tid >> 5, 0);
  const int me = blockIdx.x, kb = me >> 2, cb = me & 3;
  const bool full = me < 32;
  const uint32_t bars = sb + K_BAR;
  TG(0)
  if (tid == 0) {
    for (int i = 0; i < 2; i++) { mbar_init(bars + (KB_FULL + i) * 8, 1); mbar_init(bars + (KB_EMPTY + i) * 8, 1); }
    for (int i = 0; i < 9; i++) mbar_init(bars + (KB_OK + i) * 8, i < 3 ? 4 : 1);
    sts32(sb + K_LN + 144, 0); sts32(sb + K_LN + 176, 0); sts32(sb + K_LN + 180, ~0u);
    asm volatile("fence.mbarrier_init.release.cluster;" ::: "memory");
  }
  if (full) {
    const bf16* W1 = prm.Wo + (size_t)kb * 512 * DM + cb * 128;
#pragma unroll 4
    for (int cidx = tid; cidx < 512 * 16; cidx += 640) {
      const int d = cidx >> 4, q = cidx & 15;
      cp16(sb + K_W + d * W_STRIDE + q * 16, W1 + (size_t)d * DM + q * 8);
    }
    asm volatile("cp.async.commit_group;" ::: "memory");
    asm volatile("cp.async.wait_group 0;" ::: "memory");
  }
  fence_async_smem();
  __syncthreads();
  if (w < 8) {
    reg_inc<176>();
    if (full) {
      uint32_t wA[32][4];
      load_wfrags(wA, sb + K_W, w, lane);
      bar_arrive(KN_INIT, 384);
      const uint32_t sp = pin(sb + K_ST + ((lane >> 4) * 8 + (lane & 7)) * 256 + (((2 * w + ((lane >> 3) & 1)) ^ (lane & 7)) << 4));
      const uint32_t tm = pin(lane < 4 ? 0x00010001u : 0u);
      FOR_UNITS {
        float d[16];
        mbar_wait(bars + (KB_FULL + (n & 1)) * 8, (n >> 1) & 1, 81);
        TR(4 * v)
        const uint64_t db = mk_desc(sb + K_O + (n & 1) * 32768, 128, 2048, 0);
        wg_fence();
#pragma unroll
        for (int ks = 0; ks < 32; ks++) {
          if (ks == 0) wg_rs32<0, 0>(d, wA[ks], db);
          else wg_rs32<0, 1>(d, wA[ks], db + (ks >> 3) * 512 + (ks & 7) * 16);
        }
        wg_commit();
        mbar_wait(bars + (KB_ST + (n & 1)) * 8, ((n >> 1) & 1) ^ 1, 82);
        wg_wait<0>();
        acc_fence(d);
        TR(4 * v + 1)
        const uint32_t tag = (sg & 2) ? 0u : tm;
        uint32_t pk[8];
#pragma unroll
        for (int i = 0; i < 8; i++) pk[i] = (pack_bf16(d[2 * i], d[2 * i + 1]) & ~tm) | tag;
        stsm4t(sp + (n & 1) * 8192, pk[0], pk[1], pk[2], pk[3]);
        stsm4t(sp + (n & 1) * 8192 + 4096, pk[4], pk[5], pk[6], pk[7]);
        bar_arrive(KN_ST + (n & 1), 288);
        TR(4 * v + 2)
      }
    }
  } else if (w < 12) {
    reg_dec<56>();
    if (full) {
      const int t = pin(tid - 256), ln = t & 31;
      const uint32_t sw = pin((lane >> 3) * 16 + (w - 8) * 4);
      const uint32_t so = pin((w - 8) * 8192 + me * 256 + ((lane * 8) ^ ((me & 7) << 4)));
      uint2 wr = ld_rlx64(prm.w_r + t * 4);
      int sstar = -1;
      auto records = [&](int sg) {
        uint4 r;
        int it = 0;
        while ((int)(r = lds128(sb + K_LN + 144)).x <= sg) { give_up(++it, SPIN_LIMIT, 86); __nanosleep(50); }
        return r;
      };
      uint32_t sl = sb + K_LN;
      float rr = 0.f;
      int kprev = -1, pv = 0, psg = 0;
      uint2 x = make_uint2(0, 0);
      auto finish = [&](int v, int sg) {
        bf16* dst = g_rows[v][0] + (sg * 32 + me) * DM + t * 4;
        *(uint2*)dst = x;
        sl ^= 64;
        const uint2 y = group_ln(x, rr, sl, sw, ln);
        *(uint2*)(dst + NTOK * DM) = y;
        x = make_uint2(add_bf16x2(x.x, y.x), add_bf16x2(x.y, y.y));
        *(uint2*)(v == (sg < sstar ? 1 : 2) ? prm.out + (sg * 32 + me) * DM + t * 4 : dst + 2 * NTOK * DM) = x;
        asm volatile("{ .reg .pred p; setp.eq.u32 p, %2, 0; @p st.relaxed.gpu.global.u64 [%0], %1; }" ::"l"(&g_fl.key[0][0][0] + max(kprev, 0)),
                     "l"((u64)score_bits(rr) << 32 | (uint32_t)~(kprev & (NTOK - 1))), "r"(t | (kprev < 0)) : "memory");
        kprev = v * NTOK + sg * 32 + me;
        asm volatile("" : "+r"(wr.x), "+r"(wr.y));
        rr = fmaf(bf_lo(y.x), bf_lo(wr.x), bf_hi(y.x) * bf_hi(wr.x)) + fmaf(bf_lo(y.y), bf_lo(wr.y), bf_hi(y.y) * bf_hi(wr.y));
      };
      FOR_UNITS {
        const uint8_t* src = g_part[v] + (sg & 1) * (32 * 8192) + so;
        const bf16* xin = (v ? g_rows[0][2] : prm.x0) + (sg * 32 + me) * DM;
        if (v == 2) {
          const uint4 r = records(sg);
          if (((sg < 32 ? r.y : r.z) >> (sg & 31)) & 1) xin = g_x2p + sg * DM;
        }
        mbar_wait(bars + (KB_GO + v) * 8, sg & 1, 87);
        TR(4 * v)
        uint2 p[8];
#pragma unroll
        for (int k = 0; k < 8; k++) p[k] = ld_rlx64(src + k * 32768);
        const uint2 x0 = ld_rlx64(xin + t * 4);
        if (pv) finish(pv, psg);
        const uint32_t flip = lds32(sb + K_LN + 176 + (sg & 2) * 2);
        int it = 0;
#pragma unroll 1
        while (__builtin_expect(!__all_sync(~0u, (int)and3(and3(and_x(p[0].x, p[1].x, flip), and_x(p[2].x, p[3].x, flip), 1u),
                                                           and_x(p[4].x, p[5].x, flip), and_x(p[6].x, p[7].x, flip)) | (t & 1)), 0)) {
          give_up(++it, SPIN_LIMIT, 85);
#pragma unroll
          for (int k = 0; k < 8; k++) p[k] = ld_rlx64(src + k * 32768);
        }
        mbar_arrive_z(bars + (KB_OK + v) * 8, ln);
#define P8(h, f) (((h(p[0].f) + h(p[1].f)) + (h(p[2].f) + h(p[3].f))) + ((h(p[4].f) + h(p[5].f)) + (h(p[6].f) + h(p[7].f))))
        x = make_uint2(add_bf16x2(x0.x, pack_bf16(P8(bf_lo, x), P8(bf_hi, x))), add_bf16x2(x0.y, pack_bf16(P8(bf_lo, y), P8(bf_hi, y))));
#undef P8
        TRV(12 + v, it)
        TR(4 * v + 1)
        pv = v; psg = sg;
        if (v == 0 || (v == 2 && sg == NSEG - 1)) {
          finish(v, sg);
          sl ^= 64;
          const uint2 y = group_ln(x, rr, sl, sw, ln);
          if (v == 0) *(uint2*)(g_xs[1] + (sg * 4 + (me >> 3)) * 8192 + (t >> 4) * 1024 + (me & 7) * 128 + ((((t & 15) >> 1) ^ (me & 7)) << 4) + (t & 1) * 8) = y;
          sts32(sb + K_LN + 128, score_bits(rr));
          bar_arrive(KN_REL, 160);
          kprev = -1;
          if (__builtin_expect(v == 0 && sg == NSEG - 1, 0)) {
            sstar = records(NSEG - 1).w;
            const int nc = min(sstar, NSEG - 1 - DELTA);
#pragma unroll 1
            for (int s0 = 0; s0 < nc; s0 += 8) {
              uint2 r[8];
#pragma unroll
              for (int i = 0; i < 8; i++) r[i] = ld_rlx64(g_rows[1][2] + (min(s0 + i, nc - 1) * 32 + me) * DM + t * 4);
#pragma unroll
              for (int i = 0; i < 8; i++) *(uint2*)(prm.out + (min(s0 + i, nc - 1) * 32 + me) * DM + t * 4) = r[i];
            }
          }
        }
        TR(4 * v + 2)
      }
    }
  } else if (w < 16) {
    reg_dec<48>();
    const int t = tid - 384, nu = full ? 3 : 4;
    if (full) bar_sync(KN_INIT, 384);
    {
      const int j0 = (full ? me * 3 : 96 + (me - 32) * 4) * 16;
#pragma unroll 1
      for (int i = t; i < nu * 3072; i += 128) {
        const int u = i / 3072, r = i - u * 3072;
        const bf16* src = r < 2048 ? ((r & 2) ? prm.w_up : prm.w_gate) + (size_t)((r >> 9) * 128 + ((r >> 2) & 7) * 16 + ((r >> 5) & 15)) * FF + j0 + u * 16 + (r & 1) * 8
                                   : prm.w_down + (size_t)(j0 + u * 16) * DM + (r - 2048) * 8;
        cp16(sb + K_W + i * 16, src);
      }
      asm volatile("cp.async.wait_all;" ::: "memory");
    }
#pragma unroll 1
    while (true) {
      bar_sync(KN_CAND, 160);
      const uint4 cand = lds128(sb + K_LN + 160);
      bar_arrive(KN_TAKEN, 160);
      const u64 k = (u64)cand.y << 32 | cand.x;
      const int sg = cand.z, ver = cand.w, tok = key_token(k);
      const int ev = sg;
      (void)ev;
      FT(0)
      const bool owner = (tok & 31) == me;
      uint8_t* dst = g_patch + (size_t)(sg & (NSEG - 1)) * 8192;
      ffn_slice(sb, t, nu, g_rows[ver][1] + (size_t)tok * DM, sg);
      if (owner) {
        if (w == 12) {
          FT(6)
          const Row x = ffn_finish(ver, sg, k, lane);
          FT(7)
          store_row(ver ? prm.out + (size_t)tok * DM : g_x2p + sg * DM, lane, x);
          if (ver == 0) store_row_img(dst, tok & 7, lane, warp_ln(x));
        } else if (w < 15 && ver == 0) {
          const uint8_t* src = g_xs[1] + (size_t)(tok >> 3) * 8192 + (t - 32) * 16;
          uint4 q[8];
#pragma unroll
          for (int i = 0; i < 8; i++) q[i] = ld_rlx128(src + i * 1024);
          if (((t - 32) >> 3) != (tok & 7)) {
#pragma unroll
            for (int i = 0; i < 8; i++) *(uint4*)(dst + (t - 32) * 16 + i * 1024) = q[i];
          }
        }
        bar_sync(KN_FFN, 128);
        if (t == 0 && ver == 0) st_release32(g_fl.patch[sg], 1);
        __syncwarp();
      }
      FT(8)
      if (ver) break;
    }
  } else {
    reg_dec<24>();
    if (w == 16) {
      u64 best = 0, mask = 0;
      bool first = true;
#pragma unroll 1
      for (int sg = 0; sg <= NSEG; sg++) {
        u64 k = wait_keys(sg < NSEG ? g_fl.key[0][sg] : g_fl.key[2][NSEG - 1], lane, 91);
        uint32_t ver = 0;
        if (sg == NSEG) {
          HD(6)
          const int sstar = key_token(best) >> 5;
          u64 m = 0;
#pragma unroll 4
          for (int s2 = 0; s2 < NSEG; s2++) {
            u64 k2;
            asm volatile("ld.relaxed.gpu.global.u64 %0, [%1];" : "=l"(k2) : "l"(&g_fl.key[s2 < sstar ? 1 : 2][s2][lane]) : "memory");
            if (k2 > m) m = k2;
          }
          const uint32_t hi = __reduce_max_sync(~0u, (uint32_t)(m >> 32));
          k = (u64)hi << 32 | __reduce_max_sync(~0u, (uint32_t)(m >> 32) == hi ? (uint32_t)m : 0u);
          ver = (key_token(k) >> 5) < sstar ? 1 : 2;
        } else {
          const bool rec = k > best;
          if (rec) { best = k; if ((key_token(k) & 31) == me) mask |= 1ull << sg; }
          sts128(sb + K_LN + 144, make_uint4(sg + 1, (uint32_t)mask, (uint32_t)(mask >> 32), key_token(best) >> 5));
          if (!rec) continue;
        }
        if (!first) bar_sync(KN_TAKEN, 160);
        first = false;
        sts128(sb + K_LN + 160, make_uint4((uint32_t)k, (uint32_t)(k >> 32), sg, ver));
        bar_arrive(KN_CAND, 160);
      }
      bar_sync(KN_TAKEN, 160);
    } else if (!full) {
    } else if (w == 17) {
      FOR_UNITS {
        wait_count(&g_fl.oflag[v][sg][kb], 4, 84);
        mbar_wait(bars + (KB_EMPTY + (n & 1)) * 8, ((n >> 1) & 1) ^ 1, 83);
        TR(v)
        if (st == NSTEP - 1) { HD(v) }
        if (lane == 0) {
          fence_async_glb();
          mbar_expect_tx(bars + (KB_FULL + (n & 1)) * 8, 32768);
          bulk_g2s(sb + K_O + (n & 1) * 32768, g_O[v] + ((size_t)(sg & (OSLOTS - 1)) * 32 + kb * 4) * 8192, 32768, bars + (KB_FULL + (n & 1)) * 8);
        }
        __syncwarp();
      }
    } else if (w == 18) {
      FOR_UNITS {
        if (sg > 0) mbar_wait(bars + (KB_OK + v) * 8, (sg - 1) & 1, 90);
        bar_sync(KN_ST + (n & 1), 288);
        fence_async_smem();
        if (lane == 0) {
          bulk_s2g(g_part[v] + ((sg & 1) * 32 + me) * 8192, sb + K_ST + (n & 1) * 8192, 8192);
          asm volatile("cp.async.bulk.commit_group;" ::: "memory");
          mbar_arrive_z(bars + (KB_EMPTY + (n & 1)) * 8, 0);
          asm volatile("cp.async.bulk.wait_group.read 0;" ::: "memory");
        }
        __syncwarp();
        mbar_arrive_z(bars + (KB_ST + (n & 1)) * 8, lane);
        TR(v)
        const uint32_t tg = clk32() + GATE_R;
        if (v == 0 && sg > 0) mbar_wait(bars + KB_REL * 8, (sg - 1) & 1, 93);
        wait_clock(tg);
        if (st == NSTEP - 1) { HD(2 + v) }
        mbar_arrive_z(bars + (KB_GO + v) * 8, lane);
      }
    } else {
#pragma unroll 1
      for (int i = 0; i <= NSEG; i++) {
        const int st = i, sg = min(i, NSEG - 1);
        (void)st;
        bar_sync(KN_REL, 160);
        const uint32_t ob = __shfl_sync(~0u, lds32(sb + K_LN + 128), 0);
        mbar_arrive_z(bars + KB_REL * 8, lane);
        if (i == NSEG) { HD(5) }
        if (lane == 0) st_release_u64(&g_fl.key[i < NSEG ? 0 : 2][sg][me], (u64)ob << 32 | (uint32_t)~(sg * 32 + me));
        __syncwarp();
        TR(0)
      }
    }
  }
}
#undef TRC

bool g_ready;

}

extern "C" void kernel_launch(void* const* d_in, const int* in_sizes, int n_in, void* d_out, int out_size) {
  (void)in_sizes; (void)n_in; (void)out_size;
  const bf16* x0 = (const bf16*)d_in[0];
  const bf16* mem0 = (const bf16*)d_in[1];
  const bf16* Wq = (const bf16*)d_in[2];
  const bf16* Wk = (const bf16*)d_in[3];
  const bf16* Wv = (const bf16*)d_in[4];
  const bf16* Wo = (const bf16*)d_in[5];
  if (!g_ready) {
    cudaFuncSetAttribute(worker_kernel, cudaFuncAttributeMaxDynamicSharedMemorySize, K_SMEM);
    cudaFuncSetAttribute(chain_kernel, cudaFuncAttributeMaxDynamicSharedMemorySize, C_SMEM);
    g_ready = true;
  }
  cudaStream_t st = cudaStreamPerThread;
  prep_kernel<<<NTOK / 8, 256, 0, st>>>(x0);
  chain_kernel<<<96, 512, C_SMEM, st>>>(Wq, Wk, Wv, Wo, mem0);
  cudaLaunchAttribute pdl[1];
  pdl[0].id = cudaLaunchAttributeProgrammaticStreamSerialization;
  pdl[0].val.programmaticStreamSerializationAllowed = 1;
  WorkerParams wp;
  wp.x0 = x0; wp.Wo = Wo; wp.w_r = (const bf16*)d_in[8]; wp.w_gate = (const bf16*)d_in[9]; wp.w_up = (const bf16*)d_in[10];
  wp.w_down = (const bf16*)d_in[11]; wp.out = (bf16*)d_out;
  cudaLaunchConfig_t cfg = {};
  cfg.gridDim = dim3(NWORK); cfg.blockDim = dim3(640); cfg.dynamicSmemBytes = K_SMEM; cfg.stream = st;
  cfg.attrs = pdl; cfg.numAttrs = 1;
  cudaLaunchKernelEx(&cfg, worker_kernel, wp);
}
```

```cpp
#include <cuda_runtime.h>
#include <cuda_bf16.h>
#include <stdint.h>

namespace {

typedef __nv_bfloat16 bf16;
typedef unsigned long long u64;

constexpr int NTOK = 2048, DM = 512, HD = 4096, NSEG = 64, FF = 1792;
#define DELTA 4
constexpr int NSTEP = NSEG + DELTA;
constexpr int SPIN_LIMIT = 40000;
constexpr int MBAR_LIMIT = 20000;
constexpr int NWORK = 36;
constexpr int OSLOTS = 8;

__device__ __align__(1024) uint8_t g_xs[2][NSEG * 32768];
__device__ __align__(1024) uint8_t g_patch[NSEG * 8192];
__device__ __align__(1024) uint8_t g_O[3][OSLOTS * 32 * 8192];
__device__ __align__(1024) uint8_t g_part[3][2 * 32 * 8192];
__device__ __align__(1024) bf16 g_rows[3][3][NTOK * DM];
__device__ __align__(1024) bf16 g_x2p[NSEG * DM];
__device__ __align__(65536) uint32_t g_M[4 * 16384];
__device__ __align__(65536) uint32_t g_P[96 * 4096];
struct Flags {
  uint32_t pol[96];
  uint32_t stamp[96];
  uint32_t oflag[3][NSEG][8];
  uint32_t ffncnt[NSTEP][8];
  uint32_t patch[NSEG][8];
  u64 key[3][NSEG][32];
  float upd[NSTEP][DM];
};
__device__ __align__(1024) Flags g_fl;
#define TR(e)
#define TRV(e, v)
#define TG(i)
#define HD(e)
#define TRDUMP
#define TREXTRA 0

#define STAT(e, v)
#define STATC(n)
#define STATDUMP
__device__ __forceinline__ uint32_t smem_u32(const void* p) { return (uint32_t)__cvta_generic_to_shared(p); }
__device__ __forceinline__ uint32_t pack_bf16(float lo, float hi) {
  uint32_t r;
  asm("cvt.rn.bf16x2.f32 %0, %1, %2;" : "=r"(r) : "f"(hi), "f"(lo));
  return r;
}
__device__ __forceinline__ float bf_lo(uint32_t v) { return __uint_as_float(v << 16); }
__device__ __forceinline__ float bf_hi(uint32_t v) { return __uint_as_float(v & 0xffff0000u); }
__device__ __forceinline__ float ex2_fast(float x) { float y; asm("ex2.approx.ftz.f32 %0, %1;" : "=f"(y) : "f"(x)); return y; }
__device__ __forceinline__ float rcp_fast(float x) { float y; asm("rcp.approx.ftz.f32 %0, %1;" : "=f"(y) : "f"(x)); return y; }
__device__ __forceinline__ float round_bf16(float x) { return __bfloat162float(__float2bfloat16_rn(x)); }
__device__ __forceinline__ uint32_t clk32() { uint32_t t; asm volatile("mov.u32 %0, %%clock;" : "=r"(t) :: "memory"); return t; }

__device__ __forceinline__ void mma16816(float (&d)[4], uint32_t a0, uint32_t a1, uint32_t a2, uint32_t a3,
                                         uint32_t b0, uint32_t b1) {
  asm("mma.sync.aligned.m16n8k16.row.col.f32.bf16.bf16.f32 {%0,%1,%2,%3}, {%4,%5,%6,%7}, {%8,%9}, {%0,%1,%2,%3};"
      : "+f"(d[0]), "+f"(d[1]), "+f"(d[2]), "+f"(d[3])
      : "r"(a0), "r"(a1), "r"(a2), "r"(a3), "r"(b0), "r"(b1));
}
__device__ __forceinline__ void ldsm4t(uint32_t (&r)[4], uint32_t addr) {
  asm volatile("ldmatrix.sync.aligned.m8n8.x4.trans.shared.b16 {%0,%1,%2,%3}, [%4];"
               : "=r"(r[0]), "=r"(r[1]), "=r"(r[2]), "=r"(r[3]) : "r"(addr) : "memory");
}
__device__ __forceinline__ void stsm4(uint32_t addr, uint32_t a, uint32_t b, uint32_t c, uint32_t d) {
  asm volatile("stmatrix.sync.aligned.m8n8.x4.shared.b16 [%0], {%1,%2,%3,%4};" ::"r"(addr), "r"(a), "r"(b), "r"(c), "r"(d) : "memory");
}
__device__ __forceinline__ void stsm4t(uint32_t addr, uint32_t a, uint32_t b, uint32_t c, uint32_t d) {
  asm volatile("stmatrix.sync.aligned.m8n8.x4.trans.shared.b16 [%0], {%1,%2,%3,%4};" ::"r"(addr), "r"(a), "r"(b), "r"(c), "r"(d) : "memory");
}
__device__ __forceinline__ uint4 lds128(uint32_t a) {
  uint4 v; asm volatile("ld.shared.v4.b32 {%0,%1,%2,%3}, [%4];" : "=r"(v.x), "=r"(v.y), "=r"(v.z), "=r"(v.w) : "r"(a) : "memory"); return v;
}
__device__ __forceinline__ uint32_t lds32(uint32_t a) { uint32_t v; asm volatile("ld.shared.b32 %0, [%1];" : "=r"(v) : "r"(a) : "memory"); return v; }
__device__ __forceinline__ void sts32(uint32_t a, uint32_t x) { asm volatile("st.shared.b32 [%0], %1;" ::"r"(a), "r"(x) : "memory"); }
__device__ __forceinline__ void sts128(uint32_t a, uint4 v) {
  asm volatile("st.shared.v4.b32 [%0], {%1,%2,%3,%4};" ::"r"(a), "r"(v.x), "r"(v.y), "r"(v.z), "r"(v.w) : "memory");
}
__device__ __forceinline__ void cp16(uint32_t dst, const void* src) {
  asm volatile("cp.async.cg.shared.global [%0], [%1], 16;" ::"r"(dst), "l"(src) : "memory");
}
__device__ __forceinline__ void mbar_init(uint32_t mbar, uint32_t cnt) {
  asm volatile("mbarrier.init.shared.b64 [%0], %1;" ::"r"(mbar), "r"(cnt) : "memory");
}
__device__ __forceinline__ void mbar_expect_tx(uint32_t mbar, uint32_t bytes) {
  asm volatile("mbarrier.arrive.expect_tx.shared.b64 _, [%0], %1;" ::"r"(mbar), "r"(bytes) : "memory");
}
__device__ __forceinline__ void mbar_arrive_z(uint32_t mbar, uint32_t z) {
  asm volatile("{ .reg .pred p; setp.eq.u32 p, %1, 0; @p mbarrier.arrive.shared.b64 _, [%0]; }" ::"r"(mbar), "r"(z) : "memory");
}
__device__ __forceinline__ void mbar_expect_tx_z(uint32_t mbar, uint32_t bytes, uint32_t z) {
  asm volatile("{ .reg .pred p; setp.eq.u32 p, %2, 0; @p mbarrier.arrive.expect_tx.shared.b64 _, [%0], %1; }" ::"r"(mbar), "r"(bytes), "r"(z) : "memory");
}
__device__ __forceinline__ void mbar_arrive_remote_z(uint32_t mbar, uint32_t z) {
  asm volatile("{ .reg .pred p; setp.eq.u32 p, %1, 0; @p mbarrier.arrive.shared::cluster.b64 _, [%0]; }" ::"r"(mbar), "r"(z) : "memory");
}
__device__ __forceinline__ bool mbar_try(uint32_t mbar, uint32_t par) {
  uint32_t ok;
  asm volatile("{ .reg .pred p; mbarrier.try_wait.parity.shared::cta.b64 p, [%1], %2; selp.u32 %0, 1, 0, p; }"
               : "=r"(ok) : "r"(mbar), "r"(par) : "memory");
  return ok;
}
__device__ __forceinline__ void fail(int) { __trap(); }
__device__ __forceinline__ void give_up(int it, int limit, int code) { if (it > limit) fail(code); }
__device__ __forceinline__ void mbar_wait(uint32_t mbar, uint32_t par, int code) {
  asm volatile("{ .reg .pred p; .reg .b32 n; mov.b32 n, %2;\n"
               "W: mbarrier.try_wait.parity.shared::cta.b64 p, [%0], %1; @p bra D;\n"
               "add.s32 n, n, -1; setp.eq.s32 p, n, 0; @p trap; bra W;\n"
               "D: }" ::"r"(mbar), "r"(par), "n"(MBAR_LIMIT) : "memory");
}
__device__ __forceinline__ void mbar_gate(uint32_t mbar, uint32_t par) {
  const uint32_t t0 = clk32();
  while (!mbar_try(mbar, par) && clk32() - t0 < 20000) {}
}
__device__ __forceinline__ void bulk_g2s(uint32_t dst, const void* src, uint32_t bytes, uint32_t mbar) {
  asm volatile("cp.async.bulk.shared::cluster.global.mbarrier::complete_tx::bytes [%0], [%1], %2, [%3];"
               ::"r"(dst), "l"(src), "r"(bytes), "r"(mbar) : "memory");
}
__device__ __forceinline__ void bulk_s2r(uint32_t dst, uint32_t src, uint32_t bytes, uint32_t mbar) {
  asm volatile("cp.async.bulk.shared::cluster.shared::cta.mbarrier::complete_tx::bytes [%0], [%1], %2, [%3];"
               ::"r"(dst), "r"(src), "r"(bytes), "r"(mbar) : "memory");
}
__device__ __forceinline__ void bulk_s2g(void* dst, uint32_t src, uint32_t bytes) {
  asm volatile("cp.async.bulk.global.shared::cta.bulk_group [%0], [%1], %2;" ::"l"(dst), "r"(src), "r"(bytes) : "memory");
}
__device__ __forceinline__ void fence_async_smem() { asm volatile("fence.proxy.async.shared::cta;" ::: "memory"); }
__device__ __forceinline__ void fence_async_glb() { asm volatile("fence.proxy.async.global;" ::: "memory"); }
__device__ __forceinline__ void bar_sync(int id, int n) { asm volatile("bar.sync %0, %1;" ::"r"(id), "r"(n) : "memory"); }
__device__ __forceinline__ void bar_arrive(int id, int n) { asm volatile("bar.arrive %0, %1;" ::"r"(id), "r"(n) : "memory"); }
__device__ __forceinline__ void cluster_sync() { asm volatile("barrier.cluster.arrive.release; barrier.cluster.wait.acquire;" ::: "memory"); }
__device__ __forceinline__ uint32_t mapa_u32(uint32_t a, uint32_t r) {
  uint32_t o;
  asm("mapa.shared::cluster.u32 %0, %1, %2;" : "=r"(o) : "r"(a), "r"(r));
  return o;
}
template <int OFF>
__device__ __forceinline__ void st_async32(uint32_t a, uint32_t x, uint32_t mbar) {
  asm volatile("st.async.weak.shared::cluster.mbarrier::complete_tx::bytes.b32 [%0 + %3], %1, [%2];" ::"r"(a), "r"(x), "r"(mbar), "n"(OFF) : "memory");
}
__device__ __forceinline__ uint4 ld_rlx128(const void* p) {
  uint4 v;
  asm volatile("ld.relaxed.gpu.global.v4.u32 {%0,%1,%2,%3}, [%4];" : "=r"(v.x), "=r"(v.y), "=r"(v.z), "=r"(v.w) : "l"(p) : "memory");
  return v;
}
__device__ __forceinline__ uint2 ld_rlx64(const void* p) {
  uint2 v; asm volatile("ld.relaxed.gpu.global.v2.u32 {%0,%1}, [%2];" : "=r"(v.x), "=r"(v.y) : "l"(p) : "memory"); return v;
}
__device__ __forceinline__ uint32_t ld_rlx32(const void* p) {
  uint32_t v; asm volatile("ld.relaxed.gpu.global.u32 %0, [%1];" : "=r"(v) : "l"(p) : "memory"); return v;
}
__device__ __forceinline__ void st_rlx32(void* p, uint32_t a) { asm volatile("st.relaxed.gpu.global.u32 [%0], %1;" ::"l"(p), "r"(a) : "memory"); }
__device__ __forceinline__ void red_release(uint32_t* p) { asm volatile("red.release.gpu.global.add.u32 [%0], 1;" ::"l"(p) : "memory"); }
__device__ __forceinline__ void st_release32(void* p, uint32_t a) { asm volatile("st.release.gpu.global.u32 [%0], %1;" ::"l"(p), "r"(a) : "memory"); }
__device__ __forceinline__ void st_release_u64(void* p, u64 a) { asm volatile("st.release.gpu.global.u64 [%0], %1;" ::"l"(p), "l"(a) : "memory"); }
__device__ __forceinline__ void wait_count(const uint32_t* p, uint32_t val, int code) {
  int it = 0;
  while (ld_rlx32(p) < val) {
    give_up(++it, SPIN_LIMIT, code);
    __nanosleep(40);
  }
}
__device__ __forceinline__ u64 wait_keys(const u64* keys, int lane, int code) {
  u64 k;
  int it = 0;
  while (true) {
    asm volatile("ld.relaxed.gpu.global.u64 %0, [%1];" : "=l"(k) : "l"(keys + lane) : "memory");
    if (__all_sync(~0u, k != 0)) break;
    give_up(++it, SPIN_LIMIT, code);
    __nanosleep(100);
  }
  const uint32_t hi = __reduce_max_sync(~0u, (uint32_t)(k >> 32));
  const uint32_t lo = __reduce_max_sync(~0u, (uint32_t)(k >> 32) == hi ? (uint32_t)k : 0u);
  return (u64)hi << 32 | lo;
}
__device__ __forceinline__ int key_token(u64 k) { return (int)(~(uint32_t)k) & (NTOK - 1); }
__device__ __forceinline__ float key_score(u64 k) {
  const uint32_t ob = (uint32_t)(k >> 32);
  return __uint_as_float((ob & 0x80000000u) ? (ob & 0x7fffffffu) : ~ob);
}

__device__ __forceinline__ uint64_t mk_desc(uint32_t saddr, uint32_t lbo, uint32_t sbo, uint32_t sw) {
  return (uint64_t)((saddr & 0x3FFFF) >> 4) | (uint64_t)(lbo >> 4) << 16 | (uint64_t)(sbo >> 4) << 32 | (uint64_t)sw << 62;
}
template <int N> __device__ __forceinline__ void reg_inc() { asm volatile("setmaxnreg.inc.sync.aligned.u32 %0;" ::"n"(N)); }
template <int N> __device__ __forceinline__ void reg_dec() { asm volatile("setmaxnreg.dec.sync.aligned.u32 %0;" ::"n"(N)); }
__device__ __forceinline__ void wg_fence() { asm volatile("wgmma.fence.sync.aligned;" ::: "memory"); }
__device__ __forceinline__ void wg_commit() { asm volatile("wgmma.commit_group.sync.aligned;" ::: "memory"); }
template <int N> __device__ __forceinline__ void wg_wait() { asm volatile("wgmma.wait_group.sync.aligned %0;" ::"n"(N) : "memory"); }
template <int N> __device__ __forceinline__ void acc_fence(float (&d)[N]) {
#pragma unroll
  for (int i = 0; i < N; i++) asm volatile("" : "+f"(d[i]) :: "memory");
}
#define O4(d, i) "+f"(d[i]), "+f"(d[i + 1]), "+f"(d[i + 2]), "+f"(d[i + 3])
template <int TB, int ACC>
__device__ __forceinline__ void wg_rs8(float (&d)[4], const uint32_t (&a)[4], uint64_t db) {
  asm volatile("wgmma.mma_async.sync.aligned.m64n8k16.f32.bf16.bf16 {%0,%1,%2,%3}, {%4,%5,%6,%7}, %8, %9, 1, 1, %10;"
               : O4(d, 0) : "r"(a[0]), "r"(a[1]), "r"(a[2]), "r"(a[3]), "l"(db), "n"(ACC), "n"(TB));
}
template <int TB, int ACC>
__device__ __forceinline__ void wg_rs24(float (&d)[12], const uint32_t (&a)[4], uint64_t db) {
  asm volatile("wgmma.mma_async.sync.aligned.m64n24k16.f32.bf16.bf16 {%0,%1,%2,%3,%4,%5,%6,%7,%8,%9,%10,%11}, {%12,%13,%14,%15}, %16, %17, 1, 1, %18;"
               : O4(d, 0), O4(d, 4), O4(d, 8) : "r"(a[0]), "r"(a[1]), "r"(a[2]), "r"(a[3]), "l"(db), "n"(ACC), "n"(TB));
}
template <int TB, int ACC>
__device__ __forceinline__ void wg_rs32(float (&d)[16], const uint32_t (&a)[4], uint64_t db) {
  asm volatile("wgmma.mma_async.sync.aligned.m64n32k16.f32.bf16.bf16 {%0,%1,%2,%3,%4,%5,%6,%7,%8,%9,%10,%11,%12,%13,%14,%15}, {%16,%17,%18,%19}, %20, %21, 1, 1, %22;"
               : O4(d, 0), O4(d, 4), O4(d, 8), O4(d, 12) : "r"(a[0]), "r"(a[1]), "r"(a[2]), "r"(a[3]), "l"(db), "n"(ACC), "n"(TB));
}
template <int ACC>
__device__ __forceinline__ void wg_rs64(float (&d)[32], uint32_t a0, uint32_t a1, uint32_t a2, uint32_t a3, uint64_t db) {
  asm volatile("wgmma.mma_async.sync.aligned.m64n64k16.f32.bf16.bf16 {%0,%1,%2,%3,%4,%5,%6,%7,%8,%9,%10,%11,%12,%13,%14,%15,"
               "%16,%17,%18,%19,%20,%21,%22,%23,%24,%25,%26,%27,%28,%29,%30,%31}, {%32,%33,%34,%35}, %36, %37, 1, 1, 0;"
               : O4(d, 0), O4(d, 4), O4(d, 8), O4(d, 12), O4(d, 16), O4(d, 20), O4(d, 24), O4(d, 28)
               : "r"(a0), "r"(a1), "r"(a2), "r"(a3), "l"(db), "n"(ACC));
}
template <int ACC>
__device__ __forceinline__ void wg_ss24(float (&d)[12], uint64_t da, uint64_t db) {
  asm volatile("wgmma.mma_async.sync.aligned.m64n24k16.f32.bf16.bf16 {%0,%1,%2,%3,%4,%5,%6,%7,%8,%9,%10,%11}, %12, %13, %14, 1, 1, 1, 0;"
               : O4(d, 0), O4(d, 4), O4(d, 8) : "l"(da), "l"(db), "n"(ACC));
}
template <int ACC>
__device__ __forceinline__ void wg_ss40(float (&d)[20], uint64_t da, uint64_t db) {
  asm volatile("wgmma.mma_async.sync.aligned.m64n40k16.f32.bf16.bf16 {%0,%1,%2,%3,%4,%5,%6,%7,%8,%9,%10,%11,%12,%13,%14,%15,%16,%17,%18,%19}, %20, %21, %22, 1, 1, 1, 1;"
               : O4(d, 0), O4(d, 4), O4(d, 8), O4(d, 12), O4(d, 16) : "l"(da), "l"(db), "n"(ACC));
}

struct Row { uint32_t w[8]; };
__device__ __forceinline__ uint32_t add_bf16x2(uint32_t a, uint32_t b) {
  uint32_t d; asm("add.rn.bf16x2 %0, %1, %2;" : "=r"(d) : "r"(a), "r"(b)); return d;
}
__device__ __forceinline__ Row warp_ln(const Row& r, float& extra) {
  float x[16];
#pragma unroll
  for (int i = 0; i < 8; i++) { x[2 * i] = bf_lo(r.w[i]); x[2 * i + 1] = bf_hi(r.w[i]); }
  float m = (((x[0] + x[1]) + (x[2] + x[3])) + ((x[4] + x[5]) + (x[6] + x[7]))) + (((x[8] + x[9]) + (x[10] + x[11])) + ((x[12] + x[13]) + (x[14] + x[15])));
  m *= (1.f / 16);
  float v0 = 0.f, v1 = 0.f;
#pragma unroll
  for (int i = 0; i < 16; i += 2) { const float d0 = x[i] - m, d1 = x[i + 1] - m; v0 = fmaf(d0, d0, v0); v1 = fmaf(d1, d1, v1); }
  float v = v0 + v1;
#pragma unroll
  for (int o = 1; o <= 16; o <<= 1) {
    const float mo = __shfl_xor_sync(~0u, m, o), vo = __shfl_xor_sync(~0u, v, o);
    extra += __shfl_xor_sync(~0u, extra, o);
    const float d = mo - m;
    v = fmaf(d * d, 8.f * o, v + vo);
    m = 0.5f * (m + mo);
  }
  const float var = fmaf(v, 1.f / DM, 1e-5f);
  float rs = rsqrtf(var);
  rs = rs * fmaf(-0.5f * var * rs, rs, 1.5f);
  Row y;
#pragma unroll
  for (int i = 0; i < 8; i++) y.w[i] = pack_bf16((x[2 * i] - m) * rs, (x[2 * i + 1] - m) * rs);
  return y;
}
__device__ __forceinline__ Row warp_ln(const Row& r) { float e = 0.f; return warp_ln(r, e); }
__device__ __forceinline__ Row load_row(const bf16* p, int lane) {
  Row r;
#pragma unroll
  for (int q = 0; q < 4; q++) { const uint2 v = ld_rlx64(p + lane * 4 + q * 128); r.w[2 * q] = v.x; r.w[2 * q + 1] = v.y; }
  return r;
}
__device__ __forceinline__ void store_row(bf16* p, int lane, const Row& r) {
#pragma unroll
  for (int q = 0; q < 4; q++) *(uint2*)(p + lane * 4 + q * 128) = make_uint2(r.w[2 * q], r.w[2 * q + 1]);
}
__device__ __forceinline__ void store_row_img(uint8_t* grp, int rr, int lane, const Row& r) {
  uint8_t* p = grp + (lane >> 4) * 1024 + rr * 128 + ((((lane & 15) >> 1) ^ rr) << 4) + (lane & 1) * 8;
#pragma unroll
  for (int q = 0; q < 4; q++) *(uint2*)(p + q * 2048) = make_uint2(r.w[2 * q], r.w[2 * q + 1]);
}

__global__ void __launch_bounds__(256) prep_kernel(const bf16* __restrict__ x0, const bf16* Wq, const bf16* Wk, const bf16* Wv, const bf16* Wo) {
  const int lane = threadIdx.x & 31, row = blockIdx.x * 8 + (threadIdx.x >> 5);
  const Row r = load_row(x0 + (size_t)row * DM, lane);
  const int gt = blockIdx.x * 256 + threadIdx.x, nt = gridDim.x * 256;
  asm volatile("prefetch.global.L2 [%0];" ::"l"((gt & 1 ? Wk : Wq) + (gt >> 1) * 64));
  asm volatile("prefetch.global.L2 [%0];" ::"l"((gt & 1 ? Wo : Wv) + (gt >> 1) * 64));
  uint4* M = (uint4*)g_M;
  for (int i = gt; i < 4 * 16384 / 4; i += nt) M[i] = make_uint4(~0u, ~0u, ~0u, ~0u);
  uint4* P = (uint4*)g_P;
  for (int i = gt; i < 96 * 4096 / 4; i += nt) P[i] = make_uint4(0, 0, 0, 0);
  if (gt < 16384) ((uint4*)(g_part[1] + 32 * 8192))[gt] = make_uint4(0, 0, 0, 0);
  uint4* F = (uint4*)&g_fl;
  for (int i = gt; i < (int)(sizeof(Flags) / 16); i += nt) F[i] = make_uint4(0, 0, 0, 0);
  store_row_img(g_xs[0] + (size_t)blockIdx.x * 8192, row & 7, lane, warp_ln(r));
}

constexpr int W_STRIDE = 272;
constexpr int C_WO = 0;
constexpr int C_X = 49152;
constexpr int C_M = C_X + 9 * 8192;
constexpr int C_Q = C_M + 24576;
constexpr int C_K = C_Q + 10240, C_V = C_K + 10240;
constexpr int C_SA = C_V + 10240, C_SB = C_SA + 8192, C_SP = C_SB + 8192;
constexpr int C_O = C_SP + 2048;
constexpr int C_OT = C_O + 6144;
constexpr int C_BAR = C_OT + 8192;
constexpr int C_SMEM = C_BAR + 256 + 1024 + TREXTRA;
static_assert(C_X + 512 * W_STRIDE <= C_OT, "staging");
enum { B_M0 = 0, B_M1, B_M2, B_R, B_X = B_R + 4, B_O, B_T, B_F, B_XL1, B_XL2, B_XL3, B_P1, B_P2, B_P3, B_OT, B_XF, B_NUM };
constexpr int C_INFO = C_BAR + 160, C_POL = C_BAR + 192;
enum { NB_ALL = 0, NB_M0, NB_PV, NB_W0, NB_TA, NB_X1, NB_M1, NB_M2, NB_RD };
constexpr float SCALE_LOG2E = 0.08838834764831845f * 1.4426950408889634f;
#define N0STEPS 9
#define N2STEPS 12
#define OGATE 3
#define OEARLY 1
#define SHIPLATE 0
#define XGATE 3
#define SHIP 1024
#define GATE_P 2700
#define GATE_W 200
#define GATE_G 200
#define GATE_M 3850
#define HOLE0 29
#define HOLE1 32
#define HOLE2 32
__device__ __forceinline__ uint32_t gtime() { uint32_t t; asm volatile("mov.u32 %0, %%globaltimer_lo;" : "=r"(t) :: "memory"); return t; }
__device__ __forceinline__ void wait_clock(uint32_t t) { while ((int)(clk32() - t) < 0) {} }
__device__ __forceinline__ bool bar_or(int id, int n, uint32_t v) {
  uint32_t r;
  asm volatile("{ .reg .pred p, q; setp.ne.u32 p, %1, 0; bar.red.or.pred q, %2, %3, p; vote.sync.any.pred q, q, 0xffffffff; selp.u32 %0, 1, 0, q; }"
               : "=r"(r) : "r"(v), "r"(id), "r"(n) : "memory");
  return r;
}
__device__ __forceinline__ void bar_sync_z(int id, int n, uint32_t z) {
  asm volatile("{ .reg .pred p; setp.eq.u32 p, %2, 0; @p bar.sync %0, %1; }" ::"r"(id), "r"(n), "r"(z) : "memory");
}

__device__ __forceinline__ uint32_t probe_polarity(uint32_t* p) {
  uint32_t best[2] = {~0u, ~0u};
#pragma unroll 1
  for (int rep = 0; rep < 4; rep++) {
#pragma unroll
    for (int pg = 0; pg < 2; pg++) {
      uint32_t t0, t1, v;
      asm volatile("mov.u32 %0, %%clock;" : "=r"(t0) :: "memory");
      asm volatile("atom.relaxed.gpu.global.add.u32 %0, [%1], 0;" : "=r"(v) : "l"(p + pg * 1024) : "memory");
      asm volatile("{ .reg .pred p; setp.ne.u32 p, %1, 0x13572468; mov.u32 %0, 0; @p mov.u32 %0, %%clock; }" : "=r"(t1) : "r"(v) : "memory");
      if (rep > 0) best[pg] = min(best[pg], t1 - t0);
    }
  }
  return best[1] < best[0] ? 1u : 0u;
}
__device__ __forceinline__ uint32_t ppage(uint32_t lp, uint32_t pol) { return lp ? 3 - pol : pol; }
__device__ __forceinline__ uint32_t and_x(uint32_t a, uint32_t b, uint32_t m) {
  uint32_t d; asm("lop3.b32 %0, %1, %2, %3, 0x42;" : "=r"(d) : "r"(a), "r"(b), "r"(m)); return d;
}
__device__ __forceinline__ uint32_t and3(uint32_t a, uint32_t b, uint32_t c) {
  uint32_t d; asm("lop3.b32 %0, %1, %2, %3, 0x80;" : "=r"(d) : "r"(a), "r"(b), "r"(c)); return d;
}

template <int N> struct IC { static constexpr int value = N; };
template <class F> __device__ __forceinline__ void static_for2(F f) { f(IC<0>()); f(IC<1>()); }
template <class F> __device__ __forceinline__ void static_for3(F f) { f(IC<0>()); f(IC<1>()); f(IC<2>()); }
__device__ __forceinline__ void load_wfrags(uint32_t (&wA)[32][4], uint32_t stage, int w, int lane) {
  const int mi = lane >> 3, r = lane & 7;
#pragma unroll
  for (int ks = 0; ks < 32; ks++) ldsm4t(wA[ks], stage + (ks * 16 + (mi >> 1) * 8 + r) * W_STRIDE + (w * 16 + (mi & 1) * 8) * 2);
}
template <int K0, int K1>
__device__ __forceinline__ void tok_seq(float (&d)[16], const uint32_t (&wA)[32][4], uint64_t desc, uint32_t wave) {
#pragma unroll
  for (int k = K0; k < K1; k++) {
    const int ks = k & 31;
    constexpr int HM0 = 1, HM1 = 2, HM2 = 4;
    const int hm = (k == HOLE0 ? HM0 : 0) | (k == HOLE1 ? HM1 : 0) | (k == HOLE2 ? HM2 : 0);
    if (hm) bar_sync_z(NB_RD, 384, ((hm >> wave) & 1) ^ 1);
    if (ks == 0) wg_rs32<0, 0>(d, wA[ks], desc);
    else wg_rs32<0, 1>(d, wA[ks], desc + (ks >> 2) * 64 + (ks & 3) * 2);
  }
}
template <int K0, int K1>
__device__ __forceinline__ void mem_part(float (&d)[12], const uint32_t (&wA)[32][4], uint64_t desc) {
#pragma unroll
  for (int ks = K0; ks < K1; ks++) {
    if (ks == 0) wg_rs24<1, 0>(d, wA[ks], desc);
    else wg_rs24<1, 1>(d, wA[ks], desc + ks * 48);
  }
}
__device__ __forceinline__ void out_tile(float (&d)[12], uint64_t da, uint64_t db) {
#pragma unroll
  for (int i = 0; i < 8; i++) { if (i == 0) wg_ss24<0>(d, da, db); else wg_ss24<1>(d, da + i * 128, db + (i >> 1) * 32 + (i & 1) * 2); }
}
__device__ __forceinline__ void tok_pack(uint32_t (&p)[8], const float (&d)[16]) {
#pragma unroll
  for (int i = 0; i < 8; i++) p[i] = pack_bf16(d[2 * i], d[2 * i + 1]);
}
__device__ __forceinline__ void tok_store(uint32_t dst, const uint32_t (&p)[8]) {
  stsm4(dst, p[0], p[1], p[2], p[3]);
  stsm4(dst + 4096, p[4], p[5], p[6], p[7]);
}
template <class T> __device__ __forceinline__ T keep(T v) { asm volatile("" : "+r"(v)); return v; }
__device__ __forceinline__ uint32_t pin(uint32_t v) { return __shfl_sync(~0u, v, threadIdx.x & 31); }

#define TRC blockIdx.x
#define TRS (C_BAR + 256)
__device__ __forceinline__ void chain_proj(const uint32_t sb, const int w, const int lane_, const uint32_t rank) {
  uint32_t wA[32][4];
  load_wfrags(wA, sb + C_X, w, lane_);
  bar_sync(NB_ALL, 512);
  bar_sync(NB_ALL, 512);
  cluster_sync();
  const int lane = pin(lane_);
  const uint32_t bars = sb + C_BAR;
  const uint32_t quad = pin(sb + (lane_ >> 4) * 2048 + (lane_ & 15) * 16);
  const uint32_t own = C_Q + rank * 10240;
  const uint64_t dX1 = mk_desc(sb + C_X, 16, 8192, 1), dX2 = dX1 + 2048, dX3 = dX1 + 4096;
  const uint64_t dM = mk_desc(sb + C_M, 128, 256, 0);
  const uint32_t r1 = rank == 0 ? 1 : 0, r2 = rank == 2 ? 1 : 2;
  const uint32_t xa = pin(sb + own + 8192 + w * 256 + lane_ * 4);
  const uint32_t a1x = pin(mapa_u32(xa, r1)), a2x = pin(mapa_u32(xa, r2));
  const uint32_t b1x = pin(mapa_u32(bars + B_X * 8, r1)), b2x = pin(mapa_u32(bars + B_X * 8, r2));
  const uint32_t wave = rank == 2 ? 0 : rank + 1;
  uint32_t npatch = 0;
  constexpr int K3 = 32 - N0STEPS - N2STEPS;
  float a[16];
  bar_sync(NB_X1, 288);
  wg_fence();
  tok_seq<32, 32 + K3>(a, wA, dX1, 3);
  wg_commit();
  wg_wait<0>();
#pragma unroll 1
  for (int st = 0; st < NSTEP; st++) {
    uint32_t pk[8];
    wg_fence();
    tok_seq<32 + K3, 32 + K3 + N0STEPS>(a, wA, dX1, 3);
    TR(0)
    bar_sync(NB_PV, 384);
    tok_seq<32 + K3 + N0STEPS, 64>(a, wA, dX1, 3);
    wg_commit();
    wg_wait<0>();
    acc_fence(a);
    mbar_arrive_z(bars + B_XF * 8, lane);
    tok_pack(pk, a);
    TR(1)
    bar_sync(NB_W0, 416);
    tok_store(quad + w * 256 + (rank == 0 ? own : C_SA), pk);
    __syncwarp();
    mbar_arrive_z(bars + B_P2 * 8, lane);
    wg_fence();
    tok_seq<0, 32>(a, wA, dX2, wave);
    wg_commit();
    const uint32_t info = lds32(sb + C_INFO + (st & 1) * 4);
    TR(2)
    wg_wait<0>();
    acc_fence(a);
    TR(3)
    tok_pack(pk, a);
    tok_store(quad + w * 256 + (rank == 0 ? C_SA : own), pk);
    if (rank == 2) tok_store(quad + w * 256 + C_SB, pk);
    __syncwarp();
    mbar_arrive_z(bars + B_P1 * 8, lane);
    if (__builtin_expect(info & 4, 0)) {
      float a3[4];
      mbar_wait(bars + B_XL3 * 8, npatch & 1, 32);
      npatch++;
      wg_fence();
#pragma unroll
      for (int ks = 0; ks < 32; ks++) {
        if (ks == 0) wg_rs8<0, 0>(a3, wA[ks], dX3);
        else wg_rs8<0, 1>(a3, wA[ks], dX3 + (ks >> 2) * 64 + (ks & 3) * 2);
      }
      wg_commit();
      wg_wait<0>();
      acc_fence(a3);
      const uint32_t dst = sb + (rank == 2 ? own + (info & 3) * 2048 : C_SP) + w * 256 + lane * 4;
      sts32(dst, pack_bf16(a3[0], a3[1])); sts32(dst + 128, pack_bf16(a3[2], a3[3]));
      __syncwarp();
      mbar_arrive_z(bars + B_P3 * 8, lane);
    }
    TR(4)
    bar_sync(NB_X1, 288);
    wg_fence();
    tok_seq<32, 32 + K3>(a, wA, dX1, wave);
    TR(6)
    {
      float am[12];
      bar_sync(NB_M0, 384);
      mem_part<0, 10>(am, wA, dM);
      TR(7)
      bar_sync(NB_M1, 384);
      mem_part<10, 21>(am, wA, dM);
      const bool redo = bar_or(NB_M2, 384, 0);
      mem_part<21, 32>(am, wA, dM);
      wg_commit();
      wg_wait<0>();
      if (__builtin_expect(redo, 0)) {
        bar_sync(NB_M0, 384);
        wg_fence();
        mem_part<0, 32>(am, wA, dM);
        wg_commit();
        wg_wait<0>();
      }
      acc_fence(am);
      TR(8)
      const uint32_t x00 = pack_bf16(am[0], am[1]), x01 = pack_bf16(am[2], am[3]), x10 = pack_bf16(am[4], am[5]), x11 = pack_bf16(am[6], am[7]);
      uint32_t x20 = pack_bf16(am[8], am[9]), x21 = pack_bf16(am[10], am[11]);
      if (info & 4) { x20 = x10; x21 = x11; }
      st_async32<0>(a1x, rank == 0 ? x10 : x00, b1x); st_async32<0>(a2x, rank == 2 ? x10 : x20, b2x);
      st_async32<128>(a1x, rank == 0 ? x11 : x01, b1x); st_async32<128>(a2x, rank == 2 ? x11 : x21, b2x);
      sts32(xa, rank == 0 ? x00 : rank == 2 ? x20 : x10); sts32(xa + 128, rank == 0 ? x01 : rank == 2 ? x21 : x11);
      __syncwarp();
      mbar_arrive_z(bars + B_X * 8, lane);
      if (w == 7) {
        const uint32_t stamp = (gtime() & ~31u) | ((st + 1) & 31);
        asm volatile("{ .reg .pred p; setp.eq.u32 p, %2, 0; @p st.relaxed.gpu.global.u32 [%0], %1; }" ::"l"(&g_fl.stamp[blockIdx.x]), "r"(stamp), "r"(lane) : "memory");
      }
    }
    TR(9)
  }
}

__device__ __forceinline__ void chain_mem(const uint32_t sb, const int w, const int lane_, const uint32_t rank, const int h,
                                          const bf16* __restrict__ mem0) {
  const int lane = pin(lane_);
  const int wave = rank == 2 ? 0 : rank + 1;
  const int c = w - 8, t = c * 32 + lane, b = wave * 32 + h;
  const uint32_t bars = sb + C_BAR;
  uint32_t pgbits = 0;
  {
    uint32_t pol = 1;
    const int tl = lane / 3, u = ((tl * 3 + rank) * 4 + c) * 3 + (lane - tl * 3);
    if (lane < 9 && u < 96) {
      int it = 0;
      while ((pol = ld_rlx32(&g_fl.pol[u])) == 0) give_up(++it, SPIN_LIMIT, 40);
    }
    pgbits = __reduce_or_sync(~0u, lane < 9 ? ppage(h >> 4, (pol - 1) & 1) << (2 * lane) : 0u);
  }
  const int wi = (lane & 1) * 2 + (lane >> 4), cq = (lane >> 2) & 3;
  bar_sync(NB_ALL, 512);
#pragma unroll 1
  for (int i = c; i < 16; i += 4) {
    uint32_t r[4];
    ldsm4t(r, sb + C_OT + i * 512 + lane * 16);
    const uint32_t a = sb + C_M + (2 * i + (lane >> 4)) * 768 + (lane & 15) * 16;
    stsm4(a, r[0], r[1], r[2], r[3]); stsm4(a + 256, r[0], r[1], r[2], r[3]); stsm4(a + 512, r[0], r[1], r[2], r[3]);
  }
  fence_async_smem();
  mbar_expect_tx_z(bars + B_X * 8, 4096, t); mbar_expect_tx_z(bars + B_O * 8, 4096, t);
  bar_sync(NB_ALL, 512);
  cluster_sync();
  bar_arrive(NB_PV, 384); bar_arrive(NB_W0, 416); bar_arrive(NB_M0, 384); bar_arrive(NB_M1, 384);
  bar_arrive(NB_RD, 384);

  const int mi = lane >> 3;
  const uint32_t l16 = pin(sb + lane * 16);
  const uint32_t r1 = rank == 2 ? 0 : rank + 1, r2 = rank == 0 ? 2 : rank - 1;
  const uint32_t oa = pin(sb + C_O + rank * 2048 + (lane >> 2) * 64 + (((lane & 3) ^ (lane >> 3)) << 4));
  const uint32_t a1 = mapa_u32(oa, r1), b1 = mapa_u32(bars + B_O * 8, r1), a2 = mapa_u32(oa, r2), b2 = mapa_u32(bars + B_O * 8, r2);
  const uint64_t dWo = mk_desc(sb + C_WO, 8192, 1024, 1), dO = mk_desc(sb + C_O, 16, 2048, 2);
  const uint64_t dQ = mk_desc(sb + C_Q, 128, 2048, 0), dK = mk_desc(sb + C_K, 128, 2048, 0);
  const uint64_t dV = mk_desc(sb + C_V, 2048, 128, 0), dVm = mk_desc(sb + C_V + 8192, 0, 128, 0);
  const int lim = pin(c < 2 ? 16 * c + (lane >> 2) - 2 * (lane & 3) : 64);
  uint8_t* Pw = (uint8_t*)g_P + (rank * 4 + c) * 3 * 16384 + (h & 15) * 256 + lane * 4;
  const uint32_t polP = lds32(sb + C_POL + 16);
  const uint8_t* Pr0 = (const uint8_t*)g_P + b * 16384 + ((lane >> 4) * 4 + (lane & 3)) * 256 + c * 64 + cq * 16 + ppage(0, polP) * 4096;
  const uint8_t* Pr1 = Pr0 + (3 - 2 * polP) * 4096;
  uint8_t* Mw = (uint8_t*)g_M + (b >> 5) * 16384 + ((lane & 2) ? 4096 : 12288) + (b & 31) * 256 + c * 64 + cq * 16 + wi * 4;
  uint32_t nretry = 0;
  const uint32_t gate_p = GATE_P + wave * GATE_W;

  (void)bar_or(NB_M2, 384, 0);
#pragma unroll 1
  for (int st = 0;; st++) {
    mbar_wait(bars + B_T * 8, st & 1, 42);
    STAT(10, clk32())
    mbar_wait(bars + B_X * 8, st & 1, 41);
    STAT(11, clk32())
    fence_async_smem();
    TR(0)
    {
      float s[20];
      wg_fence();
#pragma unroll
      for (int i = 0; i < 8; i++) { if (i == 0) wg_ss40<0>(s, dQ, dK); else wg_ss40<1>(s, dQ + i * 16, dK + i * 16); }
      wg_commit();
      wg_wait<0>();
      acc_fence(s);
      TR(1)
#pragma unroll
      for (int j = 0; j < 4; j++) {
        if (lim < 8 * j) s[4 * j] = -INFINITY;
        if (lim < 8 * j + 1) s[4 * j + 1] = -INFINITY;
        if (lim < 8 * j - 8) s[4 * j + 2] = -INFINITY;
        if (lim < 8 * j - 7) s[4 * j + 3] = -INFINITY;
      }
      float m0 = fmaxf(fmaxf(fmaxf(s[0], s[1]), fmaxf(s[4], s[5])), fmaxf(fmaxf(s[8], s[9]), fmaxf(s[12], s[13])));
      float m1 = fmaxf(fmaxf(fmaxf(s[2], s[3]), fmaxf(s[6], s[7])), fmaxf(fmaxf(s[10], s[11]), fmaxf(s[14], s[15])));
      m0 = fmaxf(m0, fmaxf(s[16], s[17])); m1 = fmaxf(m1, fmaxf(s[18], s[19]));
      m0 = fmaxf(m0, __shfl_xor_sync(~0u, m0, 1)); m1 = fmaxf(m1, __shfl_xor_sync(~0u, m1, 1));
      m0 = fmaxf(m0, __shfl_xor_sync(~0u, m0, 2)); m1 = fmaxf(m1, __shfl_xor_sync(~0u, m1, 2));
      m0 *= -SCALE_LOG2E; m1 *= -SCALE_LOG2E;
      uint32_t p[10];
      float l0 = 0.f, l1 = 0.f;
#pragma unroll
      for (int k = 0; k < 10; k++) {
        const float e0 = ex2_fast(fmaf(s[2 * k], SCALE_LOG2E, (k & 1) ? m1 : m0)), e1 = ex2_fast(fmaf(s[2 * k + 1], SCALE_LOG2E, (k & 1) ? m1 : m0));
        p[k] = pack_bf16(e0, e1);
        if (k & 1) l1 += e0 + e1; else l0 += e0 + e1;
      }
      asm volatile("" : "+f"(l0), "+f"(l1));
      float oA[32], oB[32];
      wg_fence();
      wg_rs64<0>(oA, p[0], p[1], p[2], p[3], dV); wg_rs64<1>(oA, p[4], p[5], p[6], p[7], dV + 256); wg_rs64<1>(oA, p[8], p[9], 0, 0, dVm);
      wg_commit();
      wg_rs64<0>(oB, p[0], p[1], p[2], p[3], dV + 64); wg_rs64<1>(oB, p[4], p[5], p[6], p[7], dV + 320); wg_rs64<1>(oB, p[8], p[9], 0, 0, dVm + 64);
      wg_commit();
      l0 += __shfl_xor_sync(~0u, l0, 1); l1 += __shfl_xor_sync(~0u, l1, 1);
      l0 += __shfl_xor_sync(~0u, l0, 2); l1 += __shfl_xor_sync(~0u, l1, 2);
      const float i0 = rcp_fast(l0), i1 = rcp_fast(l1);
      const bool mrows = c == 2 && st < NSTEP - 1;
      auto send = [&](const float (&o)[32], auto hc) {
        constexpr int H = decltype(hc)::value;
        static_for2([&](auto bc) {
          constexpr int B = decltype(bc)::value, J = 16 * B;
          asm volatile("st.async.weak.shared::cluster.mbarrier::complete_tx::bytes.v4.b32 [%0 + %9], {%5,%6,%7,%8}, [%1];\n"
                       "st.async.weak.shared::cluster.mbarrier::complete_tx::bytes.v4.b32 [%2 + %9], {%5,%6,%7,%8}, [%3];\n"
                       "st.shared.v4.b32 [%4 + %9], {%5,%6,%7,%8};"
                       ::"r"(a1), "r"(b1), "r"(a2), "r"(b2), "r"(oa), "r"(pack_bf16(o[J] * i0, o[J + 1] * i0)), "r"(pack_bf16(o[J + 4] * i0, o[J + 5] * i0)),
                         "r"(pack_bf16(o[J + 8] * i0, o[J + 9] * i0)), "r"(pack_bf16(o[J + 12] * i0, o[J + 13] * i0)), "n"(H * 1024 + B * 512) : "memory");
        });
      };
      auto keep_tok = [&](const float (&o)[32], int H) {
        const uint32_t ta = l16 + C_OT + c * 4096 + H * 1024;
#pragma unroll
        for (int k = 0; k < 4; k++) {
          const int J = (k & 1) * 16 + (k >> 1) * 2;
          const float iv = (k >> 1) ? i1 : i0;
          stsm4(ta + (k & 1) * 512 + (k >> 1) * 2048, pack_bf16(o[J] * iv, o[J + 1] * iv), pack_bf16(o[J + 4] * iv, o[J + 5] * iv),
                pack_bf16(o[J + 8] * iv, o[J + 9] * iv), pack_bf16(o[J + 12] * iv, o[J + 13] * iv));
        }
      };
      wg_wait<1>();
      acc_fence(oA);
      if (mrows) send(oA, IC<0>());
      wg_wait<0>();
      acc_fence(oB);
      if (st < NSTEP - 1) bar_arrive(NB_PV, 384);
      if (mrows) {
        send(oB, IC<1>());
        __syncwarp();
        mbar_arrive_z(bars + B_O * 8, lane);
      } else if (c < 2) {
        keep_tok(oA, 0);
        keep_tok(oB, 1);
        __syncwarp();
        mbar_arrive_z(bars + B_OT * 8, lane);
      }
      TR(2)
      if (st == NSTEP - 1) break;
      mbar_expect_tx_z(bars + B_X * 8, 4096, t);
    }
    uint32_t tref;
    {
      const uint32_t tag = (st & 1) ^ 1;
      float oc0[12], oc1[12], oc2[12];
      mbar_wait(bars + B_O * 8, st & 1, 43);
      fence_async_smem();
      TR(3)
      wg_fence();
      out_tile(oc0, dWo, dO);
      wg_commit();
      out_tile(oc1, dWo + 1024, dO);
      wg_commit();
      asm volatile("" : "+r"(pgbits));
      auto put = [&](const float (&oc)[12], auto tlc) {
        constexpr int TL = decltype(tlc)::value;
        static_for3([&](auto jc) {
          constexpr int j = decltype(jc)::value;
          uint8_t* p = Pw + ((pgbits >> (2 * (TL * 3 + j))) & 3) * 4096;
          asm volatile("st.relaxed.gpu.global.u32 [%0 + %3], %1; st.relaxed.gpu.global.u32 [%0 + %3 + 128], %2;" ::"l"(p),
                       "r"((pack_bf16(oc[4 * j], oc[4 * j + 1]) & ~1u) | tag), "r"((pack_bf16(oc[4 * j + 2], oc[4 * j + 3]) & ~1u) | tag),
                       "n"((TL * 36 + j) * 16384) : "memory");
        });
      };
      wg_wait<1>();
      acc_fence(oc0);
      put(oc0, IC<0>());
      sts32(sb + C_INFO + 24, clk32());
      TR(4)
      wg_wait<0>();
      if (rank != 2) {
        wg_fence();
        out_tile(oc2, dWo + 2048, dO);
        wg_commit();
        acc_fence(oc1);
        put(oc1, IC<1>());
        bar_sync(NB_TA, 160);
        TR(5)
        wg_wait<0>();
        bar_arrive(NB_W0, 416);
        acc_fence(oc2);
        put(oc2, IC<2>());
      } else {
        bar_arrive(NB_W0, 416);
        acc_fence(oc1);
        put(oc1, IC<1>());
        bar_sync(NB_TA, 160);
      }
      tref = __shfl_sync(~0u, lds32(sb + C_INFO + 12), 0);
      mbar_arrive_remote_z(((t & 1) ? b2 : b1) + (B_F - B_O) * 8, t >> 1);
      mbar_expect_tx_z(bars + B_O * 8, 4096, t);
      TR(6)
    }
    const int sn = (st + 1) & 3;
    {
      const uint32_t flip = (st & 1) ? ~0u : 0u;
      const bool u16 = lane & 16;
      uint8_t* mw = Mw + sn * 65536;
      asm volatile("" : "+l"(mw));
      const uint32_t bs = (lane & 4) ? 0x3f800000u : 0x00003f80u, bs0 = (lane & 8) ? 0u : bs, bs1 = (lane & 8) ? bs : 0u;
      const bool early = st < DELTA && b % 3 != 0;
      uint32_t m0word = 0;
      if (__builtin_expect(early, 0)) {
        const unsigned short* mp = (const unsigned short*)mem0 + ((lane & 1) * 4 + (lane >> 4) * 2) * DM + b / 3 * 16 + c * 4 + ((lane >> 2) & 3);
        m0word = (uint32_t)mp[0] | (uint32_t)mp[DM] << 16;
      }
      STATC(c_rdy)
      wait_clock(tref + gate_p);
      TR(7)
      uint32_t mword;
      int it = 0;
      bool all;
#pragma unroll 1
      do {
        const uint4 q0 = ld_rlx128(Pr0), q1 = ld_rlx128(Pr0 + 2048), q2 = ld_rlx128(Pr1), q3 = ld_rlx128(Pr1 + 2048);
        float d0[4] = {0.f, 0.f, 0.f, 0.f}, d1[4] = {0.f, 0.f, 0.f, 0.f};
        mma16816(d0, q0.x, q0.y, q0.z, q0.w, bs0, bs1);
        mma16816(d1, q1.x, q1.y, q1.z, q1.w, bs0, bs1);
        mma16816(d0, q2.x, q2.y, q2.z, q2.w, bs0, bs1);
        mma16816(d1, q3.x, q3.y, q3.z, q3.w, bs0, bs1);
        all = __all_sync(~0u, (int)and3(and_x(q0.x, q1.x, flip), and_x(q2.x, q3.x, flip), 1u));
        const float a0 = d0[0] + d1[0], a1 = d0[1] + d1[1], a2 = d0[2] + d1[2], a3 = d0[3] + d1[3];
        mword = pack_bf16((u16 ? a2 : a0) + __shfl_xor_sync(~0u, u16 ? a0 : a2, 16), (u16 ? a3 : a1) + __shfl_xor_sync(~0u, u16 ? a1 : a3, 16));
        asm volatile("{ .reg .pred p; setp.ne.u32 p, %2, 0; @p st.relaxed.gpu.global.u32 [%0], %1; }" ::"l"(mw), "r"(early ? m0word : mword), "r"((uint32_t)all) : "memory");
      } while (__builtin_expect(!all, 0) && ++it < SPIN_LIMIT);
      bar_arrive(NB_RD, 384);
      STATC(c_mst)
      STAT(0, lds32(sb + C_INFO + 24) - tref) STAT(1, c_rdy - tref) STAT(2, c_mst - tref) STAT(3, tref) STAT(4, it)
      if (!all) fail(44);
      TRV(14, it)
    }
    TR(9)
    {
      const uint32_t ma = l16 + C_M + c * 2048 + mi * 4;
      auto scan = [&](uint32_t m, uint32_t a) { return __vimax3_u32(__vimax3_u32(m, lds32(a), lds32(a + 512)), lds32(a + 1024), lds32(a + 1536)); };
      mbar_wait(bars + B_M0 * 8, (st + 1) & 1, 45);
      bar_arrive(NB_M0, 384);
      STATC(c_g0)
      TR(10)
      uint32_t m = scan(0, ma);
      mbar_wait(bars + B_M1 * 8, (st + 1) & 1, 46);
      bar_arrive(NB_M1, 384);
      STATC(c_g1)
      TR(11)
      m = scan(m, ma + 8192);
      mbar_wait(bars + B_M2 * 8, (st + 1) & 1, 47);
      STATC(c_g2)
      TR(12)
      int it = 0;
      const bool redo = bar_or(NB_M2, 384, scan(m, ma + 16384) == ~0u);
      if (__builtin_expect(redo, 0)) {
#pragma unroll 1
        for (int g = 0; g < 3;) {
          if (!__any_sync(~0u, scan(0, ma + g * 8192) == ~0u)) { g++; continue; }
          give_up(++it, SPIN_LIMIT, 48);
          if (lane == 0) {
            mbar_expect_tx(bars + (B_R + c) * 8, 2048);
            bulk_g2s(sb + C_M + g * 8192 + c * 2048, (const uint8_t*)g_M + sn * 65536 + (lds32(sb + C_POL + sn * 4) ? 4096 : 12288) + g * 16384 + c * 2048,
                     2048, bars + (B_R + c) * 8);
          }
          __syncwarp();
          mbar_wait(bars + (B_R + c) * 8, nretry++ & 1, 49);
        }
        bar_arrive(NB_M0, 384);
      }
      STAT(5, c_g0 - tref) STAT(7, c_g1 - tref) STAT(8, c_g2 - tref)
      STAT(9, clk32() - tref) STAT(6, it + redo * 256)
      TR(13)
      TRV(15, it)
      st_rlx32(Mw + (st & 3) * 65536, ~0u);
    }
  }
}

__device__ __forceinline__ void chain_dma(const uint32_t sb, const int w, const int lane, const uint32_t rank, const int h) {
  const uint32_t bars = sb + C_BAR;
  bar_sync(NB_ALL, 512);
  if (w == 12) { HD(3) }
  bar_sync(NB_ALL, 512);
  if (w == 12) { HD(4) }
  cluster_sync();
  if (w == 12) { HD(5) }
  if (w == 12) {
    u64 best = 0;
    uint32_t npatch = 0;
#pragma unroll 1
    for (int st = -1; st < NSTEP; st++) {
      const int sg = st - DELTA;
      uint32_t info = 0;
      if (st >= 0) {
        if (sg >= 0) {
          const u64 k = wait_keys(g_fl.key[0][sg], lane, 50);
          if (k > best) { best = k; info = 4 | ((key_token(k) >> 3) & 3); }
        }
        TR(0)
        if (st > 0) mbar_wait(bars + B_P1 * 8, (st - 1) & 1, 51);
        sts32(sb + C_INFO + (st & 1) * 4, info);
        if (sg >= 0) {
          if (XGATE == 3) mbar_wait(bars + B_X * 8, (st - 1) & 1, 58);
          else if ((int)lds32(sb + C_INFO + 8) < st - 1) mbar_gate(bars + (B_M0 + XGATE) * 8, (st - 1) & 1);
          TR(1)
          if (lane == 0) {
            fence_async_glb();
            mbar_expect_tx(bars + B_XL2 * 8, 32768);
            bulk_g2s(sb + C_X + 32768, g_xs[1] + (size_t)sg * 32768, 32768, bars + B_XL2 * 8);
          }
          __syncwarp();
          mbar_wait(bars + B_XL2 * 8, sg & 1, 52);
        }
        TR(2)
        bar_arrive(NB_W0, 416);
        mbar_wait(bars + B_XF * 8, st & 1, 53);
      }
      if (st + 1 < NSEG) {
        if (lane == 0) {
          mbar_expect_tx(bars + B_XL1 * 8, 32768);
          bulk_g2s(sb + C_X, g_xs[0] + (size_t)(st + 1) * 32768, 32768, bars + B_XL1 * 8);
        }
        __syncwarp();
        mbar_wait(bars + B_XL1 * 8, (st + 1) & 1, 57);
      }
      TR(3)
      if (st < 1) { HD(7 + st) }
      bar_arrive(NB_X1, 288);
      if (__builtin_expect(info, 0)) {
        if (npatch > 0) mbar_wait(bars + B_P3 * 8, (npatch - 1) & 1, 55);
        npatch++;
        wait_count(g_fl.patch[sg], 1, 56);
        if (lane == 0) {
          fence_async_glb();
          mbar_expect_tx(bars + B_XL3 * 8, 8192);
          bulk_g2s(sb + C_X + 65536, g_patch + (size_t)sg * 8192, 8192, bars + B_XL3 * 8);
        }
        __syncwarp();
      }
    }
  } else if (w == 13) {
    constexpr uint32_t NP = 8192 / SHIP;
    const uint32_t o = (lane >> 1) * SHIP, own = sb + C_Q + rank * 10240, bt = bars + B_T * 8;
    const uint32_t d2 = 1 + (lane & 1);
    const uint32_t src2 = (rank == 0 ? sb + C_SA : rank == 1 ? own : sb + C_SB) + o;
    const uint32_t skip = (lane & 1) ? 4 | (o >> 11) : 8;
    uint32_t npatch = 0;
#pragma unroll 1
    for (int st = 0; st < NSTEP; st++) {
      mbar_wait(bars + (SHIPLATE ? B_P1 : B_P2) * 8, st & 1, 62);
      fence_async_smem();
      if (st > 0) mbar_wait(bars + B_F * 8, (st - 1) & 1, 60);
      const uint32_t info = lds32(sb + C_INFO + (st & 1) * 4);
      TR(2)
      if (st < NSEG && rank != 0 && lane < 2 * NP && d2 == 1) bulk_s2r(mapa_u32(own + o, 0), sb + C_SA + o, SHIP, mapa_u32(bt, 0));
      __syncwarp();
      TR(3)
      mbar_wait(bars + B_P1 * 8, st & 1, 61);
      fence_async_smem();
      TR(0)
      if (st >= DELTA && lane < 2 * NP && d2 != rank && info != skip) bulk_s2r(mapa_u32(own + o, d2), src2, SHIP, mapa_u32(bt, d2));
      __syncwarp();
      TR(1)
      if (__builtin_expect(info, 0)) {
        mbar_wait(bars + B_P3 * 8, npatch & 1, 63);
        npatch++;
        fence_async_smem();
        if (rank != 2 && lane == 0) bulk_s2r(mapa_u32(own + (info & 3) * 2048, 2), sb + C_SP, 2048, mapa_u32(bt, 2));
        __syncwarp();
      }
    }
  } else if (w == 14) {
    const int s0 = rank == 0 ? 0 : DELTA;
    mbar_expect_tx_z(bars + B_T * 8, s0 == 0 ? 16384 : 0, lane);
#pragma unroll 1
    for (int st = 0; st < NSTEP; st++) {
      const int sg = st - s0;
      const bool act = (unsigned)sg < (unsigned)NSEG;
      mbar_wait(bars + B_OT * 8, st & 1, 70);
      fence_async_smem();
      if (OGATE >= 0 && st < NSTEP - 1 && (rank != 0 || !OEARLY)) mbar_wait(bars + (OGATE > 0 ? B_M0 + OGATE - 1 : B_F) * 8, (st + (OGATE > 0)) & 1, 71);
      TR(0)
      if (lane == 0) {
        if (act) bulk_s2g(g_O[rank] + ((size_t)(sg & (OSLOTS - 1)) * 32 + h) * 8192, sb + C_OT, 8192);
        asm volatile("cp.async.bulk.commit_group;" ::: "memory");
        asm volatile("cp.async.bulk.wait_group.read 0;" ::: "memory");
        mbar_expect_tx(bars + B_T * 8, (unsigned)(sg + 1) < (unsigned)NSEG ? 16384 : 0);
        asm volatile("cp.async.bulk.wait_group 0;" ::: "memory");
        if (act) red_release(&g_fl.oflag[rank][sg][h >> 2]);
      }
      __syncwarp();
      TR(1)
    }
  } else {
    mbar_arrive_z(bars + B_M0 * 8, lane); mbar_arrive_z(bars + B_M1 * 8, lane); mbar_arrive_z(bars + B_M2 * 8, lane);
    const uint32_t gate_g = GATE_G, gate_m = GATE_M;
#pragma unroll 1
    for (int st = 0; st < NSTEP; st++) {
      mbar_wait(bars + B_M2 * 8, st & 1, 74);
      sts32(sb + C_INFO + 8, st);
      if (st == NSTEP - 1) break;
      mbar_wait(bars + B_X * 8, st & 1, 75);
      if (st < 4) { HD(8 + st) }
      if (st == NSTEP - 2) { HD(12) }
      const uint32_t now = gtime() & ~31u, tag = (st + 1) & 31;
      uint32_t s0, s1, s2;
      int it = 0;
#pragma unroll 1
      do {
        s0 = ld_rlx32(&g_fl.stamp[lane]) ^ tag; s1 = ld_rlx32(&g_fl.stamp[32 + lane]) ^ tag; s2 = ld_rlx32(&g_fl.stamp[64 + lane]) ^ tag;
        give_up(it++, SPIN_LIMIT, 76);
      } while (__any_sync(~0u, ((s0 | s1 | s2) & 31) != 0));
      const uint32_t tref = now + __reduce_max_sync(~0u, __vimax3_s32((int)(s0 - now), (int)(s1 - now), (int)(s2 - now)));
      const uint32_t g0 = gtime();
      uint32_t g1, c1;
      it = 0;
      do { g1 = gtime(); c1 = clk32(); } while (g1 == g0 && ++it < 64);
      c1 -= (g1 - tref) * 7 / 4;
      sts32(sb + C_INFO + 12, c1);
      TR(0)
      bar_arrive(NB_TA, 160);
      const int sn = (st + 1) & 3;
      const uint8_t* src = (const uint8_t*)g_M + sn * 65536 + (lds32(sb + C_POL + sn * 4) ? 4096 : 12288);
      c1 += gate_m;
      const int d = (int)(c1 - 600 - clk32());
      if (d > 0) __nanosleep(d / 4);
#pragma unroll 1
      for (int g = 0; g < 3; g++) {
        mbar_expect_tx_z(bars + (B_M0 + g) * 8, 8192, lane);
        wait_clock(c1 + g * gate_g);
        if (lane == 0) bulk_g2s(sb + C_M + g * 8192, src + g * 16384, 8192, bars + (B_M0 + g) * 8);
        __syncwarp();
        TR(1 + g)
      }
    }
  }
}

__global__ void __cluster_dims__(3, 1, 1) __launch_bounds__(512, 1)
chain_kernel(const bf16* __restrict__ Wq, const bf16* __restrict__ Wk, const bf16* __restrict__ Wv,
             const bf16* __restrict__ Wo, const bf16* __restrict__ mem0) {
  extern __shared__ __align__(1024) uint8_t smem_raw[];
  const uint32_t sb = (smem_u32(smem_raw) + 1023) & ~1023u;
  const int tid = threadIdx.x, lane = tid & 31;
  const int w = __shfl_sync(~0u, tid >> 5, 0);
  uint32_t rank;
  asm volatile("mov.u32 %0, %%cluster_ctarank;" : "=r"(rank));
  const int h = blockIdx.x / 3;
  asm volatile("griddepcontrol.launch_dependents;" ::: "memory");
  TG(0)
  if (tid == 0) {
    const uint32_t bars = sb + C_BAR;
    mbar_init(bars + B_M0 * 8, 1); mbar_init(bars + B_M1 * 8, 1); mbar_init(bars + B_M2 * 8, 1);
    for (int i = 0; i < 4; i++) mbar_init(bars + (B_R + i) * 8, 1);
    mbar_init(bars + B_X * 8, 9); mbar_init(bars + B_O * 8, 2); mbar_init(bars + B_T * 8, 1); mbar_init(bars + B_F * 8, 2);
    mbar_init(bars + B_XL1 * 8, 1); mbar_init(bars + B_XL2 * 8, 1); mbar_init(bars + B_XL3 * 8, 1);
    mbar_init(bars + B_P1 * 8, 8); mbar_init(bars + B_P2 * 8, 8); mbar_init(bars + B_P3 * 8, 8); mbar_init(bars + B_OT * 8, 2); mbar_init(bars + B_XF * 8, 8);
    asm volatile("fence.mbarrier_init.release.cluster;" ::: "memory");
  }
  {
    cp16(sb + C_OT + tid * 16, mem0 + (tid & 7) * DM + (tid >> 3) * 8);
    const bf16* W1 = (rank == 0 ? Wq : rank == 1 ? Wk : Wv) + h * 128;
#pragma unroll 4
    for (int cidx = tid; cidx < 512 * 16; cidx += 512) {
      const int d = cidx >> 4, q = cidx & 15;
      cp16(sb + C_X + d * W_STRIDE + q * 16, W1 + (size_t)d * HD + q * 8);
    }
    const int nt = rank == 2 ? 2 : 3;
    for (int cidx = tid; cidx < nt * 1024; cidx += 512) {
      const int tl = cidx >> 10, e = (cidx >> 3) & 127, q = cidx & 7;
      const int es = (e & ~30) | ((e & 6) << 2) | ((e >> 2) & 6);
      cp16(sb + C_WO + tl * 16384 + e * 128 + ((q ^ (e & 7)) << 4), Wo + (size_t)(h * 128 + es) * DM + (tl * 3 + rank) * 64 + q * 8);
    }
    asm volatile("cp.async.commit_group;" ::: "memory");
    if (w == 0) { HD(0) }
    if (lane == 0) {
      if (w < 4) sts32(sb + C_POL + w * 4, probe_polarity(g_M + w * 16384 + (blockIdx.x & 31) * 32));
      else if (w == 4) {
        const int u = (rank == 2 ? 0 : rank + 1) * 32 + h;
        const uint32_t pol = probe_polarity(g_P + u * 4096);
        sts32(sb + C_POL + 16, pol);
        st_rlx32(&g_fl.pol[u], pol + 1);
      }
    }
    if (w == 0) { HD(1) }
    asm volatile("cp.async.wait_group 0;" ::: "memory");
    fence_async_smem();
    __syncthreads();
    if (w == 0) { HD(2) }
  }
  if (w < 8) {
    reg_inc<184>();
    chain_proj(sb, w, lane, rank);
    TG(1)
    TRDUMP
    cluster_sync();
  } else if (w < 12) {
    reg_dec<120>();
    chain_mem(sb, w, lane, rank, h, mem0);
    STATDUMP
    TRDUMP
    cluster_sync();
  } else {
    reg_dec<24>();
    chain_dma(sb, w, lane, rank, h);
    TRDUMP
    cluster_sync();
  }
}
#undef TRC
#undef TRS

constexpr int K_BAR = 0, K_LN = 128, K_FH = 320, K_FS = 512, K_FY = 2048;
constexpr int K_W = 3072;
constexpr int K_O = K_W + 3 * 49152;
constexpr int K_ST = K_O + 65536;
constexpr int K_SMEM = K_ST + 16384;
static_assert(K_SMEM <= 232448 && 512 * W_STRIDE <= 3 * 49152, "shared memory");
enum { KB_FULL = 0, KB_EMPTY = 2, KB_OK = 4, KB_GO = 7, KB_ST = 10, KB_REL = 12 };
enum { KN_ST = 1, KN_ST1, KN_REL, KN_FFN, KN_INIT, KN_RES, KN_CAND, KN_TAKEN };
#define GATE_R 450
struct WorkerParams {
  const bf16 *x0, *Wo, *w_r, *w_gate, *w_up, *w_down;
  bf16* out;
};
#define TRC (96 + blockIdx.x)
#define FT(e)
#define FOR_UNITS _Pragma("unroll 1") for (int st = 0, n = 0; st < NSTEP; st++) \
                  _Pragma("unroll 1") for (int v = st < NSEG ? 0 : st < NSTEP - 1 ? 1 : 2, sg = v ? st - DELTA : st; v < (st >= DELTA ? 3 : 1); v++, n++, sg = st - DELTA)

__device__ __forceinline__ void ffn_slice(uint32_t sb, int t, int nu, const bf16* yrow, int ev) {
  const int lane = t & 31, c = t >> 5;
  FT(1)
  const uint32_t sg_ = sb + (nu == 3 ? K_FS : K_ST), sh = sb + K_FH;
  {
    const uint2 r = ld_rlx64(yrow + t * 4);
    asm volatile("st.shared.v2.b32 [%0], {%1,%2};" ::"r"(sb + K_FY + t * 8), "r"(r.x), "r"(r.y) : "memory");
    __syncwarp();
  }
  const uint32_t sy = sb + K_FY + (t >> 2) * 32;
  FT(2)
#pragma unroll 1
  for (int u = 0; u < nu; u++) {
    float g[8];
#pragma unroll
    for (int i = 0; i < 8; i++) g[i] = 0.f;
    const uint32_t wa = sb + K_W + u * 49152 + c * 8192 + lane * 16;
    auto fma8 = [&](float y, const uint4& a) {
      g[0] += y * bf_lo(a.x); g[1] += y * bf_hi(a.x); g[2] += y * bf_lo(a.y); g[3] += y * bf_hi(a.y);
      g[4] += y * bf_lo(a.z); g[5] += y * bf_hi(a.z); g[6] += y * bf_lo(a.w); g[7] += y * bf_hi(a.w);
    };
    uint4 a0 = lds128(wa), a1 = lds128(wa + 512);
    uint32_t y0 = lds32(sy);
#pragma unroll 1
    for (int i = 0; i < 16; i += 4) {
      const uint4 b0 = lds128(wa + (i + 2) * 512), b1 = lds128(wa + (i + 3) * 512);
      const uint32_t y1 = lds32(sy + i * 2 + 4);
      fma8(bf_lo(y0), a0); fma8(bf_hi(y0), a1);
      a0 = lds128(wa + (i + 4) * 512); a1 = lds128(wa + (i + 5) * 512);
      y0 = lds32(sy + i * 2 + 8);
      fma8(bf_lo(y1), b0); fma8(bf_hi(y1), b1);
    }
#pragma unroll
    for (int i = 0; i < 4; i++) g[i] = ((lane & 16) ? g[4 + i] : g[i]) + __shfl_xor_sync(~0u, (lane & 16) ? g[i] : g[4 + i], 16);
#pragma unroll
    for (int i = 0; i < 2; i++) g[i] = ((lane & 8) ? g[2 + i] : g[i]) + __shfl_xor_sync(~0u, (lane & 8) ? g[i] : g[2 + i], 8);
    g[0] = ((lane & 4) ? g[1] : g[0]) + __shfl_xor_sync(~0u, (lane & 4) ? g[0] : g[1], 4);
    sts32(sg_ + u * 512 + c * 128 + ((lane & 3) * 8 + (lane >> 2)) * 4, __float_as_uint(g[0]));
  }
  FT(3)
  bar_sync(KN_FFN, 128);
  {
    const uint32_t pa = sg_ + c * 512 + lane * 4;
    const float gt = round_bf16((__uint_as_float(lds32(pa)) + __uint_as_float(lds32(pa + 128))) + (__uint_as_float(lds32(pa + 256)) + __uint_as_float(lds32(pa + 384))));
    const float up = __shfl_xor_sync(~0u, gt, 16);
    if (lane < 16 && c < nu) sts32(sh + (c * 16 + lane) * 4, __float_as_uint(round_bf16(round_bf16(gt / (1.f + __expf(-gt))) * up)));
  }
  bar_sync(KN_FFN, 128);
  FT(4)
  float a0 = 0.f, a1 = 0.f, a2 = 0.f, a3 = 0.f;
#pragma unroll 1
  for (int u = 0; u < 2 * nu; u++) {
    const uint32_t wa = sb + K_W + (u >> 1) * 49152 + 32768 + (u & 1) * 8192 + t * 8;
    const uint4 h0 = lds128(sh + u * 32), h1 = lds128(sh + u * 32 + 16);
    const uint32_t hv[8] = {h0.x, h0.y, h0.z, h0.w, h1.x, h1.y, h1.z, h1.w};
    uint2 d[8];
#pragma unroll
    for (int k = 0; k < 8; k++) asm volatile("ld.shared.v2.b32 {%0,%1}, [%2];" : "=r"(d[k].x), "=r"(d[k].y) : "r"(wa + k * 1024) : "memory");
#pragma unroll
    for (int k = 0; k < 8; k++) {
      const float hf = __uint_as_float(hv[k]);
      a0 += hf * bf_lo(d[k].x); a1 += hf * bf_hi(d[k].x); a2 += hf * bf_lo(d[k].y); a3 += hf * bf_hi(d[k].y);
    }
  }
  FT(5)
  asm volatile("red.relaxed.gpu.global.add.v4.f32 [%0], {%1,%2,%3,%4};" ::"l"(&g_fl.upd[ev][t * 4]), "f"(a0), "f"(a1), "f"(a2), "f"(a3) : "memory");
  bar_sync(KN_FFN, 128);
  if (t == 96) red_release(g_fl.ffncnt[ev]);
  __syncwarp();
}
__device__ __forceinline__ Row ffn_finish(int ver, int ev, u64 key, int lane) {
  const int tok = key_token(key);
  Row x = load_row(g_rows[ver][0] + (size_t)tok * DM, lane);
  const Row y = load_row(g_rows[ver][1] + (size_t)tok * DM, lane);
  const float sig = round_bf16(1.f / (1.f + __expf(-key_score(key))));
  wait_count(g_fl.ffncnt[ev], NWORK, 80);
#pragma unroll
  for (int q = 0; q < 4; q++) {
    const uint4 u = ld_rlx128(&g_fl.upd[ev][q * 128 + lane * 4]);
    const uint32_t a = pack_bf16(__uint_as_float(u.x), __uint_as_float(u.y)), b = pack_bf16(__uint_as_float(u.z), __uint_as_float(u.w));
    x.w[2 * q] = add_bf16x2(x.w[2 * q], add_bf16x2(y.w[2 * q], pack_bf16(bf_lo(a) * sig, bf_hi(a) * sig)));
    x.w[2 * q + 1] = add_bf16x2(x.w[2 * q + 1], add_bf16x2(y.w[2 * q + 1], pack_bf16(bf_lo(b) * sig, bf_hi(b) * sig)));
  }
  return x;
}
__device__ __forceinline__ uint2 group_ln(uint2 r, float& e, uint32_t sl, uint32_t sw, int lane) {
  const float x0 = bf_lo(r.x), x1 = bf_hi(r.x), x2 = bf_lo(r.y), x3 = bf_hi(r.y);
  const float s = (x0 + x1) + (x2 + x3), q = fmaf(x0, x0, x1 * x1) + fmaf(x2, x2, x3 * x3);
  const bool u16 = lane & 16, u8 = lane & 8;
  const float a = (u16 ? q : s) + __shfl_xor_sync(~0u, u16 ? s : q, 16), b = e + __shfl_xor_sync(~0u, e, 16);
  float v = (u8 ? b : a) + __shfl_xor_sync(~0u, u8 ? a : b, 8);
  v += __shfl_xor_sync(~0u, v, 4); v += __shfl_xor_sync(~0u, v, 2); v += __shfl_xor_sync(~0u, v, 1);
  sts32(sl + sw, __float_as_uint(v));
  bar_sync(KN_RES, 128);
  const uint4 ss = lds128(sl), qq = lds128(sl + 32), ee = lds128(sl + 16);
  const float m = ((__uint_as_float(ss.x) + __uint_as_float(ss.y)) + (__uint_as_float(ss.z) + __uint_as_float(ss.w))) * (1.f / DM);
  const float m2 = ((__uint_as_float(qq.x) + __uint_as_float(qq.y)) + (__uint_as_float(qq.z) + __uint_as_float(qq.w))) * (1.f / DM);
  e = (__uint_as_float(ee.x) + __uint_as_float(ee.y)) + (__uint_as_float(ee.z) + __uint_as_float(ee.w));
  float rs;
  asm("rsqrt.approx.ftz.f32 %0, %1;" : "=f"(rs) : "f"(fmaxf(fmaf(-m, m, m2), 0.f) + 1e-5f));
  return make_uint2(pack_bf16((x0 - m) * rs, (x1 - m) * rs), pack_bf16((x2 - m) * rs, (x3 - m) * rs));
}
__device__ __forceinline__ uint32_t score_bits(float r) {
  const uint32_t b = pack_bf16(0.f, r);
  return (b & 0x80000000u) ? ~b : (b | 0x80000000u);
}

__global__ void __launch_bounds__(640, 1) worker_kernel(const __grid_constant__ WorkerParams prm) {
  extern __shared__ __align__(1024) uint8_t smem_raw[];
  const uint32_t sb = smem_u32(smem_raw);
  const int tid = threadIdx.x, lane = tid & 31;
  const int w = __shfl_sync(~0u, tid >> 5, 0);
  const int me = blockIdx.x, kb = me >> 2, cb = me & 3;
  const bool full = me < 32;
  const uint32_t bars = sb + K_BAR;
  TG(0)
  if (tid == 0) {
    for (int i = 0; i < 2; i++) { mbar_init(bars + (KB_FULL + i) * 8, 1); mbar_init(bars + (KB_EMPTY + i) * 8, 1); }
    for (int i = 0; i < 9; i++) mbar_init(bars + (KB_OK + i) * 8, i < 3 ? 4 : 1);
    sts32(sb + K_LN + 144, 0); sts32(sb + K_LN + 176, 0); sts32(sb + K_LN + 180, ~0u);
    asm volatile("fence.mbarrier_init.release.cluster;" ::: "memory");
  }
  if (full) {
    const bf16* W1 = prm.Wo + (size_t)kb * 512 * DM + cb * 128;
#pragma unroll 4
    for (int cidx = tid; cidx < 512 * 16; cidx += 640) {
      const int d = cidx >> 4, q = cidx & 15;
      cp16(sb + K_W + d * W_STRIDE + q * 16, W1 + (size_t)d * DM + q * 8);
    }
    asm volatile("cp.async.commit_group;" ::: "memory");
    asm volatile("cp.async.wait_group 0;" ::: "memory");
  }
  fence_async_smem();
  __syncthreads();
  if (w < 8) {
    reg_inc<176>();
    if (full) {
      uint32_t wA[32][4];
      load_wfrags(wA, sb + K_W, w, lane);
      bar_arrive(KN_INIT, 384);
      const uint32_t sp = pin(sb + K_ST + ((lane >> 4) * 8 + (lane & 7)) * 256 + (((2 * w + ((lane >> 3) & 1)) ^ (lane & 7)) << 4));
      const uint32_t tm = pin(lane < 4 ? 0x00010001u : 0u);
      FOR_UNITS {
        float d[16];
        mbar_wait(bars + (KB_FULL + (n & 1)) * 8, (n >> 1) & 1, 81);
        TR(4 * v)
        const uint64_t db = mk_desc(sb + K_O + (n & 1) * 32768, 128, 2048, 0);
        wg_fence();
#pragma unroll
        for (int ks = 0; ks < 32; ks++) {
          if (ks == 0) wg_rs32<0, 0>(d, wA[ks], db);
          else wg_rs32<0, 1>(d, wA[ks], db + (ks >> 3) * 512 + (ks & 7) * 16);
        }
        wg_commit();
        mbar_wait(bars + (KB_ST + (n & 1)) * 8, ((n >> 1) & 1) ^ 1, 82);
        wg_wait<0>();
        acc_fence(d);
        TR(4 * v + 1)
        const uint32_t tag = (sg & 2) ? 0u : tm;
        uint32_t pk[8];
#pragma unroll
        for (int i = 0; i < 8; i++) pk[i] = (pack_bf16(d[2 * i], d[2 * i + 1]) & ~tm) | tag;
        stsm4t(sp + (n & 1) * 8192, pk[0], pk[1], pk[2], pk[3]);
        stsm4t(sp + (n & 1) * 8192 + 4096, pk[4], pk[5], pk[6], pk[7]);
        bar_arrive(KN_ST + (n & 1), 288);
        TR(4 * v + 2)
      }
    }
  } else if (w < 12) {
    reg_dec<56>();
    if (full) {
      const int t = pin(tid - 256), ln = t & 31;
      const uint32_t sw = pin((lane >> 3) * 16 + (w - 8) * 4);
      const uint32_t so = pin((w - 8) * 8192 + me * 256 + ((lane * 8) ^ ((me & 7) << 4)));
      uint2 wr = ld_rlx64(prm.w_r + t * 4);
      int sstar = -1;
      auto records = [&](int sg) {
        uint4 r;
        int it = 0;
        while ((int)(r = lds128(sb + K_LN + 144)).x <= sg) { give_up(++it, SPIN_LIMIT, 86); __nanosleep(50); }
        return r;
      };
      uint32_t sl = sb + K_LN;
      float rr = 0.f;
      int kprev = -1, pv = 0, psg = 0;
      uint2 x = make_uint2(0, 0);
      auto finish = [&](int v, int sg) {
        bf16* dst = g_rows[v][0] + (sg * 32 + me) * DM + t * 4;
        *(uint2*)dst = x;
        sl ^= 64;
        const uint2 y = group_ln(x, rr, sl, sw, ln);
        *(uint2*)(dst + NTOK * DM) = y;
        x = make_uint2(add_bf16x2(x.x, y.x), add_bf16x2(x.y, y.y));
        *(uint2*)(v == (sg < sstar ? 1 : 2) ? prm.out + (sg * 32 + me) * DM + t * 4 : dst + 2 * NTOK * DM) = x;
        asm volatile("{ .reg .pred p; setp.eq.u32 p, %2, 0; @p st.relaxed.gpu.global.u64 [%0], %1; }" ::"l"(&g_fl.key[0][0][0] + max(kprev, 0)),
                     "l"((u64)score_bits(rr) << 32 | (uint32_t)~(kprev & (NTOK - 1))), "r"(t | (kprev < 0)) : "memory");
        kprev = v * NTOK + sg * 32 + me;
        asm volatile("" : "+r"(wr.x), "+r"(wr.y));
        rr = fmaf(bf_lo(y.x), bf_lo(wr.x), bf_hi(y.x) * bf_hi(wr.x)) + fmaf(bf_lo(y.y), bf_lo(wr.y), bf_hi(y.y) * bf_hi(wr.y));
      };
      FOR_UNITS {
        const uint8_t* src = g_part[v] + (sg & 1) * (32 * 8192) + so;
        const bf16* xin = (v ? g_rows[0][2] : prm.x0) + (sg * 32 + me) * DM;
        if (v == 2) {
          const uint4 r = records(sg);
          if (((sg < 32 ? r.y : r.z) >> (sg & 31)) & 1) xin = g_x2p + sg * DM;
        }
        mbar_wait(bars + (KB_GO + v) * 8, sg & 1, 87);
        TR(4 * v)
        uint2 p[8];
#pragma unroll
        for (int k = 0; k < 8; k++) p[k] = ld_rlx64(src + k * 32768);
        const uint2 x0 = ld_rlx64(xin + t * 4);
        if (pv) finish(pv, psg);
        const uint32_t flip = lds32(sb + K_LN + 176 + (sg & 2) * 2);
        int it = 0;
#pragma unroll 1
        while (__builtin_expect(!__all_sync(~0u, (int)and3(and3(and_x(p[0].x, p[1].x, flip), and_x(p[2].x, p[3].x, flip), 1u),
                                                           and_x(p[4].x, p[5].x, flip), and_x(p[6].x, p[7].x, flip)) | (t & 1)), 0)) {
          give_up(++it, SPIN_LIMIT, 85);
#pragma unroll
          for (int k = 0; k < 8; k++) p[k] = ld_rlx64(src + k * 32768);
        }
        mbar_arrive_z(bars + (KB_OK + v) * 8, ln);
#define P8(h, f) (((h(p[0].f) + h(p[1].f)) + (h(p[2].f) + h(p[3].f))) + ((h(p[4].f) + h(p[5].f)) + (h(p[6].f) + h(p[7].f))))
        x = make_uint2(add_bf16x2(x0.x, pack_bf16(P8(bf_lo, x), P8(bf_hi, x))), add_bf16x2(x0.y, pack_bf16(P8(bf_lo, y), P8(bf_hi, y))));
#undef P8
        TRV(12 + v, it)
        TR(4 * v + 1)
        pv = v; psg = sg;
        if (v == 0 || (v == 2 && st >= NSEG)) {
          pv = 0;
          finish(v, sg);
          sl ^= 64;
          const uint2 y = group_ln(x, rr, sl, sw, ln);
          if (v == 0) *(uint2*)(g_xs[1] + (sg * 4 + (me >> 3)) * 8192 + (t >> 4) * 1024 + (me & 7) * 128 + ((((t & 15) >> 1) ^ (me & 7)) << 4) + (t & 1) * 8) = y;
          sts32(sb + K_LN + 128, score_bits(rr));
          bar_arrive(KN_REL, 160);
          kprev = -1;
          if (__builtin_expect(v == 0 && sg == NSEG - 1, 0)) {
            sstar = records(NSEG - 1).w;
            const int nc = min(sstar, NSEG - 1 - DELTA);
#pragma unroll 1
            for (int s0 = 0; s0 < nc; s0 += 8) {
              uint2 r[8];
#pragma unroll
              for (int i = 0; i < 8; i++) r[i] = ld_rlx64(g_rows[1][2] + (min(s0 + i, nc - 1) * 32 + me) * DM + t * 4);
#pragma unroll
              for (int i = 0; i < 8; i++) *(uint2*)(prm.out + (min(s0 + i, nc - 1) * 32 + me) * DM + t * 4) = r[i];
            }
          }
        }
        TR(4 * v + 2)
      }
    }
  } else if (w < 16) {
    reg_dec<48>();
    const int t = tid - 384, nu = full ? 3 : 4;
    if (full) bar_sync(KN_INIT, 384);
    {
      const int j0 = (full ? me * 3 : 96 + (me - 32) * 4) * 16;
#pragma unroll 1
      for (int i = t; i < nu * 3072; i += 128) {
        const int u = i / 3072, r = i - u * 3072;
        const bf16* src = r < 2048 ? ((r & 2) ? prm.w_up : prm.w_gate) + (size_t)((r >> 9) * 128 + ((r >> 2) & 7) * 16 + ((r >> 5) & 15)) * FF + j0 + u * 16 + (r & 1) * 8
                                   : prm.w_down + (size_t)(j0 + u * 16) * DM + (r - 2048) * 8;
        cp16(sb + K_W + i * 16, src);
      }
      asm volatile("cp.async.wait_all;" ::: "memory");
    }
    bar_arrive(KN_TAKEN, 160);
#pragma unroll 1
    while (true) {
      bar_sync(KN_CAND, 160);
      const uint4 cand = lds128(sb + K_LN + 160);
      const u64 k = (u64)cand.y << 32 | cand.x;
      const int ev = cand.z, ver = cand.w & 3, tok = key_token(k);
      const bool last = cand.w & 4;
      if (!last) {
        bar_arrive(KN_TAKEN, 160);
        FT(0)
        ffn_slice(sb, t, nu, g_rows[ver][1] + (size_t)tok * DM, ev);
      }
      if ((tok & 31) == me && (ver == 0 || last)) {
        uint8_t* dst = g_patch + (size_t)(tok >> 5) * 8192;
        if (w == 12) {
          FT(6)
          const Row x = ffn_finish(ver, ev, k, lane);
          FT(7)
          store_row(ver ? prm.out + (size_t)tok * DM : g_x2p + ev * DM, lane, x);
          if (ver == 0) store_row_img(dst, tok & 7, lane, warp_ln(x));
        } else if (w < 15 && ver == 0) {
          const uint8_t* src = g_xs[1] + (size_t)(tok >> 3) * 8192 + (t - 32) * 16;
          uint4 q[8];
#pragma unroll
          for (int i = 0; i < 8; i++) q[i] = ld_rlx128(src + i * 1024);
          if (((t - 32) >> 3) != (tok & 7)) {
#pragma unroll
            for (int i = 0; i < 8; i++) *(uint4*)(dst + (t - 32) * 16 + i * 1024) = q[i];
          }
        }
        bar_sync(KN_FFN, 128);
        if (t == 0 && ver == 0) st_release32(g_fl.patch[ev], 1);
        __syncwarp();
      }
      FT(8)
      if (last) break;
    }
  } else {
    reg_dec<24>();
    if (w == 16) {
      u64 best = 0, mask = 0;
      int sstar = 0;
      uint32_t ver = 0, ev = 0;
      auto post = [&](uint32_t cmd) {
        bar_sync(KN_TAKEN, 160);
        sts128(sb + K_LN + 160, make_uint4((uint32_t)best, (uint32_t)(best >> 32), ev, ver | cmd));
        bar_arrive(KN_CAND, 160);
      };
#pragma unroll 1
      for (int st = 0; st < NSTEP; st++) {
        u64 k = wait_keys(st < NSEG ? g_fl.key[0][st] : g_fl.key[2][st - DELTA], lane, 91);
        if (st >= NSEG) {
          if (st == NSEG) best = 0;
          u64 m = 0;
#pragma unroll 4
          for (int s2 = st == NSEG ? 0 : st - DELTA; s2 <= st - DELTA; s2++) {
            u64 k2;
            asm volatile("ld.relaxed.gpu.global.u64 %0, [%1];" : "=l"(k2) : "l"(&g_fl.key[s2 < sstar ? 1 : 2][s2][lane]) : "memory");
            if (k2 > m) m = k2;
          }
          if (st < NSTEP - 1) {
            const uint32_t hi = __reduce_max_sync(~0u, (uint32_t)(m >> 32));
            k = (u64)hi << 32 | __reduce_max_sync(~0u, (uint32_t)(m >> 32) == hi ? (uint32_t)m : 0u);
          }
        }
        const bool rec = k > best;
        if (rec) best = k;
        if (st < NSEG) {
          sstar = key_token(best) >> 5;
          if (rec && (key_token(k) & 31) == me) mask |= 1ull << st;
          sts128(sb + K_LN + 144, make_uint4(st + 1, (uint32_t)mask, (uint32_t)(mask >> 32), sstar));
        }
        if (rec) {
          ver = st < NSEG ? 0 : (key_token(k) >> 5) < sstar ? 1 : 2;
          ev = st;
          post(0);
        }
      }
      HD(6)
      post(4);
    } else if (!full) {
    } else if (w == 17) {
      FOR_UNITS {
        wait_count(&g_fl.oflag[v][sg][kb], 4, 84);
        mbar_wait(bars + (KB_EMPTY + (n & 1)) * 8, ((n >> 1) & 1) ^ 1, 83);
        TR(v)
        if (st == NSTEP - 1) { HD(v) }
        if (lane == 0) {
          fence_async_glb();
          mbar_expect_tx(bars + (KB_FULL + (n & 1)) * 8, 32768);
          bulk_g2s(sb + K_O + (n & 1) * 32768, g_O[v] + ((size_t)(sg & (OSLOTS - 1)) * 32 + kb * 4) * 8192, 32768, bars + (KB_FULL + (n & 1)) * 8);
        }
        __syncwarp();
      }
    } else if (w == 18) {
      FOR_UNITS {
        if (sg > 0) mbar_wait(bars + (KB_OK + v) * 8, (sg - 1) & 1, 90);
        bar_sync(KN_ST + (n & 1), 288);
        fence_async_smem();
        if (lane == 0) {
          bulk_s2g(g_part[v] + ((sg & 1) * 32 + me) * 8192, sb + K_ST + (n & 1) * 8192, 8192);
          asm volatile("cp.async.bulk.commit_group;" ::: "memory");
          mbar_arrive_z(bars + (KB_EMPTY + (n & 1)) * 8, 0);
          asm volatile("cp.async.bulk.wait_group.read 0;" ::: "memory");
        }
        __syncwarp();
        mbar_arrive_z(bars + (KB_ST + (n & 1)) * 8, lane);
        TR(v)
        const uint32_t tg = clk32() + GATE_R;
        if (v == (st < NSEG ? 0 : 2) && st > 0) mbar_wait(bars + KB_REL * 8, (st - 1) & 1, 93);
        wait_clock(tg);
        if (st == NSTEP - 1) { HD(2 + v) }
        mbar_arrive_z(bars + (KB_GO + v) * 8, lane);
      }
    } else {
#pragma unroll 1
      for (int st = 0; st < NSTEP; st++) {
        const int sg = st < NSEG ? st : st - DELTA;
        bar_sync(KN_REL, 160);
        const uint32_t ob = __shfl_sync(~0u, lds32(sb + K_LN + 128), 0);
        mbar_arrive_z(bars + KB_REL * 8, lane);
        if (st == NSTEP - 1) { HD(5) }
        if (lane == 0) st_release_u64(&g_fl.key[st < NSEG ? 0 : 2][sg][me], (u64)ob << 32 | (uint32_t)~(sg * 32 + me));
        __syncwarp();
        TR(0)
      }
    }
  }
}
#undef TRC

bool g_ready;

}

extern "C" void kernel_launch(void* const* d_in, const int* in_sizes, int n_in, void* d_out, int out_size) {
  (void)in_sizes; (void)n_in; (void)out_size;
  const bf16* x0 = (const bf16*)d_in[0];
  const bf16* mem0 = (const bf16*)d_in[1];
  const bf16* Wq = (const bf16*)d_in[2];
  const bf16* Wk = (const bf16*)d_in[3];
  const bf16* Wv = (const bf16*)d_in[4];
  const bf16* Wo = (const bf16*)d_in[5];
  if (!g_ready) {
    cudaFuncSetAttribute(worker_kernel, cudaFuncAttributeMaxDynamicSharedMemorySize, K_SMEM);
    cudaFuncSetAttribute(chain_kernel, cudaFuncAttributeMaxDynamicSharedMemorySize, C_SMEM);
    g_ready = true;
  }
  cudaStream_t st = cudaStreamPerThread;
  prep_kernel<<<NTOK / 8, 256, 0, st>>>(x0, Wq, Wk, Wv, Wo);
  chain_kernel<<<96, 512, C_SMEM, st>>>(Wq, Wk, Wv, Wo, mem0);
  cudaLaunchAttribute pdl[1];
  pdl[0].id = cudaLaunchAttributeProgrammaticStreamSerialization;
  pdl[0].val.programmaticStreamSerializationAllowed = 1;
  WorkerParams wp;
  wp.x0 = x0; wp.Wo = Wo; wp.w_r = (const bf16*)d_in[8]; wp.w_gate = (const bf16*)d_in[9]; wp.w_up = (const bf16*)d_in[10];
  wp.w_down = (const bf16*)d_in[11]; wp.out = (bf16*)d_out;
  cudaLaunchConfig_t cfg = {};
  cfg.gridDim = dim3(NWORK); cfg.blockDim = dim3(640); cfg.dynamicSmemBytes = K_SMEM; cfg.stream = st;
  cfg.attrs = pdl; cfg.numAttrs = 1;
  cudaLaunchKernelEx(&cfg, worker_kernel, wp);
}
```

```cpp
#include <cuda_runtime.h>
#include <cuda_bf16.h>
#include <stdint.h>

namespace {

typedef __nv_bfloat16 bf16;
typedef unsigned long long u64;

constexpr int NTOK = 2048, DM = 512, HD = 4096, NSEG = 64, FF = 1792;
#define DELTA 4
constexpr int NSTEP = NSEG + DELTA;
#define WLAG 1
constexpr int WD = DELTA + WLAG, WSTEP = NSEG + WD;
constexpr int SPIN_LIMIT = 40000;
constexpr int MBAR_LIMIT = 20000;
constexpr int NWORK = 36;
constexpr int OSLOTS = 8;
#define SLP_C 100
#define SLP_K 200
#define WEXP 0

__device__ __align__(1024) uint8_t g_xs[2][NSEG * 32768];
__device__ __align__(1024) uint8_t g_patch[NSEG * 8192];
__device__ __align__(1024) uint8_t g_O[OSLOTS][3][32 * 8192];
__device__ __align__(1024) uint8_t g_part[3][2 * 32 * 8192];
__device__ __align__(1024) bf16 g_rows[NTOK][3][3][DM];
__device__ __align__(1024) bf16 g_x2p[NSEG * DM];
struct Flags {
  uint32_t pol[96];
  uint32_t stamp[96];
  uint32_t oflag[3][NSEG][8];
  uint32_t ffncnt[WSTEP][8];
  uint32_t patch[NSEG][8];
  u64 key[3][NSEG][32];
  float upd[WSTEP][DM];
};
struct Exchange { uint32_t M[4 * 16384], P[96 * 4096]; Flags fl; };
__device__ __align__(65536) Exchange g_ex;
#define g_M g_ex.M
#define g_P g_ex.P
#define g_fl g_ex.fl
#define TR(e)
#define TRV(e, v)
#define TG(i)
#define HD(e)
#define TRDUMP
#define TREXTRA 0

#define STAT(e, v)
#define STATC(n)
#define STATDUMP
__device__ __forceinline__ uint32_t smem_u32(const void* p) { return (uint32_t)__cvta_generic_to_shared(p); }
__device__ __forceinline__ uint32_t pack_bf16(float lo, float hi) {
  uint32_t r;
  asm("cvt.rn.bf16x2.f32 %0, %1, %2;" : "=r"(r) : "f"(hi), "f"(lo));
  return r;
}
__device__ __forceinline__ float bf_lo(uint32_t v) { return __uint_as_float(v << 16); }
__device__ __forceinline__ float bf_hi(uint32_t v) { return __uint_as_float(v & 0xffff0000u); }
__device__ __forceinline__ float ex2_fast(float x) { float y; asm("ex2.approx.ftz.f32 %0, %1;" : "=f"(y) : "f"(x)); return y; }
__device__ __forceinline__ float round_bf16(float x) { return __bfloat162float(__float2bfloat16_rn(x)); }
__device__ __forceinline__ uint32_t clk32() { uint32_t t; asm volatile("mov.u32 %0, %%clock;" : "=r"(t) :: "memory"); return t; }

__device__ __forceinline__ void mma16816(float (&d)[4], uint32_t a0, uint32_t a1, uint32_t a2, uint32_t a3,
                                         uint32_t b0, uint32_t b1) {
  asm("mma.sync.aligned.m16n8k16.row.col.f32.bf16.bf16.f32 {%0,%1,%2,%3}, {%4,%5,%6,%7}, {%8,%9}, {%0,%1,%2,%3};"
      : "+f"(d[0]), "+f"(d[1]), "+f"(d[2]), "+f"(d[3])
      : "r"(a0), "r"(a1), "r"(a2), "r"(a3), "r"(b0), "r"(b1));
}
__device__ __forceinline__ void ldsm4t(uint32_t (&r)[4], uint32_t addr) {
  asm volatile("ldmatrix.sync.aligned.m8n8.x4.trans.shared.b16 {%0,%1,%2,%3}, [%4];"
               : "=r"(r[0]), "=r"(r[1]), "=r"(r[2]), "=r"(r[3]) : "r"(addr) : "memory");
}
__device__ __forceinline__ void stsm4(uint32_t addr, uint32_t a, uint32_t b, uint32_t c, uint32_t d) {
  asm volatile("stmatrix.sync.aligned.m8n8.x4.shared.b16 [%0], {%1,%2,%3,%4};" ::"r"(addr), "r"(a), "r"(b), "r"(c), "r"(d) : "memory");
}
__device__ __forceinline__ void stsm4t(uint32_t addr, uint32_t a, uint32_t b, uint32_t c, uint32_t d) {
  asm volatile("stmatrix.sync.aligned.m8n8.x4.trans.shared.b16 [%0], {%1,%2,%3,%4};" ::"r"(addr), "r"(a), "r"(b), "r"(c), "r"(d) : "memory");
}
__device__ __forceinline__ uint4 lds128(uint32_t a) {
  uint4 v; asm volatile("ld.shared.v4.b32 {%0,%1,%2,%3}, [%4];" : "=r"(v.x), "=r"(v.y), "=r"(v.z), "=r"(v.w) : "r"(a) : "memory"); return v;
}
__device__ __forceinline__ uint32_t lds32(uint32_t a) { uint32_t v; asm volatile("ld.shared.b32 %0, [%1];" : "=r"(v) : "r"(a) : "memory"); return v; }
__device__ __forceinline__ void sts32(uint32_t a, uint32_t x) { asm volatile("st.shared.b32 [%0], %1;" ::"r"(a), "r"(x) : "memory"); }
__device__ __forceinline__ void sts128(uint32_t a, uint4 v) {
  asm volatile("st.shared.v4.b32 [%0], {%1,%2,%3,%4};" ::"r"(a), "r"(v.x), "r"(v.y), "r"(v.z), "r"(v.w) : "memory");
}
__device__ __forceinline__ void cp16(uint32_t dst, const void* src) {
  asm volatile("cp.async.cg.shared.global [%0], [%1], 16;" ::"r"(dst), "l"(src) : "memory");
}
__device__ __forceinline__ void mbar_init(uint32_t mbar, uint32_t cnt) {
  asm volatile("mbarrier.init.shared.b64 [%0], %1;" ::"r"(mbar), "r"(cnt) : "memory");
}
__device__ __forceinline__ void mbar_expect_tx(uint32_t mbar, uint32_t bytes) {
  asm volatile("mbarrier.arrive.expect_tx.shared.b64 _, [%0], %1;" ::"r"(mbar), "r"(bytes) : "memory");
}
__device__ __forceinline__ void mbar_arrive_z(uint32_t mbar, uint32_t z) {
  asm volatile("{ .reg .pred p; setp.eq.u32 p, %1, 0; @p mbarrier.arrive.shared.b64 _, [%0]; }" ::"r"(mbar), "r"(z) : "memory");
}
__device__ __forceinline__ void mbar_expect_tx_z(uint32_t mbar, uint32_t bytes, uint32_t z) {
  asm volatile("{ .reg .pred p; setp.eq.u32 p, %2, 0; @p mbarrier.arrive.expect_tx.shared.b64 _, [%0], %1; }" ::"r"(mbar), "r"(bytes), "r"(z) : "memory");
}
__device__ __forceinline__ void mbar_arrive_remote_z(uint32_t mbar, uint32_t z) {
  asm volatile("{ .reg .pred p; setp.eq.u32 p, %1, 0; @p mbarrier.arrive.shared::cluster.b64 _, [%0]; }" ::"r"(mbar), "r"(z) : "memory");
}
__device__ __forceinline__ void fail(int) { __trap(); }
__device__ __forceinline__ void give_up(int it, int limit, int code) { if (it > limit) fail(code); }
__device__ __forceinline__ void mbar_wait(uint32_t mbar, uint32_t par, int code) {
  asm volatile("{ .reg .pred p; .reg .b32 n; mov.b32 n, %2;\n"
               "W: mbarrier.try_wait.parity.shared::cta.b64 p, [%0], %1; @p bra D;\n"
               "add.s32 n, n, -1; setp.eq.s32 p, n, 0; @p trap; bra W;\n"
               "D: }" ::"r"(mbar), "r"(par), "n"(MBAR_LIMIT) : "memory");
}
__device__ __forceinline__ void bulk_g2s(uint32_t dst, const void* src, uint32_t bytes, uint32_t mbar) {
  asm volatile("cp.async.bulk.shared::cluster.global.mbarrier::complete_tx::bytes [%0], [%1], %2, [%3];"
               ::"r"(dst), "l"(src), "r"(bytes), "r"(mbar) : "memory");
}
__device__ __forceinline__ void bulk_s2r(uint32_t dst, uint32_t src, uint32_t bytes, uint32_t mbar) {
  asm volatile("cp.async.bulk.shared::cluster.shared::cta.mbarrier::complete_tx::bytes [%0], [%1], %2, [%3];"
               ::"r"(dst), "r"(src), "r"(bytes), "r"(mbar) : "memory");
}
__device__ __forceinline__ void bulk_s2g(void* dst, uint32_t src, uint32_t bytes) {
  asm volatile("cp.async.bulk.global.shared::cta.bulk_group [%0], [%1], %2;" ::"l"(dst), "r"(src), "r"(bytes) : "memory");
}
__device__ __forceinline__ void fence_async_smem() { asm volatile("fence.proxy.async.shared::cta;" ::: "memory"); }
__device__ __forceinline__ void fence_async_glb() { asm volatile("fence.proxy.async.global;" ::: "memory"); }
__device__ __forceinline__ void bar_sync(int id, int n) { asm volatile("bar.sync %0, %1;" ::"r"(id), "r"(n) : "memory"); }
__device__ __forceinline__ void bar_arrive(int id, int n) { asm volatile("bar.arrive %0, %1;" ::"r"(id), "r"(n) : "memory"); }
__device__ __forceinline__ void cluster_sync() { asm volatile("barrier.cluster.arrive.release; barrier.cluster.wait.acquire;" ::: "memory"); }
__device__ __forceinline__ uint32_t mapa_u32(uint32_t a, uint32_t r) {
  uint32_t o;
  asm("mapa.shared::cluster.u32 %0, %1, %2;" : "=r"(o) : "r"(a), "r"(r));
  return o;
}
template <int OFF>
__device__ __forceinline__ void st_async32(uint32_t a, uint32_t x, uint32_t mbar) {
  asm volatile("st.async.weak.shared::cluster.mbarrier::complete_tx::bytes.b32 [%0 + %3], %1, [%2];" ::"r"(a), "r"(x), "r"(mbar), "n"(OFF) : "memory");
}
__device__ __forceinline__ uint4 ld_rlx128(const void* p) {
  uint4 v;
  asm volatile("ld.relaxed.gpu.global.v4.u32 {%0,%1,%2,%3}, [%4];" : "=r"(v.x), "=r"(v.y), "=r"(v.z), "=r"(v.w) : "l"(p) : "memory");
  return v;
}
__device__ __forceinline__ uint2 ld_rlx64(const void* p) {
  uint2 v; asm volatile("ld.relaxed.gpu.global.v2.u32 {%0,%1}, [%2];" : "=r"(v.x), "=r"(v.y) : "l"(p) : "memory"); return v;
}
__device__ __forceinline__ uint32_t ld_rlx32(const void* p) {
  uint32_t v; asm volatile("ld.relaxed.gpu.global.u32 %0, [%1];" : "=r"(v) : "l"(p) : "memory"); return v;
}
__device__ __forceinline__ void st_rlx32(void* p, uint32_t a) { asm volatile("st.relaxed.gpu.global.u32 [%0], %1;" ::"l"(p), "r"(a) : "memory"); }
__device__ __forceinline__ void red_release(uint32_t* p) { asm volatile("red.release.gpu.global.add.u32 [%0], 1;" ::"l"(p) : "memory"); }
__device__ __forceinline__ void st_release32(void* p, uint32_t a) { asm volatile("st.release.gpu.global.u32 [%0], %1;" ::"l"(p), "r"(a) : "memory"); }
__device__ __forceinline__ void st_release_u64(void* p, u64 a) { asm volatile("st.release.gpu.global.u64 [%0], %1;" ::"l"(p), "l"(a) : "memory"); }
__device__ __forceinline__ void wait_count(const uint32_t* p, uint32_t val, int code) {
  int it = 0;
  while (ld_rlx32(p) < val) {
    give_up(++it, SPIN_LIMIT, code);
    __nanosleep(SLP_C);
  }
}
__device__ __forceinline__ u64 wait_keys(const u64* keys, int lane, int code) {
  u64 k;
  int it = 0;
  while (true) {
    asm volatile("ld.relaxed.gpu.global.u64 %0, [%1];" : "=l"(k) : "l"(keys + lane) : "memory");
    if (__all_sync(~0u, k != 0)) break;
    give_up(++it, SPIN_LIMIT, code);
    __nanosleep(SLP_K);
  }
  const uint32_t hi = __reduce_max_sync(~0u, (uint32_t)(k >> 32));
  const uint32_t lo = __reduce_max_sync(~0u, (uint32_t)(k >> 32) == hi ? (uint32_t)k : 0u);
  return (u64)hi << 32 | lo;
}
__device__ __forceinline__ int key_token(u64 k) { return (int)(~(uint32_t)k) & (NTOK - 1); }
__device__ __forceinline__ float key_score(u64 k) {
  const uint32_t ob = (uint32_t)(k >> 32);
  return __uint_as_float((ob & 0x80000000u) ? (ob & 0x7fffffffu) : ~ob);
}

__device__ __forceinline__ uint64_t mk_desc(uint32_t saddr, uint32_t lbo, uint32_t sbo, uint32_t sw) {
  return (uint64_t)((saddr & 0x3FFFF) >> 4) | (uint64_t)(lbo >> 4) << 16 | (uint64_t)(sbo >> 4) << 32 | (uint64_t)sw << 62;
}
template <int N> __device__ __forceinline__ void reg_inc() { asm volatile("setmaxnreg.inc.sync.aligned.u32 %0;" ::"n"(N)); }
template <int N> __device__ __forceinline__ void reg_dec() { asm volatile("setmaxnreg.dec.sync.aligned.u32 %0;" ::"n"(N)); }
__device__ __forceinline__ void wg_fence() { asm volatile("wgmma.fence.sync.aligned;" ::: "memory"); }
__device__ __forceinline__ void wg_commit() { asm volatile("wgmma.commit_group.sync.aligned;" ::: "memory"); }
template <int N> __device__ __forceinline__ void wg_wait() { asm volatile("wgmma.wait_group.sync.aligned %0;" ::"n"(N) : "memory"); }
template <int N> __device__ __forceinline__ void acc_fence(float (&d)[N]) {
#pragma unroll
  for (int i = 0; i < N; i++) asm volatile("" : "+f"(d[i]) :: "memory");
}
#define O4(d, i) "+f"(d[i]), "+f"(d[i + 1]), "+f"(d[i + 2]), "+f"(d[i + 3])
template <int TB, int ACC>
__device__ __forceinline__ void wg_rs8(float (&d)[4], const uint32_t (&a)[4], uint64_t db) {
  asm volatile("wgmma.mma_async.sync.aligned.m64n8k16.f32.bf16.bf16 {%0,%1,%2,%3}, {%4,%5,%6,%7}, %8, %9, 1, 1, %10;"
               : O4(d, 0) : "r"(a[0]), "r"(a[1]), "r"(a[2]), "r"(a[3]), "l"(db), "n"(ACC), "n"(TB));
}
template <int TB, int ACC>
__device__ __forceinline__ void wg_rs24(float (&d)[12], const uint32_t (&a)[4], uint64_t db) {
  asm volatile("wgmma.mma_async.sync.aligned.m64n24k16.f32.bf16.bf16 {%0,%1,%2,%3,%4,%5,%6,%7,%8,%9,%10,%11}, {%12,%13,%14,%15}, %16, %17, 1, 1, %18;"
               : O4(d, 0), O4(d, 4), O4(d, 8) : "r"(a[0]), "r"(a[1]), "r"(a[2]), "r"(a[3]), "l"(db), "n"(ACC), "n"(TB));
}
template <int TB, int ACC>
__device__ __forceinline__ void wg_rs32(float (&d)[16], const uint32_t (&a)[4], uint64_t db) {
  asm volatile("wgmma.mma_async.sync.aligned.m64n32k16.f32.bf16.bf16 {%0,%1,%2,%3,%4,%5,%6,%7,%8,%9,%10,%11,%12,%13,%14,%15}, {%16,%17,%18,%19}, %20, %21, 1, 1, %22;"
               : O4(d, 0), O4(d, 4), O4(d, 8), O4(d, 12) : "r"(a[0]), "r"(a[1]), "r"(a[2]), "r"(a[3]), "l"(db), "n"(ACC), "n"(TB));
}
template <int ACC>
__device__ __forceinline__ void wg_rs64(float (&d)[32], uint32_t a0, uint32_t a1, uint32_t a2, uint32_t a3, uint64_t db) {
  asm volatile("wgmma.mma_async.sync.aligned.m64n64k16.f32.bf16.bf16 {%0,%1,%2,%3,%4,%5,%6,%7,%8,%9,%10,%11,%12,%13,%14,%15,"
               "%16,%17,%18,%19,%20,%21,%22,%23,%24,%25,%26,%27,%28,%29,%30,%31}, {%32,%33,%34,%35}, %36, %37, 1, 1, 0;"
               : O4(d, 0), O4(d, 4), O4(d, 8), O4(d, 12), O4(d, 16), O4(d, 20), O4(d, 24), O4(d, 28)
               : "r"(a0), "r"(a1), "r"(a2), "r"(a3), "l"(db), "n"(ACC));
}
template <int ACC>
__device__ __forceinline__ void wg_ss24(float (&d)[12], uint64_t da, uint64_t db) {
  asm volatile("wgmma.mma_async.sync.aligned.m64n24k16.f32.bf16.bf16 {%0,%1,%2,%3,%4,%5,%6,%7,%8,%9,%10,%11}, %12, %13, %14, 1, 1, 1, 0;"
               : O4(d, 0), O4(d, 4), O4(d, 8) : "l"(da), "l"(db), "n"(ACC));
}
template <int ACC>
__device__ __forceinline__ void wg_rs40(float (&d)[20], const uint32_t (&a)[4], uint64_t db) {
  asm volatile("wgmma.mma_async.sync.aligned.m64n40k16.f32.bf16.bf16 {%0,%1,%2,%3,%4,%5,%6,%7,%8,%9,%10,%11,%12,%13,%14,%15,%16,%17,%18,%19}, {%20,%21,%22,%23}, %24, %25, 1, 1, 1;"
               : O4(d, 0), O4(d, 4), O4(d, 8), O4(d, 12), O4(d, 16) : "r"(a[0]), "r"(a[1]), "r"(a[2]), "r"(a[3]), "l"(db), "n"(ACC));
}

struct Row { uint32_t w[8]; };
__device__ __forceinline__ uint32_t add_bf16x2(uint32_t a, uint32_t b) {
  uint32_t d; asm("add.rn.bf16x2 %0, %1, %2;" : "=r"(d) : "r"(a), "r"(b)); return d;
}
__device__ __forceinline__ Row warp_ln(const Row& r, float& extra) {
  float x[16];
#pragma unroll
  for (int i = 0; i < 8; i++) { x[2 * i] = bf_lo(r.w[i]); x[2 * i + 1] = bf_hi(r.w[i]); }
  float m = (((x[0] + x[1]) + (x[2] + x[3])) + ((x[4] + x[5]) + (x[6] + x[7]))) + (((x[8] + x[9]) + (x[10] + x[11])) + ((x[12] + x[13]) + (x[14] + x[15])));
  m *= (1.f / 16);
  float v0 = 0.f, v1 = 0.f;
#pragma unroll
  for (int i = 0; i < 16; i += 2) { const float d0 = x[i] - m, d1 = x[i + 1] - m; v0 = fmaf(d0, d0, v0); v1 = fmaf(d1, d1, v1); }
  float v = v0 + v1;
#pragma unroll
  for (int o = 1; o <= 16; o <<= 1) {
    const float mo = __shfl_xor_sync(~0u, m, o), vo = __shfl_xor_sync(~0u, v, o);
    extra += __shfl_xor_sync(~0u, extra, o);
    const float d = mo - m;
    v = fmaf(d * d, 8.f * o, v + vo);
    m = 0.5f * (m + mo);
  }
  const float var = fmaf(v, 1.f / DM, 1e-5f);
  float rs = rsqrtf(var);
  rs = rs * fmaf(-0.5f * var * rs, rs, 1.5f);
  Row y;
#pragma unroll
  for (int i = 0; i < 8; i++) y.w[i] = pack_bf16((x[2 * i] - m) * rs, (x[2 * i + 1] - m) * rs);
  return y;
}
__device__ __forceinline__ Row warp_ln(const Row& r) { float e = 0.f; return warp_ln(r, e); }
__device__ __forceinline__ Row load_row(const bf16* p, int lane) {
  Row r;
#pragma unroll
  for (int q = 0; q < 4; q++) { const uint2 v = ld_rlx64(p + lane * 4 + q * 128); r.w[2 * q] = v.x; r.w[2 * q + 1] = v.y; }
  return r;
}
__device__ __forceinline__ void store_row(bf16* p, int lane, const Row& r) {
#pragma unroll
  for (int q = 0; q < 4; q++) *(uint2*)(p + lane * 4 + q * 128) = make_uint2(r.w[2 * q], r.w[2 * q + 1]);
}
template <int KB>
__device__ __forceinline__ void store_row_img(uint8_t* img, int rr, int lane, const Row& r) {
  uint8_t* p = img + (lane >> 4) * KB + rr * 128 + ((((lane & 15) >> 1) ^ (rr & 7)) << 4) + (lane & 1) * 8;
#pragma unroll
  for (int q = 0; q < 4; q++) *(uint2*)(p + q * 2 * KB) = make_uint2(r.w[2 * q], r.w[2 * q + 1]);
}

__global__ void __launch_bounds__(256) prep_kernel(const bf16* __restrict__ x0, const bf16* Wq, const bf16* Wk, const bf16* Wv, const bf16* Wo) {
  const int lane = threadIdx.x & 31, row = blockIdx.x * 8 + (threadIdx.x >> 5);
  const Row r = load_row(x0 + (size_t)row * DM, lane);
  const int gt = blockIdx.x * 256 + threadIdx.x, nt = gridDim.x * 256;
  asm volatile("prefetch.global.L2 [%0];" ::"l"((gt & 1 ? Wk : Wq) + (gt >> 1) * 64));
  asm volatile("prefetch.global.L2 [%0];" ::"l"((gt & 1 ? Wo : Wv) + (gt >> 1) * 64));
  uint4* M = (uint4*)g_M;
  for (int i = gt; i < 4 * 16384 / 4; i += nt) M[i] = make_uint4(~0u, ~0u, ~0u, ~0u);
  uint4* P = (uint4*)g_P;
  for (int i = gt; i < 96 * 4096 / 4; i += nt) P[i] = make_uint4(0, 0, 0, 0);
  if (gt < 16384) ((uint4*)(g_part[1] + 32 * 8192))[gt] = make_uint4(0, 0, 0, 0);
  uint4* F = (uint4*)&g_fl;
  for (int i = gt; i < (int)(sizeof(Flags) / 16); i += nt) F[i] = make_uint4(0, 0, 0, 0);
  store_row_img<4096>(g_xs[0] + (size_t)(row >> 5) * 32768, row & 31, lane, warp_ln(r));
}

constexpr int W_STRIDE = 272;
constexpr int C_WO = 0;
constexpr int C_X = 49152;
constexpr int C_M = C_X + 9 * 8192;
constexpr int C_Q = C_M + 24576;
constexpr int C_K = C_Q + 10240, C_V = C_K + 10240;
constexpr int C_SA = C_V + 10240, C_SB = C_SA + 8192, C_SP = C_SB + 8192;
constexpr int C_O = C_SP + 2048;
constexpr int C_OT = C_O + 6144;
constexpr int C_BAR = C_OT + 16384;
constexpr int C_SMEM = C_BAR + 256 + (TREXTRA > 9000 ? TREXTRA : 1024 + TREXTRA);
static_assert(C_X + 512 * W_STRIDE <= C_OT, "staging");
enum { B_M0 = 0, B_M1, B_M2, B_R, B_X = B_R + 4, B_O, B_T, B_F, B_XL, B_XL3, B_P1, B_P2, B_P3, B_OT, B_XF, B_I, B_NUM };
constexpr int C_INFO = C_BAR + 176, C_POL = C_BAR + 208;
enum { NB_ALL = 0, NB_M0, NB_PV, NB_W0, NB_TA, NB_X1, NB_M1, NB_M2, NB_RD, NB_XB };
constexpr float SCALE_LOG2E = 0.08838834764831845f * 1.4426950408889634f;
#define N0STEPS 9
#define N2STEPS 11
#define FGATE 1
constexpr int K3 = 32 - N0STEPS - N2STEPS;
static_assert(K3 % 4 == 0, "the rows of layer 1 are refilled in two parts");
#define BGATE 0
#define IGRP 0
#define SHIPLATE 7
#define SHIP 1024
#define GATE_P 2300
#define GATE_W 200
#define EXPF 0
#define GATE_G 200
#define GATE_M 3400
#define HOLE0 24
#define HOLE1 32
#define HOLE2 32
__device__ __forceinline__ uint32_t gtime() { uint32_t t; asm volatile("mov.u32 %0, %%globaltimer_lo;" : "=r"(t) :: "memory"); return t; }
__device__ __forceinline__ void wait_clock(uint32_t t) {
  asm volatile("{ .reg .pred p; .reg .b32 c; .reg .b64 cc;\nL: mov.u64 cc, %%clock64; cvt.u32.u64 c, cc; sub.u32 c, c, %0; setp.lt.s32 p, c, 0; @p bra L; }" ::"r"(t) : "memory");
}
__device__ __forceinline__ bool bar_or(int id, int n, uint32_t v) {
  uint32_t r;
  asm volatile("{ .reg .pred p, q; setp.ne.u32 p, %1, 0; bar.red.or.pred q, %2, %3, p; vote.sync.any.pred q, q, 0xffffffff; selp.u32 %0, 1, 0, q; }"
               : "=r"(r) : "r"(v), "r"(id), "r"(n) : "memory");
  return r;
}
__device__ __forceinline__ void bar_sync_z(int id, int n, uint32_t z) {
  asm volatile("{ .reg .pred p; setp.eq.u32 p, %2, 0; @p bar.sync %0, %1; }" ::"r"(id), "r"(n), "r"(z) : "memory");
}

__device__ __forceinline__ uint32_t probe_polarity(uint32_t* p, int lane) {
  uint32_t best[2] = {~0u, ~0u};
#pragma unroll 1
  for (int rep = 0; rep < 3; rep++) {
#pragma unroll
    for (int pg = 0; pg < 2; pg++) {
      uint32_t t0, t1, v = 0;
      asm volatile("mov.u32 %0, %%clock;" : "=r"(t0) :: "memory");
      asm volatile("{ .reg .pred p; setp.eq.u32 p, %2, 0; @p atom.relaxed.gpu.global.add.u32 %0, [%1], 0; }" : "+r"(v) : "l"(p + pg * 1024), "r"(lane) : "memory");
      asm volatile("{ .reg .pred p; setp.ne.u32 p, %1, 0x13572468; mov.u32 %0, 0; @p mov.u32 %0, %%clock; }" : "=r"(t1) : "r"(v) : "memory");
      if (rep > 0) best[pg] = min(best[pg], t1 - t0);
    }
  }
  return __shfl_sync(~0u, best[1] < best[0] ? 1u : 0u, 0);
}
__device__ __forceinline__ uint32_t ppage(uint32_t lp, uint32_t pol) { return lp ? 3 - pol : pol; }
__device__ __forceinline__ uint32_t and_x(uint32_t a, uint32_t b, uint32_t m) {
  uint32_t d; asm("lop3.b32 %0, %1, %2, %3, 0x42;" : "=r"(d) : "r"(a), "r"(b), "r"(m)); return d;
}
__device__ __forceinline__ uint32_t and3(uint32_t a, uint32_t b, uint32_t c) {
  uint32_t d; asm("lop3.b32 %0, %1, %2, %3, 0x80;" : "=r"(d) : "r"(a), "r"(b), "r"(c)); return d;
}

template <int N> struct IC { static constexpr int value = N; };
template <class F> __device__ __forceinline__ void static_for2(F f) { f(IC<0>()); f(IC<1>()); }
template <class F> __device__ __forceinline__ void static_for3(F f) { f(IC<0>()); f(IC<1>()); f(IC<2>()); }
__device__ __forceinline__ void load_wfrags(uint32_t (&wA)[32][4], uint32_t stage, int w, int lane) {
  const int mi = lane >> 3, r = lane & 7;
#pragma unroll
  for (int ks = 0; ks < 32; ks++) ldsm4t(wA[ks], stage + (ks * 16 + (mi >> 1) * 8 + r) * W_STRIDE + (w * 16 + (mi & 1) * 8) * 2);
}
template <int K0, int K1>
__device__ __forceinline__ void tok_seq(float (&d)[16], const uint32_t (&wA)[32][4], uint64_t desc, uint32_t wave) {
#pragma unroll
  for (int k = K0; k < K1; k++) {
    const int ks = k & 31;
    constexpr int HM0 = 1, HM1 = 2, HM2 = 4;
    const int hm = (k == HOLE0 ? HM0 : 0) | (k == HOLE1 ? HM1 : 0) | (k == HOLE2 ? HM2 : 0);
    if (hm) bar_sync_z(NB_RD, 384, ((hm >> wave) & 1) ^ 1);
    if (ks == 0) wg_rs32<0, 0>(d, wA[ks], desc);
    else wg_rs32<0, 1>(d, wA[ks], desc + (ks >> 2) * 256 + (ks & 3) * 2);
  }
}
template <int K0, int K1>
__device__ __forceinline__ void mem_part(float (&d)[12], const uint32_t (&wA)[32][4], uint64_t desc) {
#pragma unroll
  for (int ks = K0; ks < K1; ks++) {
    if (ks == 0) wg_rs24<1, 0>(d, wA[ks], desc);
    else wg_rs24<1, 1>(d, wA[ks], desc + ks * 48);
  }
}
__device__ __forceinline__ void out_tile(float (&d)[12], uint64_t da, uint64_t db) {
#pragma unroll
  for (int i = 0; i < 8; i++) { if (i == 0) wg_ss24<0>(d, da, db); else wg_ss24<1>(d, da + i * 128, db + (i >> 1) * 32 + (i & 1) * 2); }
}
__device__ __forceinline__ void tok_pack(uint32_t (&p)[8], const float (&d)[16]) {
#pragma unroll
  for (int i = 0; i < 8; i++) p[i] = pack_bf16(d[2 * i], d[2 * i + 1]);
}
__device__ __forceinline__ void tok_store(uint32_t dst, const uint32_t (&p)[8]) {
  stsm4(dst, p[0], p[1], p[2], p[3]);
  stsm4(dst + 4096, p[4], p[5], p[6], p[7]);
}
template <class T> __device__ __forceinline__ T keep(T v) { asm volatile("" : "+r"(v)); return v; }
__device__ __forceinline__ uint32_t pin(uint32_t v) { return __shfl_sync(~0u, v, threadIdx.x & 31); }

#define TRC blockIdx.x
#define TRS (C_BAR + 256)
__device__ __forceinline__ void chain_proj(const uint32_t sb, const int w, const int lane_, const uint32_t rank) {
  uint32_t wA[32][4];
  load_wfrags(wA, sb + C_X, w, lane_);
  bar_sync(NB_ALL, 512);
  bar_sync(NB_ALL, 512);
  cluster_sync();
  const int lane = pin(lane_);
  const uint32_t bars = sb + C_BAR;
  const uint32_t quad = pin(sb + (lane_ >> 4) * 2048 + (lane_ & 15) * 16);
  const uint32_t own = C_Q + rank * 10240;
  const uint64_t dX1 = mk_desc(sb + C_X, 16, 1024, 1), dX2 = dX1 + 2048, dX3 = dX1 + 4096;
  const uint64_t dM = mk_desc(sb + C_M, 128, 256, 0);
  const uint32_t r1 = rank == 0 ? 1 : 0, r2 = rank == 2 ? 1 : 2;
  const uint32_t xa = pin(sb + own + 8192 + w * 256 + lane_ * 4);
  const uint32_t a1x = pin(mapa_u32(xa, r1)), a2x = pin(mapa_u32(xa, r2));
  const uint32_t b1x = pin(mapa_u32(bars + B_X * 8, r1)), b2x = pin(mapa_u32(bars + B_X * 8, r2));
  const uint32_t wave = rank == 2 ? 0 : rank + 1;
  uint32_t npatch = 0;
  float a[16];
  bar_sync(NB_X1, 288);
  wg_fence();
  tok_seq<32, 32 + K3>(a, wA, dX1, 3);
  wg_commit();
  wg_wait<0>();
#pragma unroll 1
  for (int st = 0; st < NSTEP; st++) {
    uint32_t pk[8];
    bar_sync(NB_XB, 288);
    wg_fence();
    tok_seq<32 + K3, 32 + K3 + N0STEPS>(a, wA, dX1, 3);
    TR(0)
    bar_sync(NB_PV, 384);
    tok_seq<32 + K3 + N0STEPS, 64>(a, wA, dX1, 3);
    wg_commit();
    wg_wait<0>();
    acc_fence(a);
    mbar_arrive_z(bars + B_XF * 8, lane);
    tok_pack(pk, a);
    TR(1)
    bar_sync(NB_W0, 416);
    tok_store(quad + w * 256 + (rank == 0 ? own : C_SA), pk);
    __syncwarp();
    mbar_arrive_z(bars + B_P1 * 8, lane);
    wg_fence();
    tok_seq<0, 32>(a, wA, dX2, wave);
    wg_commit();
    const uint32_t info = lds32(sb + C_INFO + (st & 1) * 4);
    TR(2)
    wg_wait<0>();
    acc_fence(a);
    TR(3)
    tok_pack(pk, a);
    tok_store(quad + w * 256 + (rank == 0 ? C_SA : own), pk);
    if (rank == 2) tok_store(quad + w * 256 + C_SB, pk);
    __syncwarp();
    mbar_arrive_z(bars + B_P2 * 8, lane);
    if (__builtin_expect(info & 4, 0)) {
      float a3[4];
      mbar_wait(bars + B_XL3 * 8, npatch & 1, 32);
      npatch++;
      wg_fence();
#pragma unroll
      for (int ks = 0; ks < 32; ks++) {
        if (ks == 0) wg_rs8<0, 0>(a3, wA[ks], dX3);
        else wg_rs8<0, 1>(a3, wA[ks], dX3 + (ks >> 2) * 64 + (ks & 3) * 2);
      }
      wg_commit();
      wg_wait<0>();
      acc_fence(a3);
      const uint32_t dst = sb + (rank == 2 ? own + (info & 3) * 2048 : C_SP) + w * 256 + lane * 4;
      sts32(dst, pack_bf16(a3[0], a3[1])); sts32(dst + 128, pack_bf16(a3[2], a3[3]));
      __syncwarp();
      mbar_arrive_z(bars + B_P3 * 8, lane);
    }
    TR(4)
    wg_fence();
    tok_seq<32, 32 + K3>(a, wA, dX1, wave);
    TR(6)
    {
      float am[12];
      bar_sync(NB_M0, 384);
      mem_part<0, 10>(am, wA, dM);
      TR(7)
      bar_sync(NB_M1, 384);
      mem_part<10, 21>(am, wA, dM);
      const bool redo = bar_or(NB_M2, 384, 0);
      mem_part<21, 32>(am, wA, dM);
      wg_commit();
      wg_wait<0>();
      if (__builtin_expect(redo, 0)) {
        bar_sync(NB_M0, 384);
        wg_fence();
        mem_part<0, 32>(am, wA, dM);
        wg_commit();
        wg_wait<0>();
      }
      acc_fence(am);
      TR(8)
      const uint32_t x00 = pack_bf16(am[0], am[1]), x01 = pack_bf16(am[2], am[3]), x10 = pack_bf16(am[4], am[5]), x11 = pack_bf16(am[6], am[7]);
      uint32_t x20 = pack_bf16(am[8], am[9]), x21 = pack_bf16(am[10], am[11]);
      if (info & 4) { x20 = x10; x21 = x11; }
      st_async32<0>(a1x, rank == 0 ? x10 : x00, b1x); st_async32<0>(a2x, rank == 2 ? x10 : x20, b2x);
      st_async32<128>(a1x, rank == 0 ? x11 : x01, b1x); st_async32<128>(a2x, rank == 2 ? x11 : x21, b2x);
      sts32(xa, rank == 0 ? x00 : rank == 2 ? x20 : x10); sts32(xa + 128, rank == 0 ? x01 : rank == 2 ? x21 : x11);
      __syncwarp();
      mbar_arrive_z(bars + B_X * 8, lane);
    }
    TR(9)
  }
}

__device__ __forceinline__ void chain_mem(const uint32_t sb, const int w, const int lane_, const uint32_t rank, const int h,
                                          const bf16* __restrict__ mem0) {
  const int lane = pin(lane_);
  const int wave = rank == 2 ? 0 : rank + 1;
  const int c = w - 8, t = c * 32 + lane, b = wave * 32 + h;
  const uint32_t bars = sb + C_BAR;
  const int wi = (lane & 1) * 2 + (lane >> 4), cq = (lane >> 2) & 3;
  bar_sync(NB_ALL, 512);
#pragma unroll 1
  for (int i = c; i < 16; i += 4) {
    uint32_t r[4];
    ldsm4t(r, sb + C_OT + i * 512 + lane * 16);
    const uint32_t a = sb + C_M + (2 * i + (lane >> 4)) * 768 + (lane & 15) * 16;
    stsm4(a, r[0], r[1], r[2], r[3]); stsm4(a + 256, r[0], r[1], r[2], r[3]); stsm4(a + 512, r[0], r[1], r[2], r[3]);
  }
  fence_async_smem();
  mbar_expect_tx_z(bars + B_X * 8, 4096, t); mbar_expect_tx_z(bars + B_O * 8, 4096, t);
  bar_sync(NB_ALL, 512);
  cluster_sync();
  bar_arrive(NB_PV, 384); bar_arrive(NB_W0, 416); bar_arrive(NB_M0, 384); bar_arrive(NB_M1, 384);
  bar_arrive(NB_RD, 384);

  sts32(sb + C_POL + c * 4, probe_polarity(g_M + c * 16384 + (blockIdx.x & 31) * 32, lane));
  uint32_t pgbits, polP;
  {
    const int tl = lane / 3, u = ((tl * 3 + rank) * 4 + c) * 3 + (lane - tl * 3);
    uint32_t pol;
    int it = 0;
    do { pol = ld_rlx32(&g_fl.pol[lane < 9 && u < 96 ? u : b]); give_up(it++, SPIN_LIMIT, 40); } while (__any_sync(~0u, pol == 0));
    pgbits = __reduce_or_sync(~0u, lane < 9 ? ppage(h >> 4, (pol - 1) & 1) << (2 * lane) : 0u);
    polP = __shfl_sync(~0u, pol - 1, 9);
  }
  const int mi = lane >> 3;
  const uint32_t l16 = pin(sb + lane * 16);
  const uint32_t r1 = rank == 2 ? 0 : rank + 1, r2 = rank == 0 ? 2 : rank - 1;
  const uint32_t oa = pin(sb + C_O + rank * 2048 + (lane >> 2) * 64 + (((lane & 3) ^ (lane >> 3)) << 4));
  const uint32_t a1 = mapa_u32(oa, r1), b1 = mapa_u32(bars + B_O * 8, r1), a2 = mapa_u32(oa, r2), b2 = mapa_u32(bars + B_O * 8, r2);
  const uint64_t dWo = mk_desc(sb + C_WO, 8192, 1024, 1), dO = mk_desc(sb + C_O, 16, 2048, 2);
  const uint64_t dK = mk_desc(sb + C_K, 128, 2048, 0);
  const uint64_t dV = mk_desc(sb + C_V, 2048, 128, 0), dVm = mk_desc(sb + C_V + 8192, 0, 128, 0);
  const uint32_t qa = pin(sb + C_Q + (c ? c + 1 : mi & 1) * 2048 + (mi >> 1) * 128 + (lane & 7) * 16);
  const uint32_t dg = ((lane >> 2) < 2 * (lane & 3) ? 1 : 0) | ((lane >> 2) < 2 * (lane & 3) + 1 ? 2 : 0);
  const uint32_t msk = pin(c == 0 ? dg | dg << 4 : c == 1 ? dg << 2 | 3 << 4 : c == 2 ? dg << 4 : 0);
  uint8_t* Pw = (uint8_t*)g_P + (rank * 4 + c) * 3 * 16384 + (h & 15) * 256 + lane * 4;
  const uint8_t* Pr0 = (const uint8_t*)g_P + b * 16384 + ((lane >> 4) * 4 + (lane & 3)) * 256 + c * 64 + cq * 16 + ppage(0, polP) * 4096;
  const uint8_t* Pr1 = Pr0 + (3 - 2 * polP) * 4096;
  uint8_t* Mw = (uint8_t*)g_M + (b >> 5) * 16384 + ((lane & 2) ? 4096 : 12288) + (b & 31) * 256 + c * 64 + cq * 16 + wi * 4;
  uint32_t nretry = 0;
  const uint32_t gate_p = GATE_P + wave * GATE_W;

  (void)bar_or(NB_M2, 384, 0);
#pragma unroll 1
  for (int st = 0;; st++) {
    mbar_wait(bars + B_T * 8, st & 1, 42);
    STAT(10, clk32())
    {
      float s[20];
      {
        uint32_t q[8][4];
        if (c == 3) mbar_wait(bars + B_X * 8, st & 1, 41);
#pragma unroll
        for (int i = 0; i < 8; i++) ldsm4t(q[i], qa + i * 256);
        if (c != 3) mbar_wait(bars + B_X * 8, st & 1, 41);
        STAT(11, clk32())
        fence_async_smem();
        TR(0)
        wg_fence();
#pragma unroll
        for (int i = 0; i < 8; i++) { if (i == 0) wg_rs40<0>(s, q[i], dK); else wg_rs40<1>(s, q[i], dK + i * 16); }
        wg_commit();
        wg_wait<0>();
        acc_fence(s);
      }
      TR(1)
      const bool w0 = c == 0;
      float z[10] = {s[16], s[17], s[0], s[1], w0 ? s[18] : s[4], w0 ? s[19] : s[5], w0 ? s[2] : s[8], w0 ? s[3] : s[9], w0 ? s[6] : s[12], w0 ? s[7] : s[13]};
      if (msk & 1) z[2] = -INFINITY;
      if (msk & 2) z[3] = -INFINITY;
      if (msk & 4) z[6] = -INFINITY;
      if (msk & 8) z[7] = -INFINITY;
      if (msk & 16) z[8] = -INFINITY;
      if (msk & 32) z[9] = -INFINITY;
      float m0 = fmaxf(fmaxf(z[0], z[1]), fmaxf(z[2], z[3])), m1 = fmaxf(fmaxf(fmaxf(z[4], z[5]), fmaxf(z[6], z[7])), fmaxf(z[8], z[9]));
      m0 = fmaxf(m0, __shfl_xor_sync(~0u, m0, 1)); m1 = fmaxf(m1, __shfl_xor_sync(~0u, m1, 1));
      m0 = fmaxf(m0, __shfl_xor_sync(~0u, m0, 2)); m1 = fmaxf(m1, __shfl_xor_sync(~0u, m1, 2));
      if (!w0) m0 = m1 = fmaxf(m0, m1);
      m0 *= -SCALE_LOG2E; m1 *= -SCALE_LOG2E;
      uint32_t p[5];
#pragma unroll
      for (int k = 0; k < 5; k++) {
        z[2 * k] = ex2_fast(fmaf(z[2 * k], SCALE_LOG2E, k < 2 ? m0 : m1)); z[2 * k + 1] = ex2_fast(fmaf(z[2 * k + 1], SCALE_LOG2E, k < 2 ? m0 : m1));
        p[k] = pack_bf16(z[2 * k], z[2 * k + 1]);
      }
      const uint32_t p2 = w0 ? 0 : p[2], p3 = w0 ? 0 : p[3], p4 = w0 ? 0 : p[4];
      float oA[32], oB[32];
      wg_fence();
      wg_rs64<0>(oA, p[0], p[2], 0, 0, dVm); wg_rs64<1>(oA, p[1], p[3], p2, p[4], dV); wg_rs64<1>(oA, p3, 0, p4, 0, dV + 256);
      wg_commit();
      wg_rs64<0>(oB, p[0], p[2], 0, 0, dVm + 64); wg_rs64<1>(oB, p[1], p[3], p2, p[4], dV + 64); wg_rs64<1>(oB, p3, 0, p4, 0, dV + 320);
      wg_commit();
      float l0 = (z[0] + z[1]) + (z[2] + z[3]), l1 = ((z[4] + z[5]) + (z[6] + z[7])) + (z[8] + z[9]);
      if (!w0) l0 += l1;
      l0 += __shfl_xor_sync(~0u, l0, 1); l1 += __shfl_xor_sync(~0u, l1, 1);
      l0 += __shfl_xor_sync(~0u, l0, 2); l1 += __shfl_xor_sync(~0u, l1, 2);
      float i0, i1;
      asm volatile("rcp.approx.ftz.f32 %0, %2; rcp.approx.ftz.f32 %1, %3;" : "=f"(i0), "=f"(i1) : "f"(l0), "f"(l1));
      const bool mrows = c == 3 && st < NSTEP - 1;
      auto send = [&](const float (&o)[32], auto hc) {
        constexpr int H = decltype(hc)::value;
        static_for2([&](auto bc) {
          constexpr int B = decltype(bc)::value, J = 16 * B;
          asm volatile("st.async.weak.shared::cluster.mbarrier::complete_tx::bytes.v4.b32 [%0 + %9], {%5,%6,%7,%8}, [%1];\n"
                       "st.async.weak.shared::cluster.mbarrier::complete_tx::bytes.v4.b32 [%2 + %9], {%5,%6,%7,%8}, [%3];\n"
                       "st.shared.v4.b32 [%4 + %9], {%5,%6,%7,%8};"
                       ::"r"(a1), "r"(b1), "r"(a2), "r"(b2), "r"(oa), "r"(pack_bf16(o[J] * i0, o[J + 1] * i0)), "r"(pack_bf16(o[J + 4] * i0, o[J + 5] * i0)),
                         "r"(pack_bf16(o[J + 8] * i0, o[J + 9] * i0)), "r"(pack_bf16(o[J + 12] * i0, o[J + 13] * i0)), "n"(H * 1024 + B * 512) : "memory");
        });
      };
      auto keep_tok = [&](uint32_t ta, int R, float iv) {
#pragma unroll
        for (int k = 0; k < 4; k++) {
          const float (&o)[32] = k < 2 ? oA : oB;
          const int J = (k & 1) * 16 + R;
          stsm4(ta + k * 512, pack_bf16(o[J] * iv, o[J + 1] * iv), pack_bf16(o[J + 4] * iv, o[J + 5] * iv),
                pack_bf16(o[J + 8] * iv, o[J + 9] * iv), pack_bf16(o[J + 12] * iv, o[J + 13] * iv));
        }
      };
      wg_wait<1>();
      acc_fence(oA);
      if (mrows) send(oA, IC<0>());
      wg_wait<0>();
      acc_fence(oB);
      if (mrows) {
        send(oB, IC<1>());
        bar_arrive(NB_PV, 384);
        __syncwarp();
        mbar_arrive_z(bars + B_O * 8, lane);
      } else if (c < 3) {
        if (st < NSTEP - 1) bar_arrive(NB_PV, 384);
        const uint32_t ta = l16 + C_OT + (st & 1) * 8192;
        keep_tok(ta + (c ? c + 1 : 0) * 2048, 0, i0);
        if (w0) keep_tok(ta + 2048, 2, i1);
        __syncwarp();
        mbar_arrive_z(bars + B_OT * 8, lane);
      }
      TR(2)
      if (st == NSTEP - 1) break;
      mbar_expect_tx_z(bars + B_X * 8, 4096, t);
    }
    uint32_t tref;
    {
      const uint32_t tag = (st & 1) ^ 1;
      float oc0[12], oc1[12], oc2[12];
      mbar_wait(bars + B_O * 8, st & 1, 43);
      fence_async_smem();
      TR(3)
      wg_fence();
      out_tile(oc0, dWo, dO);
      wg_commit();
      out_tile(oc1, dWo + 1024, dO);
      wg_commit();
      asm volatile("" : "+r"(pgbits));
      auto put = [&](const float (&oc)[12], auto tlc) {
        constexpr int TL = decltype(tlc)::value;
        static_for3([&](auto jc) {
          constexpr int j = decltype(jc)::value;
          uint8_t* p = Pw + ((pgbits >> (2 * (TL * 3 + j))) & 3) * 4096;
          asm volatile("st.relaxed.gpu.global.u32 [%0 + %3], %1; st.relaxed.gpu.global.u32 [%0 + %3 + 128], %2;" ::"l"(p),
                       "r"((pack_bf16(oc[4 * j], oc[4 * j + 1]) & ~1u) | tag), "r"((pack_bf16(oc[4 * j + 2], oc[4 * j + 3]) & ~1u) | tag),
                       "n"((TL * 36 + j) * 16384) : "memory");
        });
      };
      wg_wait<1>();
      acc_fence(oc0);
      put(oc0, IC<0>());
      sts32(sb + C_INFO + 24, clk32());
      TR(4)
      out_tile(oc2, dWo + 2048, dO);
      wg_commit();
      wg_wait<1>();
      acc_fence(oc1);
      put(oc1, IC<1>());
      bar_sync(NB_TA, 160);
      tref = lds32(sb + C_INFO + 12);
      TR(5)
      wg_wait<0>();
      bar_arrive(NB_W0, 416);
      acc_fence(oc2);
      if (rank != 2) put(oc2, IC<2>());
      mbar_arrive_remote_z(((t & 1) ? b2 : b1) + (B_F - B_O) * 8, t >> 1);
      mbar_expect_tx_z(bars + B_O * 8, 4096, t);
      TR(6)
    }
    const int sn = (st + 1) & 3;
    {
      const uint32_t flip = (st & 1) ? ~0u : 0u;
      const bool u16 = lane & 16;
      uint8_t* mw = Mw + sn * 65536;
      asm volatile("" : "+l"(mw));
      const uint32_t bs = (lane & 4) ? 0x3f800000u : 0x00003f80u, bs0 = (lane & 8) ? 0u : bs, bs1 = (lane & 8) ? bs : 0u;
      const bool early = st < DELTA && b % 3 != 0;
      uint32_t m0word = 0;
      if (__builtin_expect(early, 0)) {
        const unsigned short* mp = (const unsigned short*)mem0 + ((lane & 1) * 4 + (lane >> 4) * 2) * DM + b / 3 * 16 + c * 4 + ((lane >> 2) & 3);
        m0word = (uint32_t)mp[0] | (uint32_t)mp[DM] << 16;
      }
      STATC(c_rdy)
      wait_clock(tref + gate_p);
      TR(7)
      uint32_t mword;
      int it = 0;
      bool all;
#pragma unroll 1
      do {
        const uint4 q0 = ld_rlx128(Pr0), q1 = ld_rlx128(Pr0 + 2048), q2 = ld_rlx128(Pr1), q3 = ld_rlx128(Pr1 + 2048);
        float d0[4] = {0.f, 0.f, 0.f, 0.f}, d1[4] = {0.f, 0.f, 0.f, 0.f};
        mma16816(d0, q0.x, q0.y, q0.z, q0.w, bs0, bs1);
        mma16816(d1, q1.x, q1.y, q1.z, q1.w, bs0, bs1);
        mma16816(d0, q2.x, q2.y, q2.z, q2.w, bs0, bs1);
        mma16816(d1, q3.x, q3.y, q3.z, q3.w, bs0, bs1);
        all = __all_sync(~0u, (int)and3(and_x(q0.x, q1.x, flip), and_x(q2.x, q3.x, flip), 1u));
        const float a0 = d0[0] + d1[0], a1 = d0[1] + d1[1], a2 = d0[2] + d1[2], a3 = d0[3] + d1[3];
        mword = pack_bf16((u16 ? a2 : a0) + __shfl_xor_sync(~0u, u16 ? a0 : a2, 16), (u16 ? a3 : a1) + __shfl_xor_sync(~0u, u16 ? a1 : a3, 16));
        asm volatile("{ .reg .pred p; setp.ne.u32 p, %2, 0; @p st.relaxed.gpu.global.u32 [%0], %1; }" ::"l"(mw), "r"(early ? m0word : mword), "r"((uint32_t)all) : "memory");
      } while (__builtin_expect(!all, 0) && ++it < SPIN_LIMIT);
      bar_arrive(NB_RD, 384);
      STATC(c_mst)
      STAT(0, lds32(sb + C_INFO + 24) - tref) STAT(1, c_rdy - tref) STAT(2, c_mst - tref) STAT(3, tref) STAT(4, it)
      if (!all) fail(44);
      TRV(14, it)
    }
    TR(9)
    {
      const uint32_t ma = l16 + C_M + c * 2048 + mi * 4;
      auto scan = [&](uint32_t m, uint32_t a) { return __vimax3_u32(__vimax3_u32(m, lds32(a), lds32(a + 512)), lds32(a + 1024), lds32(a + 1536)); };
      mbar_wait(bars + B_M0 * 8, (st + 1) & 1, 45);
      bar_arrive(NB_M0, 384);
      STATC(c_g0)
      TR(10)
      uint32_t m = scan(0, ma);
      mbar_wait(bars + B_M1 * 8, (st + 1) & 1, 46);
      bar_arrive(NB_M1, 384);
      STATC(c_g1)
      TR(11)
      m = scan(m, ma + 8192);
      mbar_wait(bars + B_M2 * 8, (st + 1) & 1, 47);
      STATC(c_g2)
      TR(12)
      int it = 0;
      const bool redo = bar_or(NB_M2, 384, scan(m, ma + 16384) == ~0u);
      if (__builtin_expect(redo, 0)) {
#pragma unroll 1
        for (int g = 0; g < 3;) {
          if (!__any_sync(~0u, scan(0, ma + g * 8192) == ~0u)) { g++; continue; }
          give_up(++it, SPIN_LIMIT, 48);
          if (lane == 0) {
            mbar_expect_tx(bars + (B_R + c) * 8, 2048);
            bulk_g2s(sb + C_M + g * 8192 + c * 2048, (const uint8_t*)g_M + sn * 65536 + (lds32(sb + C_POL + sn * 4) ? 4096 : 12288) + g * 16384 + c * 2048,
                     2048, bars + (B_R + c) * 8);
          }
          __syncwarp();
          mbar_wait(bars + (B_R + c) * 8, nretry++ & 1, 49);
        }
        bar_arrive(NB_M0, 384);
      }
      STAT(5, c_g0 - tref) STAT(7, c_g1 - tref) STAT(8, c_g2 - tref)
      STAT(9, clk32() - tref) STAT(6, it + redo * 256)
      TR(13)
      TRV(15, it)
      st_rlx32(Mw + (st & 3) * 65536, ~0u);
    }
  }
}

__device__ __forceinline__ void chain_dma(const uint32_t sb, const int w, const int lane, const uint32_t rank, const int h) {
  const uint32_t bars = sb + C_BAR;
  bar_sync(NB_ALL, 512);
  if (w == 12) { HD(3) }
  bar_sync(NB_ALL, 512);
  if (w == 12) { HD(4) }
  cluster_sync();
  if (w == 12) { HD(5) }
  const int expf_ = EXPF;
  if (w == 12) {
    u64 best = 0;
    uint32_t npatch = 0, nx = 0;
    auto load = [&](uint32_t dst, const uint8_t* src, uint32_t bytes) {
      mbar_expect_tx_z(bars + B_XL * 8, bytes, lane >> 1);
      if (lane < 2 && bytes) {
        fence_async_glb();
        bulk_g2s(sb + dst, src, bytes, bars + B_XL * 8);
      }
      __syncwarp();
      mbar_wait(bars + B_XL * 8, nx++ & 1, 52);
    };
    load(C_X + lane * 16384, g_xs[0] + lane * 16384, 16384);
    HD(6)
    bar_arrive(NB_X1, 288); bar_arrive(NB_XB, 288);
#pragma unroll 1
    for (int st = 0; st < NSTEP; st++) {
      const int sg = st - DELTA;
      const bool more = st + 1 < NSEG && !(expf_ & 4);
      uint32_t info = 0;
      if (sg >= 0) {
        const u64 k = wait_keys(g_fl.key[0][sg], lane, 50);
        if (k > best) { best = k; info = 4 | ((key_token(k) >> 3) & 3); }
      }
      TR(0)
      mbar_wait(bars + (st ? B_X : B_XF) * 8, (st - 1 + !st) & 1, 58);
      sts32(sb + C_INFO + (st & 1) * 4, info);
      TR(1)
      load(lane ? C_X : C_X + 32768, lane ? g_xs[0] + (st + 1) * 32768 : g_xs[1] + sg * 32768, lane ? (more ? K3 * 1024 : 0) : (sg >= 0 && !(expf_ & 8) ? 32768 : 0));
      bar_arrive(NB_W0, 416);
      TR(2)
      if (__builtin_expect(info, 0)) {
        if (npatch > 0) mbar_wait(bars + B_P3 * 8, (npatch - 1) & 1, 55);
        npatch++;
        wait_count(g_fl.patch[sg], 1, 56);
        if (lane == 0) {
          fence_async_glb();
          mbar_expect_tx(bars + B_XL3 * 8, 8192);
          bulk_g2s(sb + C_X + 65536, g_patch + (size_t)sg * 8192, 8192, bars + B_XL3 * 8);
        }
        __syncwarp();
      }
      if (st == NSTEP - 1) break;
      mbar_wait(bars + B_XF * 8, st & 1, 53);
      mbar_wait(bars + (B_M0 + BGATE) * 8, st & 1, 54);
      load(C_X + K3 * 1024, g_xs[0] + (st + 1) * 32768 + K3 * 1024, more && lane == 0 ? 32768 - K3 * 1024 : 0);
      TR(3)
      bar_arrive(NB_XB, 288);
    }
  } else if (w == 13) {
    constexpr uint32_t NP = 8192 / SHIP;
    const uint32_t o = (lane >> 1) * SHIP, own = sb + C_Q + rank * 10240, bt = bars + B_T * 8;
    const uint32_t d2 = 1 + (lane & 1);
    const uint32_t src2 = (rank == 0 ? sb + C_SA : rank == 1 ? own : sb + C_SB) + o;
    const uint32_t skip = (lane & 1) ? 4 | (o >> 11) : 8;
    uint32_t npatch = 0;
#pragma unroll 1
    for (int st = 0; st < NSTEP; st++) {
      mbar_wait(bars + B_P1 * 8, st & 1, 61);
      fence_async_smem();
      if (st > 0) mbar_wait(bars + B_F * 8, (st - 1) & 1, 60);
      const uint32_t info = lds32(sb + C_INFO + (st & 1) * 4);
      TR(2)
      if (st < NSEG && rank != 0 && lane < 2 * NP && d2 == 1 && !(expf_ & 1)) bulk_s2r(mapa_u32(own + o, 0), sb + C_SA + o, SHIP, mapa_u32(bt, 0));
      __syncwarp();
      TR(3)
      mbar_wait(bars + B_P2 * 8, st & 1, 62);
      fence_async_smem();
      if (st > 0 && (SHIPLATE >> rank & 1)) mbar_wait(bars + B_I * 8, (st - 1) & 1, 64);
      TR(0)
      if (st >= DELTA && lane < 2 * NP && d2 != rank && info != skip && !(expf_ & 2)) bulk_s2r(mapa_u32(own + o, d2), src2, SHIP, mapa_u32(bt, d2));
      __syncwarp();
      TR(1)
      if (__builtin_expect(info, 0)) {
        mbar_wait(bars + B_P3 * 8, npatch & 1, 63);
        npatch++;
        fence_async_smem();
        if (rank != 2 && lane == 0) bulk_s2r(mapa_u32(own + (info & 3) * 2048, 2), sb + C_SP, 2048, mapa_u32(bt, 2));
        __syncwarp();
      }
    }
  } else if (w == 14) {
    const int s0 = rank == 0 ? 0 : DELTA;
    const uint32_t tbytes = (expf_ & (rank ? 2 : 1)) ? 0 : 16384;
    mbar_expect_tx_z(bars + B_T * 8, s0 == 0 ? tbytes : 0, lane);
    {
      const int u = (rank == 2 ? 0 : rank + 1) * 32 + h;
      st_rlx32(&g_fl.pol[u], probe_polarity(g_P + u * 4096, lane) + 1);
    }
#pragma unroll 1
    for (int st = 0; st < NSTEP; st++) {
      const int sg = st - s0;
      const bool act = (unsigned)sg < (unsigned)NSEG;
      mbar_wait(bars + B_OT * 8, st & 1, 70);
      mbar_expect_tx_z(bars + B_T * 8, (unsigned)(sg + 1) < (unsigned)NSEG ? tbytes : 0, lane);
      fence_async_smem();
      const int s1 = rank ? st + 1 : st;
      if (rank && s1 < NSTEP - 1) mbar_wait(bars + B_X * 8, s1 & 1, 71);
      TR(0)
      if (act && lane == 0 && !(expf_ & (rank ? 32 : 16))) {
        bulk_s2g(g_O[st & (OSLOTS - 1)][rank] + h * 8192, sb + C_OT + (st & 1) * 8192, 8192);
        asm volatile("cp.async.bulk.commit_group;" ::: "memory");
        asm volatile("cp.async.bulk.wait_group 0;" ::: "memory");
        asm volatile("fence.acq_rel.gpu;" ::: "memory");
      }
      __syncwarp();
      if (WLAG && s1 < NSTEP - 1) mbar_wait(bars + (FGATE ? B_M0 + FGATE - 1 : B_I) * 8, (s1 + (FGATE > 0)) & 1, 72);
      if (act && lane == 0) asm volatile("red.relaxed.gpu.global.add.u32 [%0], 1;" ::"l"(&g_fl.oflag[rank][sg][h >> 2]) : "memory");
      __syncwarp();
      TR(1)
    }
  } else {
    mbar_arrive_z(bars + B_M0 * 8, lane); mbar_arrive_z(bars + B_M1 * 8, lane); mbar_arrive_z(bars + B_M2 * 8, lane);
    const uint32_t gate_g = GATE_G, gate_m = GATE_M;
#pragma unroll 1
    for (int st = 0; st < NSTEP - 1; st++) {
      mbar_wait(bars + B_X * 8, st & 1, 75);
      if (st < 4) { HD(8 + st) }
      if (st == NSTEP - 2) { HD(12) }
      mbar_wait(bars + B_T * 8, st & 1, 77);
      const uint32_t now = gtime() & ~31u, tag = (st + 1) & 31;
      if (lane == 0) st_rlx32(&g_fl.stamp[blockIdx.x], now | tag);
      __syncwarp();
      wait_clock(clk32() + 550);
      uint32_t s0, s1, s2;
      int it = 0;
#pragma unroll 1
      do {
        s0 = ld_rlx32(&g_fl.stamp[lane]) ^ tag; s1 = ld_rlx32(&g_fl.stamp[32 + lane]) ^ tag; s2 = ld_rlx32(&g_fl.stamp[64 + lane]) ^ tag;
        give_up(it++, SPIN_LIMIT, 76);
      } while (__any_sync(~0u, ((s0 | s1 | s2) & 31) != 0));
      const uint32_t tref = now + __reduce_max_sync(~0u, __vimax3_s32((int)(s0 - now), (int)(s1 - now), (int)(s2 - now)));
      const uint32_t g0 = gtime();
      uint32_t g1, c1;
      it = 0;
      do { g1 = gtime(); c1 = clk32(); } while (g1 == g0 && ++it < 64);
      c1 -= (g1 - tref) * 7 / 4;
      sts32(sb + C_INFO + 12, c1);
      TR(0)
      bar_arrive(NB_TA, 160);
      const int sn = (st + 1) & 3;
      const uint8_t* src = (const uint8_t*)g_M + sn * 65536 + (lds32(sb + C_POL + sn * 4) ? 4096 : 12288);
      c1 += gate_m;
      const int d = (int)(c1 - 600 - clk32());
      if (d > 0) __nanosleep(d / 4);
      mbar_expect_tx_z(bars + (B_M0 + lane) * 8, 8192, lane / 3);
      if (lane == 0) {
#pragma unroll
        for (int g = 0; g < 3; g++) {
          wait_clock(c1 + g * gate_g);
          bulk_g2s(sb + C_M + g * 8192, src + g * 16384, 8192, bars + (B_M0 + g) * 8);
          if (g == IGRP) mbar_arrive_z(bars + B_I * 8, 0);
        }
      }
      __syncwarp();
      TR(3)
    }
  }
}

__global__ void __cluster_dims__(3, 1, 1) __launch_bounds__(512, 1)
chain_kernel(const bf16* __restrict__ Wq, const bf16* __restrict__ Wk, const bf16* __restrict__ Wv,
             const bf16* __restrict__ Wo, const bf16* __restrict__ mem0) {
  extern __shared__ __align__(1024) uint8_t smem_raw[];
  const uint32_t sb = (smem_u32(smem_raw) + 1023) & ~1023u;
  const int tid = threadIdx.x, lane = tid & 31;
  const int w = __shfl_sync(~0u, tid >> 5, 0);
  uint32_t rank;
  asm volatile("mov.u32 %0, %%cluster_ctarank;" : "=r"(rank));
  const int h = blockIdx.x / 3;
  asm volatile("griddepcontrol.launch_dependents;" ::: "memory");
  TG(0)
  if (tid == 0) {
    const uint32_t bars = sb + C_BAR;
    mbar_init(bars + B_M0 * 8, 1); mbar_init(bars + B_M1 * 8, 1); mbar_init(bars + B_M2 * 8, 1);
    for (int i = 0; i < 4; i++) mbar_init(bars + (B_R + i) * 8, 1);
    mbar_init(bars + B_X * 8, 9); mbar_init(bars + B_O * 8, 2); mbar_init(bars + B_T * 8, 1); mbar_init(bars + B_F * 8, 2);
    mbar_init(bars + B_XL * 8, 2); mbar_init(bars + B_XL3 * 8, 1);
    mbar_init(bars + B_P1 * 8, 8); mbar_init(bars + B_P2 * 8, 8); mbar_init(bars + B_P3 * 8, 8); mbar_init(bars + B_OT * 8, 3); mbar_init(bars + B_XF * 8, 8); mbar_init(bars + B_I * 8, 1);
    asm volatile("fence.mbarrier_init.release.cluster;" ::: "memory");
  }
  {
    cp16(sb + C_OT + tid * 16, mem0 + (tid & 7) * DM + (tid >> 3) * 8);
    const bf16* W1 = (rank == 0 ? Wq : rank == 1 ? Wk : Wv) + h * 128;
#pragma unroll 4
    for (int cidx = tid; cidx < 512 * 16; cidx += 512) {
      const int d = cidx >> 4, q = cidx & 15;
      cp16(sb + C_X + d * W_STRIDE + q * 16, W1 + (size_t)d * HD + q * 8);
    }
    const int nt = rank == 2 ? 2 : 3;
    for (int cidx = tid; cidx < nt * 1024; cidx += 512) {
      const int tl = cidx >> 10, e = (cidx >> 3) & 127, q = cidx & 7;
      const int es = (e & ~30) | ((e & 6) << 2) | ((e >> 2) & 6);
      cp16(sb + C_WO + tl * 16384 + e * 128 + ((q ^ (e & 7)) << 4), Wo + (size_t)(h * 128 + es) * DM + (tl * 3 + rank) * 64 + q * 8);
    }
    asm volatile("cp.async.commit_group;" ::: "memory");
    if (w == 0) { HD(0) }
    if (w == 0) { HD(1) }
    asm volatile("cp.async.wait_group 0;" ::: "memory");
    fence_async_smem();
    __syncthreads();
    if (w == 0) { HD(2) }
  }
  if (w < 8) {
    reg_inc<184>();
    chain_proj(sb, w, lane, rank);
    TG(1)
    TRDUMP
    cluster_sync();
  } else if (w < 12) {
    reg_dec<120>();
    chain_mem(sb, w, lane, rank, h, mem0);
    STATDUMP
    TRDUMP
    cluster_sync();
  } else {
    reg_dec<24>();
    chain_dma(sb, w, lane, rank, h);
    TRDUMP
    cluster_sync();
  }
}
#undef TRC
#undef TRS

constexpr int K_BAR = 0, K_LN = 128, K_FH = 320, K_FS = 512, K_FY = 2048;
constexpr int K_W = 3072;
constexpr int K_O = K_W + 3 * 49152;
constexpr int K_ST = K_O + 65536;
constexpr int K_SMEM = K_ST + 16384;
static_assert(K_SMEM <= 232448 && 512 * W_STRIDE <= 3 * 49152, "shared memory");
enum { KB_FULL = 0, KB_EMPTY = 2, KB_OK = 4, KB_GO = 7, KB_ST = 10, KB_REL = 12 };
enum { KN_ST = 1, KN_ST1, KN_REL, KN_FFN, KN_INIT, KN_RES, KN_CAND, KN_TAKEN };
#define GATE_R 450
struct WorkerParams {
  const bf16 *x0, *Wo, *w_r, *w_gate, *w_up, *w_down;
  bf16* out;
};
#define TRC (96 + blockIdx.x)
#define FT(e)
#define QUIET 4900
__device__ __forceinline__ void quiet_until(uint32_t t) {
  int d;
  while ((d = (int)(t - clk32())) > 0) __nanosleep(min(d / 3 + 20, 1000));
}
#define FOR_UNITS _Pragma("unroll 1") for (int st = 0, n = 0; st < WSTEP; st++) \
                  _Pragma("unroll 1") for (int v = st < NSEG ? 0 : st < WSTEP - 1 ? 1 : 2, sg = v ? st - WD : st; v < (st >= WD ? 3 : 1); v++, n++, sg = st - WD)

__device__ __forceinline__ void ffn_slice(uint32_t sb, int t, int nu, const bf16* yrow, int ev) {
  const int lane = t & 31, c = t >> 5;
  FT(1)
  const uint32_t sg_ = sb + (nu == 3 ? K_FS : K_ST), sh = sb + K_FH;
  {
    const uint2 r = ld_rlx64(yrow + t * 4);
    asm volatile("st.shared.v2.b32 [%0], {%1,%2};" ::"r"(sb + K_FY + t * 8), "r"(r.x), "r"(r.y) : "memory");
    __syncwarp();
  }
  const uint32_t sy = sb + K_FY + (t >> 2) * 32;
  FT(2)
#pragma unroll 1
  for (int u = 0; u < nu; u++) {
    float g[8];
#pragma unroll
    for (int i = 0; i < 8; i++) g[i] = 0.f;
    const uint32_t wa = sb + K_W + u * 49152 + c * 8192 + lane * 16;
    auto fma8 = [&](float y, const uint4& a) {
      g[0] += y * bf_lo(a.x); g[1] += y * bf_hi(a.x); g[2] += y * bf_lo(a.y); g[3] += y * bf_hi(a.y);
      g[4] += y * bf_lo(a.z); g[5] += y * bf_hi(a.z); g[6] += y * bf_lo(a.w); g[7] += y * bf_hi(a.w);
    };
    uint4 a0 = lds128(wa), a1 = lds128(wa + 512);
    uint32_t y0 = lds32(sy);
#pragma unroll 1
    for (int i = 0; i < 16; i += 4) {
      const uint4 b0 = lds128(wa + (i + 2) * 512), b1 = lds128(wa + (i + 3) * 512);
      const uint32_t y1 = lds32(sy + i * 2 + 4);
      fma8(bf_lo(y0), a0); fma8(bf_hi(y0), a1);
      a0 = lds128(wa + (i + 4) * 512); a1 = lds128(wa + (i + 5) * 512);
      y0 = lds32(sy + i * 2 + 8);
      fma8(bf_lo(y1), b0); fma8(bf_hi(y1), b1);
    }
#pragma unroll
    for (int i = 0; i < 4; i++) g[i] = ((lane & 16) ? g[4 + i] : g[i]) + __shfl_xor_sync(~0u, (lane & 16) ? g[i] : g[4 + i], 16);
#pragma unroll
    for (int i = 0; i < 2; i++) g[i] = ((lane & 8) ? g[2 + i] : g[i]) + __shfl_xor_sync(~0u, (lane & 8) ? g[i] : g[2 + i], 8);
    g[0] = ((lane & 4) ? g[1] : g[0]) + __shfl_xor_sync(~0u, (lane & 4) ? g[0] : g[1], 4);
    sts32(sg_ + u * 512 + c * 128 + ((lane & 3) * 8 + (lane >> 2)) * 4, __float_as_uint(g[0]));
  }
  FT(3)
  bar_sync(KN_FFN, 128);
  {
    const uint32_t pa = sg_ + c * 512 + lane * 4;
    const float gt = round_bf16((__uint_as_float(lds32(pa)) + __uint_as_float(lds32(pa + 128))) + (__uint_as_float(lds32(pa + 256)) + __uint_as_float(lds32(pa + 384))));
    const float up = __shfl_xor_sync(~0u, gt, 16);
    if (lane < 16 && c < nu) sts32(sh + (c * 16 + lane) * 4, __float_as_uint(round_bf16(round_bf16(gt / (1.f + __expf(-gt))) * up)));
  }
  bar_sync(KN_FFN, 128);
  FT(4)
  float a0 = 0.f, a1 = 0.f, a2 = 0.f, a3 = 0.f;
#pragma unroll 1
  for (int u = 0; u < 2 * nu; u++) {
    const uint32_t wa = sb + K_W + (u >> 1) * 49152 + 32768 + (u & 1) * 8192 + t * 8;
    const uint4 h0 = lds128(sh + u * 32), h1 = lds128(sh + u * 32 + 16);
    const uint32_t hv[8] = {h0.x, h0.y, h0.z, h0.w, h1.x, h1.y, h1.z, h1.w};
    uint2 d[8];
#pragma unroll
    for (int k = 0; k < 8; k++) asm volatile("ld.shared.v2.b32 {%0,%1}, [%2];" : "=r"(d[k].x), "=r"(d[k].y) : "r"(wa + k * 1024) : "memory");
#pragma unroll
    for (int k = 0; k < 8; k++) {
      const float hf = __uint_as_float(hv[k]);
      a0 += hf * bf_lo(d[k].x); a1 += hf * bf_hi(d[k].x); a2 += hf * bf_lo(d[k].y); a3 += hf * bf_hi(d[k].y);
    }
  }
  FT(5)
  asm volatile("red.relaxed.gpu.global.add.v4.f32 [%0], {%1,%2,%3,%4};" ::"l"(&g_fl.upd[ev][t * 4]), "f"(a0), "f"(a1), "f"(a2), "f"(a3) : "memory");
  bar_sync(KN_FFN, 128);
  if (t == 96) red_release(g_fl.ffncnt[ev]);
  __syncwarp();
}
__device__ __forceinline__ Row ffn_finish(int ver, int ev, u64 key, int lane) {
  const int tok = key_token(key);
  Row x = load_row(g_rows[tok][ver][0], lane);
  const Row y = load_row(g_rows[tok][ver][1], lane);
  const float sig = round_bf16(1.f / (1.f + __expf(-key_score(key))));
  wait_count(g_fl.ffncnt[ev], NWORK, 80);
#pragma unroll
  for (int q = 0; q < 4; q++) {
    const uint4 u = ld_rlx128(&g_fl.upd[ev][q * 128 + lane * 4]);
    const uint32_t a = pack_bf16(__uint_as_float(u.x), __uint_as_float(u.y)), b = pack_bf16(__uint_as_float(u.z), __uint_as_float(u.w));
    x.w[2 * q] = add_bf16x2(x.w[2 * q], add_bf16x2(y.w[2 * q], pack_bf16(bf_lo(a) * sig, bf_hi(a) * sig)));
    x.w[2 * q + 1] = add_bf16x2(x.w[2 * q + 1], add_bf16x2(y.w[2 * q + 1], pack_bf16(bf_lo(b) * sig, bf_hi(b) * sig)));
  }
  return x;
}
__device__ __forceinline__ uint2 group_ln(uint2 r, float& e, uint32_t sl, uint32_t sw, int lane) {
  const float x0 = bf_lo(r.x), x1 = bf_hi(r.x), x2 = bf_lo(r.y), x3 = bf_hi(r.y);
  const float s = (x0 + x1) + (x2 + x3), q = fmaf(x0, x0, x1 * x1) + fmaf(x2, x2, x3 * x3);
  const bool u16 = lane & 16, u8 = lane & 8;
  const float a = (u16 ? q : s) + __shfl_xor_sync(~0u, u16 ? s : q, 16), b = e + __shfl_xor_sync(~0u, e, 16);
  float v = (u8 ? b : a) + __shfl_xor_sync(~0u, u8 ? a : b, 8);
  v += __shfl_xor_sync(~0u, v, 4); v += __shfl_xor_sync(~0u, v, 2); v += __shfl_xor_sync(~0u, v, 1);
  sts32(sl + sw, __float_as_uint(v));
  bar_sync(KN_RES, 128);
  const uint4 ss = lds128(sl), qq = lds128(sl + 32), ee = lds128(sl + 16);
  const float m = ((__uint_as_float(ss.x) + __uint_as_float(ss.y)) + (__uint_as_float(ss.z) + __uint_as_float(ss.w))) * (1.f / DM);
  const float m2 = ((__uint_as_float(qq.x) + __uint_as_float(qq.y)) + (__uint_as_float(qq.z) + __uint_as_float(qq.w))) * (1.f / DM);
  e = (__uint_as_float(ee.x) + __uint_as_float(ee.y)) + (__uint_as_float(ee.z) + __uint_as_float(ee.w));
  float rs;
  asm("rsqrt.approx.ftz.f32 %0, %1;" : "=f"(rs) : "f"(fmaxf(fmaf(-m, m, m2), 0.f) + 1e-5f));
  return make_uint2(pack_bf16((x0 - m) * rs, (x1 - m) * rs), pack_bf16((x2 - m) * rs, (x3 - m) * rs));
}
__device__ __forceinline__ uint32_t score_bits(float r) {
  const uint32_t b = pack_bf16(0.f, r);
  return (b & 0x80000000u) ? ~b : (b | 0x80000000u);
}

__global__ void __launch_bounds__(640, 1) worker_kernel(const __grid_constant__ WorkerParams prm) {
  extern __shared__ __align__(1024) uint8_t smem_raw[];
  const uint32_t sb = smem_u32(smem_raw);
  const int tid = threadIdx.x, lane = tid & 31;
  const int w = __shfl_sync(~0u, tid >> 5, 0);
  const int me = blockIdx.x, kb = me >> 2, cb = me & 3;
  const bool full = me < 32;
  const uint32_t bars = sb + K_BAR;
  TG(0)
  if (tid == 0) {
    for (int i = 0; i < 2; i++) { mbar_init(bars + (KB_FULL + i) * 8, 1); mbar_init(bars + (KB_EMPTY + i) * 8, 1); }
    for (int i = 0; i < 9; i++) mbar_init(bars + (KB_OK + i) * 8, i < 3 ? 4 : 1);
    sts32(sb + K_LN + 144, 0); sts32(sb + K_LN + 176, 0); sts32(sb + K_LN + 180, ~0u);
    asm volatile("fence.mbarrier_init.release.cluster;" ::: "memory");
  }
  if (full) {
    const bf16* W1 = prm.Wo + (size_t)kb * 512 * DM + cb * 128;
#pragma unroll 4
    for (int cidx = tid; cidx < 512 * 16; cidx += 640) {
      const int d = cidx >> 4, q = cidx & 15;
      cp16(sb + K_W + d * W_STRIDE + q * 16, W1 + (size_t)d * DM + q * 8);
    }
    asm volatile("cp.async.commit_group;" ::: "memory");
    asm volatile("cp.async.wait_group 0;" ::: "memory");
  }
  fence_async_smem();
  __syncthreads();
  if (w < 8) {
    reg_inc<176>();
    if (full) {
      uint32_t wA[32][4];
      load_wfrags(wA, sb + K_W, w, lane);
      bar_arrive(KN_INIT, 384);
      const uint32_t sp = pin(sb + K_ST + ((lane >> 4) * 8 + (lane & 7)) * 256 + (((2 * w + ((lane >> 3) & 1)) ^ (lane & 7)) << 4));
      const uint32_t tm = pin(lane < 4 ? 0x00010001u : 0u);
      FOR_UNITS {
        float d[16];
        mbar_wait(bars + (KB_FULL + (n & 1)) * 8, (n >> 1) & 1, 81);
        TR(4 * v)
        const uint64_t db = mk_desc(sb + K_O + (n & 1) * 32768, 128, 2048, 0);
        wg_fence();
#pragma unroll
        for (int ks = 0; ks < 32; ks++) {
          if (ks == 0) wg_rs32<0, 0>(d, wA[ks], db);
          else wg_rs32<0, 1>(d, wA[ks], db + (ks >> 3) * 512 + (ks & 7) * 16);
        }
        wg_commit();
        mbar_wait(bars + (KB_ST + (n & 1)) * 8, ((n >> 1) & 1) ^ 1, 82);
        wg_wait<0>();
        acc_fence(d);
        TR(4 * v + 1)
        const uint32_t tag = (sg & 2) ? 0u : tm;
        uint32_t pk[8];
#pragma unroll
        for (int i = 0; i < 8; i++) pk[i] = (pack_bf16(d[2 * i], d[2 * i + 1]) & ~tm) | tag;
        stsm4t(sp + (n & 1) * 8192, pk[0], pk[1], pk[2], pk[3]);
        stsm4t(sp + (n & 1) * 8192 + 4096, pk[4], pk[5], pk[6], pk[7]);
        bar_arrive(KN_ST + (n & 1), 288);
        TR(4 * v + 2)
      }
    }
  } else if (w < 12) {
    reg_dec<56>();
    if (full) {
      const int t = pin(tid - 256), ln = t & 31;
      const uint32_t sw = pin((lane >> 3) * 16 + (w - 8) * 4);
      const uint32_t so = pin((w - 8) * 8192 + me * 256 + ((lane * 8) ^ ((me & 7) << 4)));
      uint2 wr = ld_rlx64(prm.w_r + t * 4);
      int sstar = -1;
      auto records = [&](int sg) {
        uint4 r;
        int it = 0;
        while ((int)(r = lds128(sb + K_LN + 144)).x <= sg) { give_up(++it, SPIN_LIMIT, 86); __nanosleep(50); }
        return r;
      };
      uint32_t sl = sb + K_LN;
      float rr = 0.f;
      int kprev = -1, pv = 0, psg = 0;
      uint2 x = make_uint2(0, 0);
      auto finish = [&](int v, int sg) {
        bf16* dst = g_rows[sg * 32 + me][v][0] + t * 4;
        if (!(WEXP & 1)) *(uint2*)dst = x;
        sl ^= 64;
        const uint2 y = group_ln(x, rr, sl, sw, ln);
        if (!(WEXP & 1)) *(uint2*)(dst + DM) = y;
        x = make_uint2(add_bf16x2(x.x, y.x), add_bf16x2(x.y, y.y));
        if (!(WEXP & 1)) *(uint2*)(v == (sg < sstar ? 1 : 2) ? prm.out + (sg * 32 + me) * DM + t * 4 : dst + 2 * DM) = x;
        asm volatile("{ .reg .pred p; setp.eq.u32 p, %2, 0; @p st.relaxed.gpu.global.u64 [%0], %1; }" ::"l"(&g_fl.key[0][0][0] + max(kprev, 0)),
                     "l"((u64)score_bits(rr) << 32 | (uint32_t)~(kprev & (NTOK - 1))), "r"(t | (kprev < 0)) : "memory");
        kprev = v * NTOK + sg * 32 + me;
        asm volatile("" : "+r"(wr.x), "+r"(wr.y));
        rr = fmaf(bf_lo(y.x), bf_lo(wr.x), bf_hi(y.x) * bf_hi(wr.x)) + fmaf(bf_lo(y.y), bf_lo(wr.y), bf_hi(y.y) * bf_hi(wr.y));
      };
      FOR_UNITS {
        const uint8_t* src = g_part[v] + (sg & 1) * (32 * 8192) + so;
        const bf16* xin = v ? g_rows[sg * 32 + me][0][2] : prm.x0 + (sg * 32 + me) * DM;
        if (v == 2) {
          const uint4 r = records(sg);
          if (((sg < 32 ? r.y : r.z) >> (sg & 31)) & 1) xin = g_x2p + sg * DM;
        }
        mbar_wait(bars + (KB_GO + v) * 8, sg & 1, 87);
        TR(4 * v)
        uint2 p[8];
#pragma unroll
        for (int k = 0; k < 8; k++) p[k] = ld_rlx64(src + k * 32768);
        const uint2 x0 = ld_rlx64(((WEXP & 2) ? prm.x0 : xin) + t * 4);
        if (pv) finish(pv, psg);
        const uint32_t flip = lds32(sb + K_LN + 176 + (sg & 2) * 2);
        int it = 0;
#pragma unroll 1
        while (__builtin_expect(!__all_sync(~0u, (int)and3(and3(and_x(p[0].x, p[1].x, flip), and_x(p[2].x, p[3].x, flip), 1u),
                                                           and_x(p[4].x, p[5].x, flip), and_x(p[6].x, p[7].x, flip)) | (t & 1)), 0)) {
          give_up(++it, SPIN_LIMIT, 85);
#pragma unroll
          for (int k = 0; k < 8; k++) p[k] = ld_rlx64(src + k * 32768);
        }
        mbar_arrive_z(bars + (KB_OK + v) * 8, ln);
#define P8(h, f) (((h(p[0].f) + h(p[1].f)) + (h(p[2].f) + h(p[3].f))) + ((h(p[4].f) + h(p[5].f)) + (h(p[6].f) + h(p[7].f))))
        x = make_uint2(add_bf16x2(x0.x, pack_bf16(P8(bf_lo, x), P8(bf_hi, x))), add_bf16x2(x0.y, pack_bf16(P8(bf_lo, y), P8(bf_hi, y))));
#undef P8
        TRV(12 + v, it)
        TR(4 * v + 1)
        pv = v; psg = sg;
        if (v == 0 || (v == 2 && st >= NSEG)) {
          pv = 0;
          finish(v, sg);
          sl ^= 64;
          const uint2 y = group_ln(x, rr, sl, sw, ln);
          if (v == 0) *(uint2*)(g_xs[1] + sg * 32768 + (t >> 4) * 4096 + me * 128 + ((((t & 15) >> 1) ^ (me & 7)) << 4) + (t & 1) * 8) = y;
          sts32(sb + K_LN + 128, score_bits(rr));
          bar_arrive(KN_REL, 160);
          kprev = -1;
          if (__builtin_expect(v == 0 && sg == NSEG - 1, 0)) {
            sstar = records(NSEG - 1).w;
            const int nc = min(sstar, NSEG - 1 - WD);
#pragma unroll 1
            for (int s0 = 0; s0 < nc; s0 += 8) {
              uint2 r[8];
#pragma unroll
              for (int i = 0; i < 8; i++) r[i] = ld_rlx64(g_rows[min(s0 + i, nc - 1) * 32 + me][1][2] + t * 4);
#pragma unroll
              for (int i = 0; i < 8; i++) *(uint2*)(prm.out + (min(s0 + i, nc - 1) * 32 + me) * DM + t * 4) = r[i];
            }
          }
        }
        TR(4 * v + 2)
      }
    }
  } else if (w < 16) {
    reg_dec<48>();
    const int t = tid - 384, nu = full ? 3 : 4;
    if (full) bar_sync(KN_INIT, 384);
    {
      const int j0 = (full ? me * 3 : 96 + (me - 32) * 4) * 16;
#pragma unroll 1
      for (int i = t; i < nu * 3072; i += 128) {
        const int u = i / 3072, r = i - u * 3072;
        const bf16* src = r < 2048 ? ((r & 2) ? prm.w_up : prm.w_gate) + (size_t)((r >> 9) * 128 + ((r >> 2) & 7) * 16 + ((r >> 5) & 15)) * FF + j0 + u * 16 + (r & 1) * 8
                                   : prm.w_down + (size_t)(j0 + u * 16) * DM + (r - 2048) * 8;
        cp16(sb + K_W + i * 16, src);
      }
      asm volatile("cp.async.wait_all;" ::: "memory");
    }
    bar_arrive(KN_TAKEN, 160);
#pragma unroll 1
    while (true) {
      bar_sync(KN_CAND, 160);
      const uint4 cand = lds128(sb + K_LN + 160);
      const u64 k = (u64)cand.y << 32 | cand.x;
      const int ev = cand.z, ver = cand.w & 3, tok = key_token(k);
      const bool last = cand.w & 4;
      if (!last) {
        bar_arrive(KN_TAKEN, 160);
        FT(0)
        ffn_slice(sb, t, nu, g_rows[tok][ver][1], ev);
      }
      if ((tok & 31) == me && (ver == 0 || last)) {
        uint8_t* dst = g_patch + (size_t)(tok >> 5) * 8192;
        if (w == 12) {
          FT(6)
          const Row x = ffn_finish(ver, ev, k, lane);
          FT(7)
          store_row(ver ? prm.out + (size_t)tok * DM : g_x2p + ev * DM, lane, x);
          if (ver == 0) store_row_img<1024>(dst, tok & 7, lane, warp_ln(x));
        } else if (w < 15 && ver == 0) {
          const uint8_t* src = g_xs[1] + (size_t)(tok >> 5) * 32768 + (tok & 24) * 128 + (t - 32) * 16;
          uint4 q[8];
#pragma unroll
          for (int i = 0; i < 8; i++) q[i] = ld_rlx128(src + i * 4096);
          if (((t - 32) >> 3) != (tok & 7)) {
#pragma unroll
            for (int i = 0; i < 8; i++) *(uint4*)(dst + (t - 32) * 16 + i * 1024) = q[i];
          }
        }
        bar_sync(KN_FFN, 128);
        if (t == 0 && ver == 0) st_release32(g_fl.patch[ev], 1);
        __syncwarp();
      }
      FT(8)
      if (last) break;
    }
  } else {
    reg_dec<24>();
    if (w == 16) {
      u64 best = 0, mask = 0;
      int sstar = 0;
      uint32_t ver = 0, ev = 0;
      auto post = [&](uint32_t cmd) {
        bar_sync(KN_TAKEN, 160);
        sts128(sb + K_LN + 160, make_uint4((uint32_t)best, (uint32_t)(best >> 32), ev, ver | cmd));
        bar_arrive(KN_CAND, 160);
      };
      u64 accn = 0, acca = 0;
      uint32_t recs = 0;
      int j = 0;
      uint32_t tq = clk32();
#pragma unroll 1
      for (int st = 0; st < WSTEP; st++) {
        const u64* keys = st < NSEG ? g_fl.key[0][st] : g_fl.key[2][st - WD];
        const bool early = __any_sync(~0u, ld_rlx32(keys + lane) == 0);
        if (early && st < NSEG) quiet_until(tq);
        u64 k = wait_keys(keys, lane, 91);
        if (early) tq = clk32() + QUIET;
        if (st < NSEG) {
          const bool rec = k > best;
          recs &= ~(1u << (st & 31));
          if (rec) {
            best = k; ev = sstar = st;
            recs |= 1u << (st & 31);
            if ((key_token(k) & 31) == me) mask |= 1ull << st;
          }
          sts128(sb + K_LN + 144, make_uint4(st + 1, (uint32_t)mask, (uint32_t)(mask >> 32), sstar));
          if (rec) post(0);
        }
#pragma unroll 1
        for (; j <= st - WD - (st < NSEG ? 2 : 0); j++) {
          u64 kn = 1, kc;
          int it = 0;
          do {
            if (j < NSEG - 1) asm volatile("ld.relaxed.gpu.global.u64 %0, [%1];" : "=l"(kn) : "l"(&g_fl.key[1][j][lane]) : "memory");
            asm volatile("ld.relaxed.gpu.global.u64 %0, [%1];" : "=l"(kc) : "l"(&g_fl.key[2][j][lane]) : "memory");
            give_up(it++, SPIN_LIMIT, 92);
          } while (__any_sync(~0u, kn == 0 || kc == 0));
          if ((recs >> (j & 31)) & 1) acca = accn;
          if (kc > acca) acca = kc;
          if (kn > accn) accn = kn;
        }
        if (st >= NSEG) {
          const u64 m = j <= sstar ? accn : acca;
          const uint32_t hi = __reduce_max_sync(~0u, (uint32_t)(m >> 32));
          k = (u64)hi << 32 | __reduce_max_sync(~0u, (uint32_t)(m >> 32) == hi ? (uint32_t)m : 0u);
          if (st == NSEG || k != best) {
            best = k; ev = st;
            ver = (key_token(k) >> 5) < sstar ? 1 : 2;
            post(0);
          }
        }
      }
      HD(6)
      post(4);
    } else if (!full) {
    } else if (w == 17) {
      uint32_t tq = clk32();
      FOR_UNITS {
        if (ld_rlx32(&g_fl.oflag[v][sg][kb]) < 4) {
          if (v == (st < NSEG ? 0 : 1) && st < WSTEP - 3) quiet_until(tq);
          wait_count(&g_fl.oflag[v][sg][kb], 4, 84);
          if (v == (st < NSEG ? 0 : 1)) tq = clk32() + QUIET;
        }
        mbar_wait(bars + (KB_EMPTY + (n & 1)) * 8, ((n >> 1) & 1) ^ 1, 83);
        TR(v)
        if (st == WSTEP - 1) { HD(v) }
        if (lane == 0) {
          fence_async_glb();
          mbar_expect_tx(bars + (KB_FULL + (n & 1)) * 8, (WEXP & 4) ? 4096 : 32768);
          bulk_g2s(sb + K_O + (n & 1) * 32768, g_O[(v ? sg + DELTA : sg) & (OSLOTS - 1)][v] + kb * 32768, (WEXP & 4) ? 4096 : 32768, bars + (KB_FULL + (n & 1)) * 8);
        }
        __syncwarp();
      }
    } else if (w == 18) {
      FOR_UNITS {
        if (sg > 0) mbar_wait(bars + (KB_OK + v) * 8, (sg - 1) & 1, 90);
        bar_sync(KN_ST + (n & 1), 288);
        fence_async_smem();
        if (lane == 0) {
          bulk_s2g(g_part[v] + ((sg & 1) * 32 + me) * 8192, sb + K_ST + (n & 1) * 8192, 8192);
          asm volatile("cp.async.bulk.commit_group;" ::: "memory");
          mbar_arrive_z(bars + (KB_EMPTY + (n & 1)) * 8, 0);
          asm volatile("cp.async.bulk.wait_group.read 0;" ::: "memory");
        }
        __syncwarp();
        mbar_arrive_z(bars + (KB_ST + (n & 1)) * 8, lane);
        TR(v)
        const uint32_t tg = clk32() + GATE_R;
        if (v == (st < NSEG ? 0 : 2) && st > 0) mbar_wait(bars + KB_REL * 8, (st - 1) & 1, 93);
        wait_clock(tg);
        if (st == WSTEP - 1) { HD(2 + v) }
        mbar_arrive_z(bars + (KB_GO + v) * 8, lane);
      }
    } else {
#pragma unroll 1
      for (int st = 0; st < WSTEP; st++) {
        const int sg = st < NSEG ? st : st - WD;
        bar_sync(KN_REL, 160);
        const uint32_t ob = __shfl_sync(~0u, lds32(sb + K_LN + 128), 0);
        mbar_arrive_z(bars + KB_REL * 8, lane);
        if (st == WSTEP - 1) { HD(5) }
        if (WEXP & 8) { __nanosleep(500); if (lane == 0) asm volatile("st.relaxed.gpu.global.u64 [%0], %1;" ::"l"(&g_fl.key[st < NSEG ? 0 : 2][sg][me]), "l"((u64)ob << 32 | (uint32_t)~(sg * 32 + me)) : "memory"); }
        else if (lane == 0) st_release_u64(&g_fl.key[st < NSEG ? 0 : 2][sg][me], (u64)ob << 32 | (uint32_t)~(sg * 32 + me));
        __syncwarp();
        TR(0)
      }
    }
  }
}
#undef TRC

bool g_ready;

}

extern "C" void kernel_launch(void* const* d_in, const int* in_sizes, int n_in, void* d_out, int out_size) {
  (void)in_sizes; (void)n_in; (void)out_size;
  const bf16* x0 = (const bf16*)d_in[0];
  const bf16* mem0 = (const bf16*)d_in[1];
  const bf16* Wq = (const bf16*)d_in[2];
  const bf16* Wk = (const bf16*)d_in[3];
  const bf16* Wv = (const bf16*)d_in[4];
  const bf16* Wo = (const bf16*)d_in[5];
  if (!g_ready) {
    cudaFuncSetAttribute(worker_kernel, cudaFuncAttributeMaxDynamicSharedMemorySize, K_SMEM);
    cudaFuncSetAttribute(chain_kernel, cudaFuncAttributeMaxDynamicSharedMemorySize, C_SMEM);
    g_ready = true;
  }
  cudaStream_t st = cudaStreamPerThread;
  prep_kernel<<<NTOK / 8, 256, 0, st>>>(x0, Wq, Wk, Wv, Wo);
  chain_kernel<<<96, 512, C_SMEM, st>>>(Wq, Wk, Wv, Wo, mem0);
  cudaLaunchAttribute pdl[1];
  pdl[0].id = cudaLaunchAttributeProgrammaticStreamSerialization;
  pdl[0].val.programmaticStreamSerializationAllowed = 1;
  WorkerParams wp;
  wp.x0 = x0; wp.Wo = Wo; wp.w_r = (const bf16*)d_in[8]; wp.w_gate = (const bf16*)d_in[9]; wp.w_up = (const bf16*)d_in[10];
  wp.w_down = (const bf16*)d_in[11]; wp.out = (bf16*)d_out;
  cudaLaunchConfig_t cfg = {};
  cfg.gridDim = dim3(NWORK); cfg.blockDim = dim3(640); cfg.dynamicSmemBytes = K_SMEM; cfg.stream = st;
  cfg.attrs = pdl; cfg.numAttrs = 1;
  cudaLaunchKernelEx(&cfg, worker_kernel, wp);
}
```

```cpp
#include <cuda_runtime.h>
#include <cuda_bf16.h>
#include <stdint.h>

namespace {

typedef __nv_bfloat16 bf16;
typedef unsigned long long u64;

constexpr int NTOK = 2048, DM = 512, HD = 4096, NSEG = 64, FF = 1792;
#define DELTA 4
constexpr int NSTEP = NSEG + DELTA;
#define WLAG 1
constexpr int WD = DELTA + WLAG, WSTEP = NSEG + WD;
constexpr int SPIN_LIMIT = 40000;
constexpr int MBAR_LIMIT = 20000;
constexpr int NWORK = 36;
constexpr int OSLOTS = 8;
#define SLP_C 100
#define SLP_K 200
#define WEXP 0

__device__ __align__(1024) uint8_t g_xs[2][NSEG * 32768];
__device__ __align__(1024) uint8_t g_patch[NSEG * 8192];
__device__ __align__(1024) uint8_t g_O[OSLOTS][3][32 * 8192];
__device__ __align__(1024) uint8_t g_part[3][2 * 32 * 8192];
__device__ __align__(1024) bf16 g_rows[NTOK][3][3][DM];
__device__ __align__(1024) bf16 g_x2p[NSEG * DM];
struct Flags {
  uint32_t pol[96];
  uint32_t stamp[96];
  uint32_t oflag[3][NSEG][8];
  uint32_t ffncnt[WSTEP][8];
  uint32_t patch[NSEG][8];
  u64 key[3][NSEG][32];
  float upd[WSTEP][DM];
};
struct Exchange { uint32_t M[4 * 16384], P[96 * 4096]; Flags fl; };
__device__ __align__(65536) Exchange g_ex;
#define g_M g_ex.M
#define g_P g_ex.P
#define g_fl g_ex.fl
#define TR(e)
#define TRV(e, v)
#define TG(i)
#define HD(e)
#define TRDUMP
#define TREXTRA 0

#define STAT(e, v)
#define STATC(n)
#define STATDUMP
__device__ __forceinline__ uint32_t smem_u32(const void* p) { return (uint32_t)__cvta_generic_to_shared(p); }
__device__ __forceinline__ uint32_t pack_bf16(float lo, float hi) {
  uint32_t r;
  asm("cvt.rn.bf16x2.f32 %0, %1, %2;" : "=r"(r) : "f"(hi), "f"(lo));
  return r;
}
__device__ __forceinline__ float bf_lo(uint32_t v) { return __uint_as_float(v << 16); }
__device__ __forceinline__ float bf_hi(uint32_t v) { return __uint_as_float(v & 0xffff0000u); }
__device__ __forceinline__ float ex2_fast(float x) { float y; asm("ex2.approx.ftz.f32 %0, %1;" : "=f"(y) : "f"(x)); return y; }
__device__ __forceinline__ float round_bf16(float x) { return __bfloat162float(__float2bfloat16_rn(x)); }
__device__ __forceinline__ uint32_t clk32() { uint32_t t; asm volatile("mov.u32 %0, %%clock;" : "=r"(t) :: "memory"); return t; }

__device__ __forceinline__ void mma16816(float (&d)[4], uint32_t a0, uint32_t a1, uint32_t a2, uint32_t a3,
                                         uint32_t b0, uint32_t b1) {
  asm("mma.sync.aligned.m16n8k16.row.col.f32.bf16.bf16.f32 {%0,%1,%2,%3}, {%4,%5,%6,%7}, {%8,%9}, {%0,%1,%2,%3};"
      : "+f"(d[0]), "+f"(d[1]), "+f"(d[2]), "+f"(d[3])
      : "r"(a0), "r"(a1), "r"(a2), "r"(a3), "r"(b0), "r"(b1));
}
__device__ __forceinline__ void ldsm4t(uint32_t (&r)[4], uint32_t addr) {
  asm volatile("ldmatrix.sync.aligned.m8n8.x4.trans.shared.b16 {%0,%1,%2,%3}, [%4];"
               : "=r"(r[0]), "=r"(r[1]), "=r"(r[2]), "=r"(r[3]) : "r"(addr) : "memory");
}
__device__ __forceinline__ void stsm4(uint32_t addr, uint32_t a, uint32_t b, uint32_t c, uint32_t d) {
  asm volatile("stmatrix.sync.aligned.m8n8.x4.shared.b16 [%0], {%1,%2,%3,%4};" ::"r"(addr), "r"(a), "r"(b), "r"(c), "r"(d) : "memory");
}
__device__ __forceinline__ void stsm4t(uint32_t addr, uint32_t a, uint32_t b, uint32_t c, uint32_t d) {
  asm volatile("stmatrix.sync.aligned.m8n8.x4.trans.shared.b16 [%0], {%1,%2,%3,%4};" ::"r"(addr), "r"(a), "r"(b), "r"(c), "r"(d) : "memory");
}
__device__ __forceinline__ uint4 lds128(uint32_t a) {
  uint4 v; asm volatile("ld.shared.v4.b32 {%0,%1,%2,%3}, [%4];" : "=r"(v.x), "=r"(v.y), "=r"(v.z), "=r"(v.w) : "r"(a) : "memory"); return v;
}
__device__ __forceinline__ uint32_t lds32(uint32_t a) { uint32_t v; asm volatile("ld.shared.b32 %0, [%1];" : "=r"(v) : "r"(a) : "memory"); return v; }
__device__ __forceinline__ void sts32(uint32_t a, uint32_t x) { asm volatile("st.shared.b32 [%0], %1;" ::"r"(a), "r"(x) : "memory"); }
__device__ __forceinline__ void sts128(uint32_t a, uint4 v) {
  asm volatile("st.shared.v4.b32 [%0], {%1,%2,%3,%4};" ::"r"(a), "r"(v.x), "r"(v.y), "r"(v.z), "r"(v.w) : "memory");
}
__device__ __forceinline__ void cp16(uint32_t dst, const void* src) {
  asm volatile("cp.async.cg.shared.global [%0], [%1], 16;" ::"r"(dst), "l"(src) : "memory");
}
__device__ __forceinline__ void mbar_init(uint32_t mbar, uint32_t cnt) {
  asm volatile("mbarrier.init.shared.b64 [%0], %1;" ::"r"(mbar), "r"(cnt) : "memory");
}
__device__ __forceinline__ void mbar_expect_tx(uint32_t mbar, uint32_t bytes) {
  asm volatile("mbarrier.arrive.expect_tx.shared.b64 _, [%0], %1;" ::"r"(mbar), "r"(bytes) : "memory");
}
__device__ __forceinline__ void mbar_arrive_z(uint32_t mbar, uint32_t z) {
  asm volatile("{ .reg .pred p; setp.eq.u32 p, %1, 0; @p mbarrier.arrive.shared.b64 _, [%0]; }" ::"r"(mbar), "r"(z) : "memory");
}
__device__ __forceinline__ void mbar_expect_tx_z(uint32_t mbar, uint32_t bytes, uint32_t z) {
  asm volatile("{ .reg .pred p; setp.eq.u32 p, %2, 0; @p mbarrier.arrive.expect_tx.shared.b64 _, [%0], %1; }" ::"r"(mbar), "r"(bytes), "r"(z) : "memory");
}
__device__ __forceinline__ void mbar_arrive_remote_z(uint32_t mbar, uint32_t z) {
  asm volatile("{ .reg .pred p; setp.eq.u32 p, %1, 0; @p mbarrier.arrive.shared::cluster.b64 _, [%0]; }" ::"r"(mbar), "r"(z) : "memory");
}
__device__ __forceinline__ void warp_sleep(uint32_t ns) { __nanosleep(ns); __syncwarp(); }
__device__ __forceinline__ void fail(int) { __trap(); }
__device__ __forceinline__ void give_up(int it, int limit, int code) { if (it > limit) fail(code); }
__device__ __forceinline__ void mbar_wait(uint32_t mbar, uint32_t par, int code) {
  asm volatile("{ .reg .pred p; .reg .b32 n; mov.b32 n, %2;\n"
               "W: mbarrier.try_wait.parity.shared::cta.b64 p, [%0], %1; @p bra D;\n"
               "add.s32 n, n, -1; setp.eq.s32 p, n, 0; @p trap; bra W;\n"
               "D: }" ::"r"(mbar), "r"(par), "n"(MBAR_LIMIT) : "memory");
}
__device__ __forceinline__ void bulk_g2s(uint32_t dst, const void* src, uint32_t bytes, uint32_t mbar) {
  asm volatile("cp.async.bulk.shared::cluster.global.mbarrier::complete_tx::bytes [%0], [%1], %2, [%3];"
               ::"r"(dst), "l"(src), "r"(bytes), "r"(mbar) : "memory");
}
__device__ __forceinline__ void bulk_s2r(uint32_t dst, uint32_t src, uint32_t bytes, uint32_t mbar) {
  asm volatile("cp.async.bulk.shared::cluster.shared::cta.mbarrier::complete_tx::bytes [%0], [%1], %2, [%3];"
               ::"r"(dst), "r"(src), "r"(bytes), "r"(mbar) : "memory");
}
__device__ __forceinline__ void bulk_s2g(void* dst, uint32_t src, uint32_t bytes) {
  asm volatile("cp.async.bulk.global.shared::cta.bulk_group [%0], [%1], %2;" ::"l"(dst), "r"(src), "r"(bytes) : "memory");
}
__device__ __forceinline__ void fence_async_smem() { asm volatile("fence.proxy.async.shared::cta;" ::: "memory"); }
__device__ __forceinline__ void fence_async_glb() { asm volatile("fence.proxy.async.global;" ::: "memory"); }
__device__ __forceinline__ void bar_sync(int id, int n) { asm volatile("bar.sync %0, %1;" ::"r"(id), "r"(n) : "memory"); }
__device__ __forceinline__ void bar_arrive(int id, int n) { asm volatile("bar.arrive %0, %1;" ::"r"(id), "r"(n) : "memory"); }
__device__ __forceinline__ void cluster_sync() { asm volatile("barrier.cluster.arrive.release; barrier.cluster.wait.acquire;" ::: "memory"); }
__device__ __forceinline__ uint32_t mapa_u32(uint32_t a, uint32_t r) {
  uint32_t o;
  asm("mapa.shared::cluster.u32 %0, %1, %2;" : "=r"(o) : "r"(a), "r"(r));
  return o;
}
template <int OFF>
__device__ __forceinline__ void st_async32(uint32_t a, uint32_t x, uint32_t mbar) {
  asm volatile("st.async.weak.shared::cluster.mbarrier::complete_tx::bytes.b32 [%0 + %3], %1, [%2];" ::"r"(a), "r"(x), "r"(mbar), "n"(OFF) : "memory");
}
__device__ __forceinline__ uint4 ld_rlx128(const void* p) {
  uint4 v;
  asm volatile("ld.relaxed.gpu.global.v4.u32 {%0,%1,%2,%3}, [%4];" : "=r"(v.x), "=r"(v.y), "=r"(v.z), "=r"(v.w) : "l"(p) : "memory");
  return v;
}
__device__ __forceinline__ uint2 ld_rlx64(const void* p) {
  uint2 v; asm volatile("ld.relaxed.gpu.global.v2.u32 {%0,%1}, [%2];" : "=r"(v.x), "=r"(v.y) : "l"(p) : "memory"); return v;
}
__device__ __forceinline__ uint32_t ld_rlx32(const void* p) {
  uint32_t v; asm volatile("ld.relaxed.gpu.global.u32 %0, [%1];" : "=r"(v) : "l"(p) : "memory"); return v;
}
__device__ __forceinline__ void st_rlx32(void* p, uint32_t a) { asm volatile("st.relaxed.gpu.global.u32 [%0], %1;" ::"l"(p), "r"(a) : "memory"); }
__device__ __forceinline__ void red_release(uint32_t* p) { asm volatile("red.release.gpu.global.add.u32 [%0], 1;" ::"l"(p) : "memory"); }
__device__ __forceinline__ void st_release32(void* p, uint32_t a) { asm volatile("st.release.gpu.global.u32 [%0], %1;" ::"l"(p), "r"(a) : "memory"); }
__device__ __forceinline__ void st_release_u64(void* p, u64 a) { asm volatile("st.release.gpu.global.u64 [%0], %1;" ::"l"(p), "l"(a) : "memory"); }
__device__ __forceinline__ void wait_count(const uint32_t* p, uint32_t val, int code) {
  int it = 0;
  while (ld_rlx32(p) < val) {
    give_up(++it, SPIN_LIMIT, code);
    warp_sleep(SLP_C);
  }
}
__device__ __forceinline__ u64 wait_keys(const u64* keys, int lane, int code) {
  u64 k;
  int it = 0;
  while (true) {
    asm volatile("ld.relaxed.gpu.global.u64 %0, [%1];" : "=l"(k) : "l"(keys + lane) : "memory");
    if (__all_sync(~0u, k != 0)) break;
    give_up(++it, SPIN_LIMIT, code);
    warp_sleep(SLP_K);
  }
  const uint32_t hi = __reduce_max_sync(~0u, (uint32_t)(k >> 32));
  const uint32_t lo = __reduce_max_sync(~0u, (uint32_t)(k >> 32) == hi ? (uint32_t)k : 0u);
  return (u64)hi << 32 | lo;
}
__device__ __forceinline__ int key_token(u64 k) { return (int)(~(uint32_t)k) & (NTOK - 1); }
__device__ __forceinline__ float key_score(u64 k) {
  const uint32_t ob = (uint32_t)(k >> 32);
  return __uint_as_float((ob & 0x80000000u) ? (ob & 0x7fffffffu) : ~ob);
}

__device__ __forceinline__ uint64_t mk_desc(uint32_t saddr, uint32_t lbo, uint32_t sbo, uint32_t sw) {
  return (uint64_t)((saddr & 0x3FFFF) >> 4) | (uint64_t)(lbo >> 4) << 16 | (uint64_t)(sbo >> 4) << 32 | (uint64_t)sw << 62;
}
template <int N> __device__ __forceinline__ void reg_inc() { asm volatile("setmaxnreg.inc.sync.aligned.u32 %0;" ::"n"(N)); }
template <int N> __device__ __forceinline__ void reg_dec() { asm volatile("setmaxnreg.dec.sync.aligned.u32 %0;" ::"n"(N)); }
__device__ __forceinline__ void wg_fence() { asm volatile("wgmma.fence.sync.aligned;" ::: "memory"); }
__device__ __forceinline__ void wg_commit() { asm volatile("wgmma.commit_group.sync.aligned;" ::: "memory"); }
template <int N> __device__ __forceinline__ void wg_wait() { asm volatile("wgmma.wait_group.sync.aligned %0;" ::"n"(N) : "memory"); }
template <int N> __device__ __forceinline__ void acc_fence(float (&d)[N]) {
#pragma unroll
  for (int i = 0; i < N; i++) asm volatile("" : "+f"(d[i]) :: "memory");
}
#define O4(d, i) "+f"(d[i]), "+f"(d[i + 1]), "+f"(d[i + 2]), "+f"(d[i + 3])
template <int TB, int ACC>
__device__ __forceinline__ void wg_rs8(float (&d)[4], const uint32_t (&a)[4], uint64_t db) {
  asm volatile("wgmma.mma_async.sync.aligned.m64n8k16.f32.bf16.bf16 {%0,%1,%2,%3}, {%4,%5,%6,%7}, %8, %9, 1, 1, %10;"
               : O4(d, 0) : "r"(a[0]), "r"(a[1]), "r"(a[2]), "r"(a[3]), "l"(db), "n"(ACC), "n"(TB));
}
template <int TB, int ACC>
__device__ __forceinline__ void wg_rs24(float (&d)[12], const uint32_t (&a)[4], uint64_t db) {
  asm volatile("wgmma.mma_async.sync.aligned.m64n24k16.f32.bf16.bf16 {%0,%1,%2,%3,%4,%5,%6,%7,%8,%9,%10,%11}, {%12,%13,%14,%15}, %16, %17, 1, 1, %18;"
               : O4(d, 0), O4(d, 4), O4(d, 8) : "r"(a[0]), "r"(a[1]), "r"(a[2]), "r"(a[3]), "l"(db), "n"(ACC), "n"(TB));
}
template <int TB, int ACC>
__device__ __forceinline__ void wg_rs32(float (&d)[16], const uint32_t (&a)[4], uint64_t db) {
  asm volatile("wgmma.mma_async.sync.aligned.m64n32k16.f32.bf16.bf16 {%0,%1,%2,%3,%4,%5,%6,%7,%8,%9,%10,%11,%12,%13,%14,%15}, {%16,%17,%18,%19}, %20, %21, 1, 1, %22;"
               : O4(d, 0), O4(d, 4), O4(d, 8), O4(d, 12) : "r"(a[0]), "r"(a[1]), "r"(a[2]), "r"(a[3]), "l"(db), "n"(ACC), "n"(TB));
}
template <int ACC>
__device__ __forceinline__ void wg_rs64(float (&d)[32], uint32_t a0, uint32_t a1, uint32_t a2, uint32_t a3, uint64_t db) {
  asm volatile("wgmma.mma_async.sync.aligned.m64n64k16.f32.bf16.bf16 {%0,%1,%2,%3,%4,%5,%6,%7,%8,%9,%10,%11,%12,%13,%14,%15,"
               "%16,%17,%18,%19,%20,%21,%22,%23,%24,%25,%26,%27,%28,%29,%30,%31}, {%32,%33,%34,%35}, %36, %37, 1, 1, 0;"
               : O4(d, 0), O4(d, 4), O4(d, 8), O4(d, 12), O4(d, 16), O4(d, 20), O4(d, 24), O4(d, 28)
               : "r"(a0), "r"(a1), "r"(a2), "r"(a3), "l"(db), "n"(ACC));
}
template <int ACC>
__device__ __forceinline__ void wg_ss24(float (&d)[12], uint64_t da, uint64_t db) {
  asm volatile("wgmma.mma_async.sync.aligned.m64n24k16.f32.bf16.bf16 {%0,%1,%2,%3,%4,%5,%6,%7,%8,%9,%10,%11}, %12, %13, %14, 1, 1, 1, 0;"
               : O4(d, 0), O4(d, 4), O4(d, 8) : "l"(da), "l"(db), "n"(ACC));
}
template <int ACC>
__device__ __forceinline__ void wg_rs40(float (&d)[20], const uint32_t (&a)[4], uint64_t db) {
  asm volatile("wgmma.mma_async.sync.aligned.m64n40k16.f32.bf16.bf16 {%0,%1,%2,%3,%4,%5,%6,%7,%8,%9,%10,%11,%12,%13,%14,%15,%16,%17,%18,%19}, {%20,%21,%22,%23}, %24, %25, 1, 1, 1;"
               : O4(d, 0), O4(d, 4), O4(d, 8), O4(d, 12), O4(d, 16) : "r"(a[0]), "r"(a[1]), "r"(a[2]), "r"(a[3]), "l"(db), "n"(ACC));
}

struct Row { uint32_t w[8]; };
__device__ __forceinline__ uint32_t add_bf16x2(uint32_t a, uint32_t b) {
  uint32_t d; asm("add.rn.bf16x2 %0, %1, %2;" : "=r"(d) : "r"(a), "r"(b)); return d;
}
__device__ __forceinline__ Row warp_ln(const Row& r, float& extra) {
  float x[16];
#pragma unroll
  for (int i = 0; i < 8; i++) { x[2 * i] = bf_lo(r.w[i]); x[2 * i + 1] = bf_hi(r.w[i]); }
  float m = (((x[0] + x[1]) + (x[2] + x[3])) + ((x[4] + x[5]) + (x[6] + x[7]))) + (((x[8] + x[9]) + (x[10] + x[11])) + ((x[12] + x[13]) + (x[14] + x[15])));
  m *= (1.f / 16);
  float v0 = 0.f, v1 = 0.f;
#pragma unroll
  for (int i = 0; i < 16; i += 2) { const float d0 = x[i] - m, d1 = x[i + 1] - m; v0 = fmaf(d0, d0, v0); v1 = fmaf(d1, d1, v1); }
  float v = v0 + v1;
#pragma unroll
  for (int o = 1; o <= 16; o <<= 1) {
    const float mo = __shfl_xor_sync(~0u, m, o), vo = __shfl_xor_sync(~0u, v, o);
    extra += __shfl_xor_sync(~0u, extra, o);
    const float d = mo - m;
    v = fmaf(d * d, 8.f * o, v + vo);
    m = 0.5f * (m + mo);
  }
  const float var = fmaf(v, 1.f / DM, 1e-5f);
  float rs = rsqrtf(var);
  rs = rs * fmaf(-0.5f * var * rs, rs, 1.5f);
  Row y;
#pragma unroll
  for (int i = 0; i < 8; i++) y.w[i] = pack_bf16((x[2 * i] - m) * rs, (x[2 * i + 1] - m) * rs);
  return y;
}
__device__ __forceinline__ Row warp_ln(const Row& r) { float e = 0.f; return warp_ln(r, e); }
__device__ __forceinline__ Row load_row(const bf16* p, int lane) {
  Row r;
#pragma unroll
  for (int q = 0; q < 4; q++) { const uint2 v = ld_rlx64(p + lane * 4 + q * 128); r.w[2 * q] = v.x; r.w[2 * q + 1] = v.y; }
  return r;
}
__device__ __forceinline__ void store_row(bf16* p, int lane, const Row& r) {
#pragma unroll
  for (int q = 0; q < 4; q++) *(uint2*)(p + lane * 4 + q * 128) = make_uint2(r.w[2 * q], r.w[2 * q + 1]);
}
template <int KB>
__device__ __forceinline__ void store_row_img(uint8_t* img, int rr, int lane, const Row& r) {
  uint8_t* p = img + (lane >> 4) * KB + rr * 128 + ((((lane & 15) >> 1) ^ (rr & 7)) << 4) + (lane & 1) * 8;
#pragma unroll
  for (int q = 0; q < 4; q++) *(uint2*)(p + q * 2 * KB) = make_uint2(r.w[2 * q], r.w[2 * q + 1]);
}

__global__ void __launch_bounds__(256) prep_kernel(const bf16* __restrict__ x0, const bf16* Wq, const bf16* Wk, const bf16* Wv, const bf16* Wo) {
  const int lane = threadIdx.x & 31, row = blockIdx.x * 8 + (threadIdx.x >> 5);
  const Row r = load_row(x0 + (size_t)row * DM, lane);
  const int gt = blockIdx.x * 256 + threadIdx.x, nt = gridDim.x * 256;
  asm volatile("prefetch.global.L2 [%0];" ::"l"((gt & 1 ? Wk : Wq) + (gt >> 1) * 64));
  asm volatile("prefetch.global.L2 [%0];" ::"l"((gt & 1 ? Wo : Wv) + (gt >> 1) * 64));
  uint4* M = (uint4*)g_M;
  for (int i = gt; i < 4 * 16384 / 4; i += nt) M[i] = make_uint4(~0u, ~0u, ~0u, ~0u);
  uint4* P = (uint4*)g_P;
  for (int i = gt; i < 96 * 4096 / 4; i += nt) P[i] = make_uint4(0, 0, 0, 0);
  if (gt < 16384) ((uint4*)(g_part[1] + 32 * 8192))[gt] = make_uint4(0, 0, 0, 0);
  uint4* F = (uint4*)&g_fl;
  for (int i = gt; i < (int)(sizeof(Flags) / 16); i += nt) F[i] = make_uint4(0, 0, 0, 0);
  store_row_img<4096>(g_xs[0] + (size_t)(row >> 5) * 32768, row & 31, lane, warp_ln(r));
}

constexpr int W_STRIDE = 272;
constexpr int C_WO = 0;
constexpr int C_X = 49152;
constexpr int C_M = C_X + 9 * 8192;
constexpr int C_Q = C_M + 24576;
constexpr int C_K = C_Q + 10240, C_V = C_K + 10240;
constexpr int C_SA = C_V + 10240, C_SB = C_SA + 8192, C_SP = C_SB + 8192;
constexpr int C_O = C_SP + 2048;
constexpr int C_OT = C_O + 6144;
constexpr int C_BAR = C_OT + 16384;
constexpr int C_SMEM = C_BAR + 256 + (TREXTRA > 9000 ? TREXTRA : 1024 + TREXTRA);
static_assert(C_X + 512 * W_STRIDE <= C_OT, "staging");
enum { B_M0 = 0, B_M1, B_M2, B_R, B_X = B_R + 4, B_O, B_T, B_F, B_XL, B_XL3, B_P1, B_P2, B_P3, B_OT, B_XF, B_I, B_NUM };
constexpr int C_INFO = C_BAR + 176, C_POL = C_BAR + 208;
enum { NB_ALL = 0, NB_M0, NB_PV, NB_W0, NB_TA, NB_X1, NB_M1, NB_M2, NB_RD, NB_XB };
constexpr float SCALE_LOG2E = 0.08838834764831845f * 1.4426950408889634f;
#define N0STEPS 9
#define N2STEPS 11
#define FGATE 1
constexpr int K3 = 32 - N0STEPS - N2STEPS;
static_assert(K3 % 4 == 0, "the rows of layer 1 are refilled in two parts");
#define BGATE 0
#define IGRP 0
#define SHIPLATE 7
#define SHIP 1024
#define GATE_P 2300
#define GATE_W 200
#define EXPF 0
#define GATE_G 200
#define GATE_M 3400
#define HOLE0 24
#define HOLE1 32
#define HOLE2 32
__device__ __forceinline__ uint32_t gtime() { uint32_t t; asm volatile("mov.u32 %0, %%globaltimer_lo;" : "=r"(t) :: "memory"); return t; }
__device__ __forceinline__ void wait_clock(uint32_t t) {
  asm volatile("{ .reg .pred p; .reg .b32 c; .reg .b64 cc;\nL: mov.u64 cc, %%clock64; cvt.u32.u64 c, cc; sub.u32 c, c, %0; setp.lt.s32 p, c, 0; @p bra L; }" ::"r"(t) : "memory");
}
__device__ __forceinline__ bool bar_or(int id, int n, uint32_t v) {
  uint32_t r;
  asm volatile("{ .reg .pred p, q; setp.ne.u32 p, %1, 0; bar.red.or.pred q, %2, %3, p; vote.sync.any.pred q, q, 0xffffffff; selp.u32 %0, 1, 0, q; }"
               : "=r"(r) : "r"(v), "r"(id), "r"(n) : "memory");
  return r;
}
__device__ __forceinline__ void bar_sync_z(int id, int n, uint32_t z) {
  asm volatile("{ .reg .pred p; setp.eq.u32 p, %2, 0; @p bar.sync %0, %1; }" ::"r"(id), "r"(n), "r"(z) : "memory");
}

__device__ __forceinline__ uint32_t probe_polarity(uint32_t* p, int lane) {
  uint32_t best[2] = {~0u, ~0u};
#pragma unroll 1
  for (int rep = 0; rep < 3; rep++) {
#pragma unroll
    for (int pg = 0; pg < 2; pg++) {
      uint32_t t0, t1, v = 0;
      asm volatile("mov.u32 %0, %%clock;" : "=r"(t0) :: "memory");
      asm volatile("{ .reg .pred p; setp.eq.u32 p, %2, 0; @p atom.relaxed.gpu.global.add.u32 %0, [%1], 0; }" : "+r"(v) : "l"(p + pg * 1024), "r"(lane) : "memory");
      asm volatile("{ .reg .pred p; setp.ne.u32 p, %1, 0x13572468; mov.u32 %0, 0; @p mov.u32 %0, %%clock; }" : "=r"(t1) : "r"(v) : "memory");
      if (rep > 0) best[pg] = min(best[pg], t1 - t0);
    }
  }
  return __shfl_sync(~0u, best[1] < best[0] ? 1u : 0u, 0);
}
__device__ __forceinline__ uint32_t ppage(uint32_t lp, uint32_t pol) { return lp ? 3 - pol : pol; }
__device__ __forceinline__ uint32_t and_x(uint32_t a, uint32_t b, uint32_t m) {
  uint32_t d; asm("lop3.b32 %0, %1, %2, %3, 0x42;" : "=r"(d) : "r"(a), "r"(b), "r"(m)); return d;
}
__device__ __forceinline__ uint32_t and3(uint32_t a, uint32_t b, uint32_t c) {
  uint32_t d; asm("lop3.b32 %0, %1, %2, %3, 0x80;" : "=r"(d) : "r"(a), "r"(b), "r"(c)); return d;
}

template <int N> struct IC { static constexpr int value = N; };
template <class F> __device__ __forceinline__ void static_for2(F f) { f(IC<0>()); f(IC<1>()); }
template <class F> __device__ __forceinline__ void static_for3(F f) { f(IC<0>()); f(IC<1>()); f(IC<2>()); }
__device__ __forceinline__ void load_wfrags(uint32_t (&wA)[32][4], uint32_t stage, int w, int lane) {
  const int mi = lane >> 3, r = lane & 7;
#pragma unroll
  for (int ks = 0; ks < 32; ks++) ldsm4t(wA[ks], stage + (ks * 16 + (mi >> 1) * 8 + r) * W_STRIDE + (w * 16 + (mi & 1) * 8) * 2);
}
template <int K0, int K1>
__device__ __forceinline__ void tok_seq(float (&d)[16], const uint32_t (&wA)[32][4], uint64_t desc, uint32_t wave) {
#pragma unroll
  for (int k = K0; k < K1; k++) {
    const int ks = k & 31;
    constexpr int HM0 = 1, HM1 = 2, HM2 = 4;
    const int hm = (k == HOLE0 ? HM0 : 0) | (k == HOLE1 ? HM1 : 0) | (k == HOLE2 ? HM2 : 0);
    if (hm) bar_sync_z(NB_RD, 384, ((hm >> wave) & 1) ^ 1);
    if (ks == 0) wg_rs32<0, 0>(d, wA[ks], desc);
    else wg_rs32<0, 1>(d, wA[ks], desc + (ks >> 2) * 256 + (ks & 3) * 2);
  }
}
template <int K0, int K1>
__device__ __forceinline__ void mem_part(float (&d)[12], const uint32_t (&wA)[32][4], uint64_t desc) {
#pragma unroll
  for (int ks = K0; ks < K1; ks++) {
    if (ks == 0) wg_rs24<1, 0>(d, wA[ks], desc);
    else wg_rs24<1, 1>(d, wA[ks], desc + ks * 48);
  }
}
__device__ __forceinline__ void out_tile(float (&d)[12], uint64_t da, uint64_t db) {
#pragma unroll
  for (int i = 0; i < 8; i++) { if (i == 0) wg_ss24<0>(d, da, db); else wg_ss24<1>(d, da + i * 128, db + (i >> 1) * 32 + (i & 1) * 2); }
}
__device__ __forceinline__ void tok_pack(uint32_t (&p)[8], const float (&d)[16]) {
#pragma unroll
  for (int i = 0; i < 8; i++) p[i] = pack_bf16(d[2 * i], d[2 * i + 1]);
}
__device__ __forceinline__ void tok_store(uint32_t dst, const uint32_t (&p)[8]) {
  stsm4(dst, p[0], p[1], p[2], p[3]);
  stsm4(dst + 4096, p[4], p[5], p[6], p[7]);
}
template <class T> __device__ __forceinline__ T keep(T v) { asm volatile("" : "+r"(v)); return v; }
__device__ __forceinline__ uint32_t pin(uint32_t v) { return __shfl_sync(~0u, v, threadIdx.x & 31); }

#define TRC blockIdx.x
#define TRS (C_BAR + 256)
__device__ __forceinline__ void chain_proj(const uint32_t sb, const int w, const int lane_, const uint32_t rank) {
  uint32_t wA[32][4];
  load_wfrags(wA, sb + C_X, w, lane_);
  bar_sync(NB_ALL, 512);
  bar_sync(NB_ALL, 512);
  cluster_sync();
  const int lane = pin(lane_);
  const uint32_t bars = sb + C_BAR;
  const uint32_t quad = pin(sb + (lane_ >> 4) * 2048 + (lane_ & 15) * 16);
  const uint32_t own = C_Q + rank * 10240;
  const uint64_t dX1 = mk_desc(sb + C_X, 16, 1024, 1), dX2 = dX1 + 2048, dX3 = dX1 + 4096;
  const uint64_t dM = mk_desc(sb + C_M, 128, 256, 0);
  const uint32_t r1 = rank == 0 ? 1 : 0, r2 = rank == 2 ? 1 : 2;
  const uint32_t xa = pin(sb + own + 8192 + w * 256 + lane_ * 4);
  const uint32_t a1x = pin(mapa_u32(xa, r1)), a2x = pin(mapa_u32(xa, r2));
  const uint32_t b1x = pin(mapa_u32(bars + B_X * 8, r1)), b2x = pin(mapa_u32(bars + B_X * 8, r2));
  const uint32_t wave = rank == 2 ? 0 : rank + 1;
  uint32_t npatch = 0;
  float a[16];
  bar_sync(NB_X1, 288);
  wg_fence();
  tok_seq<32, 32 + K3>(a, wA, dX1, 3);
  wg_commit();
  wg_wait<0>();
#pragma unroll 1
  for (int st = 0; st < NSTEP; st++) {
    uint32_t pk[8];
    bar_sync(NB_XB, 288);
    wg_fence();
    tok_seq<32 + K3, 32 + K3 + N0STEPS>(a, wA, dX1, 3);
    TR(0)
    bar_sync(NB_PV, 384);
    tok_seq<32 + K3 + N0STEPS, 64>(a, wA, dX1, 3);
    wg_commit();
    wg_wait<0>();
    acc_fence(a);
    mbar_arrive_z(bars + B_XF * 8, lane);
    tok_pack(pk, a);
    TR(1)
    bar_sync(NB_W0, 416);
    tok_store(quad + w * 256 + (rank == 0 ? own : C_SA), pk);
    __syncwarp();
    mbar_arrive_z(bars + B_P1 * 8, lane);
    wg_fence();
    tok_seq<0, 32>(a, wA, dX2, wave);
    wg_commit();
    const uint32_t info = lds32(sb + C_INFO + (st & 1) * 4);
    TR(2)
    wg_wait<0>();
    acc_fence(a);
    TR(3)
    tok_pack(pk, a);
    tok_store(quad + w * 256 + (rank == 0 ? C_SA : own), pk);
    if (rank == 2) tok_store(quad + w * 256 + C_SB, pk);
    __syncwarp();
    mbar_arrive_z(bars + B_P2 * 8, lane);
    if (__builtin_expect(info & 4, 0)) {
      float a3[4];
      mbar_wait(bars + B_XL3 * 8, npatch & 1, 32);
      npatch++;
      wg_fence();
#pragma unroll
      for (int ks = 0; ks < 32; ks++) {
        if (ks == 0) wg_rs8<0, 0>(a3, wA[ks], dX3);
        else wg_rs8<0, 1>(a3, wA[ks], dX3 + (ks >> 2) * 64 + (ks & 3) * 2);
      }
      wg_commit();
      wg_wait<0>();
      acc_fence(a3);
      const uint32_t dst = sb + (rank == 2 ? own + (info & 3) * 2048 : C_SP) + w * 256 + lane * 4;
      sts32(dst, pack_bf16(a3[0], a3[1])); sts32(dst + 128, pack_bf16(a3[2], a3[3]));
      __syncwarp();
      mbar_arrive_z(bars + B_P3 * 8, lane);
    }
    TR(4)
    wg_fence();
    tok_seq<32, 32 + K3>(a, wA, dX1, wave);
    TR(6)
    {
      float am[12];
      bar_sync(NB_M0, 384);
      mem_part<0, 10>(am, wA, dM);
      TR(7)
      bar_sync(NB_M1, 384);
      mem_part<10, 21>(am, wA, dM);
      const bool redo = bar_or(NB_M2, 384, 0);
      mem_part<21, 32>(am, wA, dM);
      wg_commit();
      wg_wait<0>();
      if (__builtin_expect(redo, 0)) {
        bar_sync(NB_M0, 384);
        wg_fence();
        mem_part<0, 32>(am, wA, dM);
        wg_commit();
        wg_wait<0>();
      }
      acc_fence(am);
      TR(8)
      const uint32_t x00 = pack_bf16(am[0], am[1]), x01 = pack_bf16(am[2], am[3]), x10 = pack_bf16(am[4], am[5]), x11 = pack_bf16(am[6], am[7]);
      uint32_t x20 = pack_bf16(am[8], am[9]), x21 = pack_bf16(am[10], am[11]);
      if (info & 4) { x20 = x10; x21 = x11; }
      st_async32<0>(a1x, rank == 0 ? x10 : x00, b1x); st_async32<0>(a2x, rank == 2 ? x10 : x20, b2x);
      st_async32<128>(a1x, rank == 0 ? x11 : x01, b1x); st_async32<128>(a2x, rank == 2 ? x11 : x21, b2x);
      sts32(xa, rank == 0 ? x00 : rank == 2 ? x20 : x10); sts32(xa + 128, rank == 0 ? x01 : rank == 2 ? x21 : x11);
      __syncwarp();
      mbar_arrive_z(bars + B_X * 8, lane);
    }
    TR(9)
  }
}

__device__ __forceinline__ void chain_mem(const uint32_t sb, const int w, const int lane_, const uint32_t rank, const int h,
                                          const bf16* __restrict__ mem0) {
  const int lane = pin(lane_);
  const int wave = rank == 2 ? 0 : rank + 1;
  const int c = w - 8, t = c * 32 + lane, b = wave * 32 + h;
  const uint32_t bars = sb + C_BAR;
  const int wi = (lane & 1) * 2 + (lane >> 4), cq = (lane >> 2) & 3;
  bar_sync(NB_ALL, 512);
#pragma unroll 1
  for (int i = c; i < 16; i += 4) {
    uint32_t r[4];
    ldsm4t(r, sb + C_OT + i * 512 + lane * 16);
    const uint32_t a = sb + C_M + (2 * i + (lane >> 4)) * 768 + (lane & 15) * 16;
    stsm4(a, r[0], r[1], r[2], r[3]); stsm4(a + 256, r[0], r[1], r[2], r[3]); stsm4(a + 512, r[0], r[1], r[2], r[3]);
  }
  fence_async_smem();
  mbar_expect_tx_z(bars + B_X * 8, 4096, t); mbar_expect_tx_z(bars + B_O * 8, 4096, t);
  bar_sync(NB_ALL, 512);
  cluster_sync();
  bar_arrive(NB_PV, 384); bar_arrive(NB_W0, 416); bar_arrive(NB_M0, 384); bar_arrive(NB_M1, 384);
  bar_arrive(NB_RD, 384);

  sts32(sb + C_POL + c * 4, probe_polarity(g_M + c * 16384 + (blockIdx.x & 31) * 32, lane));
  uint32_t pgbits, polP;
  {
    const int tl = lane / 3, u = ((tl * 3 + rank) * 4 + c) * 3 + (lane - tl * 3);
    uint32_t pol;
    int it = 0;
    do { pol = ld_rlx32(&g_fl.pol[lane < 9 && u < 96 ? u : b]); give_up(it++, SPIN_LIMIT, 40); } while (__any_sync(~0u, pol == 0));
    pgbits = __reduce_or_sync(~0u, lane < 9 ? ppage(h >> 4, (pol - 1) & 1) << (2 * lane) : 0u);
    polP = __shfl_sync(~0u, pol - 1, 9);
  }
  const int mi = lane >> 3;
  const uint32_t l16 = pin(sb + lane * 16);
  const uint32_t r1 = rank == 2 ? 0 : rank + 1, r2 = rank == 0 ? 2 : rank - 1;
  const uint32_t oa = pin(sb + C_O + rank * 2048 + (lane >> 2) * 64 + (((lane & 3) ^ (lane >> 3)) << 4));
  const uint32_t a1 = mapa_u32(oa, r1), b1 = mapa_u32(bars + B_O * 8, r1), a2 = mapa_u32(oa, r2), b2 = mapa_u32(bars + B_O * 8, r2);
  const uint64_t dWo = mk_desc(sb + C_WO, 8192, 1024, 1), dO = mk_desc(sb + C_O, 16, 2048, 2);
  const uint64_t dK = mk_desc(sb + C_K, 128, 2048, 0);
  const uint64_t dV = mk_desc(sb + C_V, 2048, 128, 0), dVm = mk_desc(sb + C_V + 8192, 0, 128, 0);
  const uint32_t qa = pin(sb + C_Q + (c ? c + 1 : mi & 1) * 2048 + (mi >> 1) * 128 + (lane & 7) * 16);
  const uint32_t dg = ((lane >> 2) < 2 * (lane & 3) ? 1 : 0) | ((lane >> 2) < 2 * (lane & 3) + 1 ? 2 : 0);
  const uint32_t msk = pin(c == 0 ? dg | dg << 4 : c == 1 ? dg << 2 | 3 << 4 : c == 2 ? dg << 4 : 0);
  uint8_t* Pw = (uint8_t*)g_P + (rank * 4 + c) * 3 * 16384 + (h & 15) * 256 + lane * 4;
  const uint8_t* Pr0 = (const uint8_t*)g_P + b * 16384 + ((lane >> 4) * 4 + (lane & 3)) * 256 + c * 64 + cq * 16 + ppage(0, polP) * 4096;
  const uint8_t* Pr1 = Pr0 + (3 - 2 * polP) * 4096;
  uint8_t* Mw = (uint8_t*)g_M + (b >> 5) * 16384 + ((lane & 2) ? 4096 : 12288) + (b & 31) * 256 + c * 64 + cq * 16 + wi * 4;
  uint32_t nretry = 0;
  const uint32_t gate_p = GATE_P + wave * GATE_W;

  (void)bar_or(NB_M2, 384, 0);
#pragma unroll 1
  for (int st = 0;; st++) {
    mbar_wait(bars + B_T * 8, st & 1, 42);
    STAT(10, clk32())
    {
      float s[20];
      {
        uint32_t q[8][4];
        if (c == 3) mbar_wait(bars + B_X * 8, st & 1, 41);
#pragma unroll
        for (int i = 0; i < 8; i++) ldsm4t(q[i], qa + i * 256);
        if (c != 3) mbar_wait(bars + B_X * 8, st & 1, 41);
        STAT(11, clk32())
        fence_async_smem();
        TR(0)
        wg_fence();
#pragma unroll
        for (int i = 0; i < 8; i++) { if (i == 0) wg_rs40<0>(s, q[i], dK); else wg_rs40<1>(s, q[i], dK + i * 16); }
        wg_commit();
        wg_wait<0>();
        acc_fence(s);
      }
      TR(1)
      const bool w0 = c == 0;
      float z[10] = {s[16], s[17], s[0], s[1], w0 ? s[18] : s[4], w0 ? s[19] : s[5], w0 ? s[2] : s[8], w0 ? s[3] : s[9], w0 ? s[6] : s[12], w0 ? s[7] : s[13]};
      if (msk & 1) z[2] = -INFINITY;
      if (msk & 2) z[3] = -INFINITY;
      if (msk & 4) z[6] = -INFINITY;
      if (msk & 8) z[7] = -INFINITY;
      if (msk & 16) z[8] = -INFINITY;
      if (msk & 32) z[9] = -INFINITY;
      float m0 = fmaxf(fmaxf(z[0], z[1]), fmaxf(z[2], z[3])), m1 = fmaxf(fmaxf(fmaxf(z[4], z[5]), fmaxf(z[6], z[7])), fmaxf(z[8], z[9]));
      m0 = fmaxf(m0, __shfl_xor_sync(~0u, m0, 1)); m1 = fmaxf(m1, __shfl_xor_sync(~0u, m1, 1));
      m0 = fmaxf(m0, __shfl_xor_sync(~0u, m0, 2)); m1 = fmaxf(m1, __shfl_xor_sync(~0u, m1, 2));
      if (!w0) m0 = m1 = fmaxf(m0, m1);
      m0 *= -SCALE_LOG2E; m1 *= -SCALE_LOG2E;
      uint32_t p[5];
#pragma unroll
      for (int k = 0; k < 5; k++) {
        z[2 * k] = ex2_fast(fmaf(z[2 * k], SCALE_LOG2E, k < 2 ? m0 : m1)); z[2 * k + 1] = ex2_fast(fmaf(z[2 * k + 1], SCALE_LOG2E, k < 2 ? m0 : m1));
        p[k] = pack_bf16(z[2 * k], z[2 * k + 1]);
      }
      const uint32_t p2 = w0 ? 0 : p[2], p3 = w0 ? 0 : p[3], p4 = w0 ? 0 : p[4];
      float oA[32], oB[32];
      wg_fence();
      wg_rs64<0>(oA, p[0], p[2], 0, 0, dVm); wg_rs64<1>(oA, p[1], p[3], p2, p[4], dV); wg_rs64<1>(oA, p3, 0, p4, 0, dV + 256);
      wg_commit();
      wg_rs64<0>(oB, p[0], p[2], 0, 0, dVm + 64); wg_rs64<1>(oB, p[1], p[3], p2, p[4], dV + 64); wg_rs64<1>(oB, p3, 0, p4, 0, dV + 320);
      wg_commit();
      float l0 = (z[0] + z[1]) + (z[2] + z[3]), l1 = ((z[4] + z[5]) + (z[6] + z[7])) + (z[8] + z[9]);
      if (!w0) l0 += l1;
      l0 += __shfl_xor_sync(~0u, l0, 1); l1 += __shfl_xor_sync(~0u, l1, 1);
      l0 += __shfl_xor_sync(~0u, l0, 2); l1 += __shfl_xor_sync(~0u, l1, 2);
      float i0, i1;
      asm volatile("rcp.approx.ftz.f32 %0, %2; rcp.approx.ftz.f32 %1, %3;" : "=f"(i0), "=f"(i1) : "f"(l0), "f"(l1));
      const bool mrows = c == 3 && st < NSTEP - 1;
      auto send = [&](const float (&o)[32], auto hc) {
        constexpr int H = decltype(hc)::value;
        static_for2([&](auto bc) {
          constexpr int B = decltype(bc)::value, J = 16 * B;
          asm volatile("st.async.weak.shared::cluster.mbarrier::complete_tx::bytes.v4.b32 [%0 + %9], {%5,%6,%7,%8}, [%1];\n"
                       "st.async.weak.shared::cluster.mbarrier::complete_tx::bytes.v4.b32 [%2 + %9], {%5,%6,%7,%8}, [%3];\n"
                       "st.shared.v4.b32 [%4 + %9], {%5,%6,%7,%8};"
                       ::"r"(a1), "r"(b1), "r"(a2), "r"(b2), "r"(oa), "r"(pack_bf16(o[J] * i0, o[J + 1] * i0)), "r"(pack_bf16(o[J + 4] * i0, o[J + 5] * i0)),
                         "r"(pack_bf16(o[J + 8] * i0, o[J + 9] * i0)), "r"(pack_bf16(o[J + 12] * i0, o[J + 13] * i0)), "n"(H * 1024 + B * 512) : "memory");
        });
      };
      auto keep_tok = [&](uint32_t ta, int R, float iv) {
#pragma unroll
        for (int k = 0; k < 4; k++) {
          const float (&o)[32] = k < 2 ? oA : oB;
          const int J = (k & 1) * 16 + R;
          stsm4(ta + k * 512, pack_bf16(o[J] * iv, o[J + 1] * iv), pack_bf16(o[J + 4] * iv, o[J + 5] * iv),
                pack_bf16(o[J + 8] * iv, o[J + 9] * iv), pack_bf16(o[J + 12] * iv, o[J + 13] * iv));
        }
      };
      wg_wait<1>();
      acc_fence(oA);
      if (mrows) send(oA, IC<0>());
      wg_wait<0>();
      acc_fence(oB);
      if (mrows) {
        send(oB, IC<1>());
        bar_arrive(NB_PV, 384);
        __syncwarp();
        mbar_arrive_z(bars + B_O * 8, lane);
      } else if (c < 3) {
        if (st < NSTEP - 1) bar_arrive(NB_PV, 384);
        const uint32_t ta = l16 + C_OT + (st & 1) * 8192;
        keep_tok(ta + (c ? c + 1 : 0) * 2048, 0, i0);
        if (w0) keep_tok(ta + 2048, 2, i1);
        __syncwarp();
        mbar_arrive_z(bars + B_OT * 8, lane);
      }
      TR(2)
      if (st == NSTEP - 1) break;
      mbar_expect_tx_z(bars + B_X * 8, 4096, t);
    }
    uint32_t tref;
    {
      const uint32_t tag = (st & 1) ^ 1;
      float oc0[12], oc1[12], oc2[12];
      mbar_wait(bars + B_O * 8, st & 1, 43);
      fence_async_smem();
      TR(3)
      wg_fence();
      out_tile(oc0, dWo, dO);
      wg_commit();
      out_tile(oc1, dWo + 1024, dO);
      wg_commit();
      asm volatile("" : "+r"(pgbits));
      auto put = [&](const float (&oc)[12], auto tlc) {
        constexpr int TL = decltype(tlc)::value;
        static_for3([&](auto jc) {
          constexpr int j = decltype(jc)::value;
          uint8_t* p = Pw + ((pgbits >> (2 * (TL * 3 + j))) & 3) * 4096;
          asm volatile("st.relaxed.gpu.global.u32 [%0 + %3], %1; st.relaxed.gpu.global.u32 [%0 + %3 + 128], %2;" ::"l"(p),
                       "r"((pack_bf16(oc[4 * j], oc[4 * j + 1]) & ~1u) | tag), "r"((pack_bf16(oc[4 * j + 2], oc[4 * j + 3]) & ~1u) | tag),
                       "n"((TL * 36 + j) * 16384) : "memory");
        });
      };
      wg_wait<1>();
      acc_fence(oc0);
      put(oc0, IC<0>());
      sts32(sb + C_INFO + 24, clk32());
      TR(4)
      out_tile(oc2, dWo + 2048, dO);
      wg_commit();
      wg_wait<1>();
      acc_fence(oc1);
      put(oc1, IC<1>());
      bar_sync(NB_TA, 160);
      tref = lds32(sb + C_INFO + 12);
      TR(5)
      wg_wait<0>();
      bar_arrive(NB_W0, 416);
      acc_fence(oc2);
      if (rank != 2) put(oc2, IC<2>());
      mbar_arrive_remote_z(((t & 1) ? b2 : b1) + (B_F - B_O) * 8, t >> 1);
      mbar_expect_tx_z(bars + B_O * 8, 4096, t);
      TR(6)
    }
    const int sn = (st + 1) & 3;
    {
      const uint32_t flip = (st & 1) ? ~0u : 0u;
      const bool u16 = lane & 16;
      uint8_t* mw = Mw + sn * 65536;
      asm volatile("" : "+l"(mw));
      const uint32_t bs = (lane & 4) ? 0x3f800000u : 0x00003f80u, bs0 = (lane & 8) ? 0u : bs, bs1 = (lane & 8) ? bs : 0u;
      const bool early = st < DELTA && b % 3 != 0;
      uint32_t m0word = 0;
      if (__builtin_expect(early, 0)) {
        const unsigned short* mp = (const unsigned short*)mem0 + ((lane & 1) * 4 + (lane >> 4) * 2) * DM + b / 3 * 16 + c * 4 + ((lane >> 2) & 3);
        m0word = (uint32_t)mp[0] | (uint32_t)mp[DM] << 16;
      }
      STATC(c_rdy)
      wait_clock(tref + gate_p);
      TR(7)
      uint32_t mword;
      int it = 0;
      bool all;
#pragma unroll 1
      do {
        const uint4 q0 = ld_rlx128(Pr0), q1 = ld_rlx128(Pr0 + 2048), q2 = ld_rlx128(Pr1), q3 = ld_rlx128(Pr1 + 2048);
        float d0[4] = {0.f, 0.f, 0.f, 0.f}, d1[4] = {0.f, 0.f, 0.f, 0.f};
        mma16816(d0, q0.x, q0.y, q0.z, q0.w, bs0, bs1);
        mma16816(d1, q1.x, q1.y, q1.z, q1.w, bs0, bs1);
        mma16816(d0, q2.x, q2.y, q2.z, q2.w, bs0, bs1);
        mma16816(d1, q3.x, q3.y, q3.z, q3.w, bs0, bs1);
        all = __all_sync(~0u, (int)and3(and_x(q0.x, q1.x, flip), and_x(q2.x, q3.x, flip), 1u));
        const float a0 = d0[0] + d1[0], a1 = d0[1] + d1[1], a2 = d0[2] + d1[2], a3 = d0[3] + d1[3];
        mword = pack_bf16((u16 ? a2 : a0) + __shfl_xor_sync(~0u, u16 ? a0 : a2, 16), (u16 ? a3 : a1) + __shfl_xor_sync(~0u, u16 ? a1 : a3, 16));
        asm volatile("{ .reg .pred p; setp.ne.u32 p, %2, 0; @p st.relaxed.gpu.global.u32 [%0], %1; }" ::"l"(mw), "r"(early ? m0word : mword), "r"((uint32_t)all) : "memory");
      } while (__builtin_expect(!all, 0) && ++it < SPIN_LIMIT);
      bar_arrive(NB_RD, 384);
      STATC(c_mst)
      STAT(0, lds32(sb + C_INFO + 24) - tref) STAT(1, c_rdy - tref) STAT(2, c_mst - tref) STAT(3, tref) STAT(4, it)
      if (!all) fail(44);
      TRV(14, it)
    }
    TR(9)
    {
      const uint32_t ma = l16 + C_M + c * 2048 + mi * 4;
      auto scan = [&](uint32_t m, uint32_t a) { return __vimax3_u32(__vimax3_u32(m, lds32(a), lds32(a + 512)), lds32(a + 1024), lds32(a + 1536)); };
      mbar_wait(bars + B_M0 * 8, (st + 1) & 1, 45);
      bar_arrive(NB_M0, 384);
      STATC(c_g0)
      TR(10)
      uint32_t m = scan(0, ma);
      mbar_wait(bars + B_M1 * 8, (st + 1) & 1, 46);
      bar_arrive(NB_M1, 384);
      STATC(c_g1)
      TR(11)
      m = scan(m, ma + 8192);
      mbar_wait(bars + B_M2 * 8, (st + 1) & 1, 47);
      STATC(c_g2)
      TR(12)
      int it = 0;
      const bool redo = bar_or(NB_M2, 384, scan(m, ma + 16384) == ~0u);
      if (__builtin_expect(redo, 0)) {
#pragma unroll 1
        for (int g = 0; g < 3;) {
          if (!__any_sync(~0u, scan(0, ma + g * 8192) == ~0u)) { g++; continue; }
          give_up(++it, SPIN_LIMIT, 48);
          if (lane == 0) {
            mbar_expect_tx(bars + (B_R + c) * 8, 2048);
            bulk_g2s(sb + C_M + g * 8192 + c * 2048, (const uint8_t*)g_M + sn * 65536 + (lds32(sb + C_POL + sn * 4) ? 4096 : 12288) + g * 16384 + c * 2048,
                     2048, bars + (B_R + c) * 8);
          }
          __syncwarp();
          mbar_wait(bars + (B_R + c) * 8, nretry++ & 1, 49);
        }
        bar_arrive(NB_M0, 384);
      }
      STAT(5, c_g0 - tref) STAT(7, c_g1 - tref) STAT(8, c_g2 - tref)
      STAT(9, clk32() - tref) STAT(6, it + redo * 256)
      TR(13)
      TRV(15, it)
      st_rlx32(Mw + (st & 3) * 65536, ~0u);
    }
  }
}

__device__ __forceinline__ void chain_dma(const uint32_t sb, const int w, const int lane, const uint32_t rank, const int h) {
  const uint32_t bars = sb + C_BAR;
  bar_sync(NB_ALL, 512);
  if (w == 12) { HD(3) }
  bar_sync(NB_ALL, 512);
  if (w == 12) { HD(4) }
  cluster_sync();
  if (w == 12) { HD(5) }
  const int expf_ = EXPF;
  if (w == 12) {
    u64 best = 0;
    uint32_t npatch = 0, nx = 0;
    auto load = [&](uint32_t dst, const uint8_t* src, uint32_t bytes) {
      mbar_expect_tx_z(bars + B_XL * 8, bytes, lane >> 1);
      if (lane < 2 && bytes) {
        fence_async_glb();
        bulk_g2s(sb + dst, src, bytes, bars + B_XL * 8);
      }
      __syncwarp();
      mbar_wait(bars + B_XL * 8, nx++ & 1, 52);
    };
    load(C_X + lane * 16384, g_xs[0] + lane * 16384, 16384);
    HD(6)
    bar_arrive(NB_X1, 288); bar_arrive(NB_XB, 288);
#pragma unroll 1
    for (int st = 0; st < NSTEP; st++) {
      const int sg = st - DELTA;
      const bool more = st + 1 < NSEG && !(expf_ & 4);
      uint32_t info = 0;
      if (sg >= 0) {
        const u64 k = wait_keys(g_fl.key[0][sg], lane, 50);
        if (k > best) { best = k; info = 4 | ((key_token(k) >> 3) & 3); }
      }
      TR(0)
      mbar_wait(bars + (st ? B_X : B_XF) * 8, (st - 1 + !st) & 1, 58);
      sts32(sb + C_INFO + (st & 1) * 4, info);
      TR(1)
      load(lane ? C_X : C_X + 32768, lane ? g_xs[0] + (st + 1) * 32768 : g_xs[1] + sg * 32768, lane ? (more ? K3 * 1024 : 0) : (sg >= 0 && !(expf_ & 8) ? 32768 : 0));
      bar_arrive(NB_W0, 416);
      TR(2)
      if (__builtin_expect(info, 0)) {
        if (npatch > 0) mbar_wait(bars + B_P3 * 8, (npatch - 1) & 1, 55);
        npatch++;
        wait_count(g_fl.patch[sg], 1, 56);
        if (lane == 0) {
          fence_async_glb();
          mbar_expect_tx(bars + B_XL3 * 8, 8192);
          bulk_g2s(sb + C_X + 65536, g_patch + (size_t)sg * 8192, 8192, bars + B_XL3 * 8);
        }
        __syncwarp();
      }
      if (st == NSTEP - 1) break;
      mbar_wait(bars + B_XF * 8, st & 1, 53);
      mbar_wait(bars + (B_M0 + BGATE) * 8, st & 1, 54);
      load(C_X + K3 * 1024, g_xs[0] + (st + 1) * 32768 + K3 * 1024, more && lane == 0 ? 32768 - K3 * 1024 : 0);
      TR(3)
      bar_arrive(NB_XB, 288);
    }
  } else if (w == 13) {
    constexpr uint32_t NP = 8192 / SHIP;
    const uint32_t o = (lane >> 1) * SHIP, own = sb + C_Q + rank * 10240, bt = bars + B_T * 8;
    const uint32_t d2 = 1 + (lane & 1);
    const uint32_t src2 = (rank == 0 ? sb + C_SA : rank == 1 ? own : sb + C_SB) + o;
    const uint32_t skip = (lane & 1) ? 4 | (o >> 11) : 8;
    uint32_t npatch = 0;
#pragma unroll 1
    for (int st = 0; st < NSTEP; st++) {
      mbar_wait(bars + B_P1 * 8, st & 1, 61);
      fence_async_smem();
      if (st > 0) mbar_wait(bars + B_F * 8, (st - 1) & 1, 60);
      const uint32_t info = lds32(sb + C_INFO + (st & 1) * 4);
      TR(2)
      if (st < NSEG && rank != 0 && lane < 2 * NP && d2 == 1 && !(expf_ & 1)) bulk_s2r(mapa_u32(own + o, 0), sb + C_SA + o, SHIP, mapa_u32(bt, 0));
      __syncwarp();
      TR(3)
      mbar_wait(bars + B_P2 * 8, st & 1, 62);
      fence_async_smem();
      if (st > 0 && (SHIPLATE >> rank & 1)) mbar_wait(bars + B_I * 8, (st - 1) & 1, 64);
      TR(0)
      if (st >= DELTA && lane < 2 * NP && d2 != rank && info != skip && !(expf_ & 2)) bulk_s2r(mapa_u32(own + o, d2), src2, SHIP, mapa_u32(bt, d2));
      __syncwarp();
      TR(1)
      if (__builtin_expect(info, 0)) {
        mbar_wait(bars + B_P3 * 8, npatch & 1, 63);
        npatch++;
        fence_async_smem();
        if (rank != 2 && lane == 0) bulk_s2r(mapa_u32(own + (info & 3) * 2048, 2), sb + C_SP, 2048, mapa_u32(bt, 2));
        __syncwarp();
      }
    }
  } else if (w == 14) {
    const int s0 = rank == 0 ? 0 : DELTA;
    const uint32_t tbytes = (expf_ & (rank ? 2 : 1)) ? 0 : 16384;
    mbar_expect_tx_z(bars + B_T * 8, s0 == 0 ? tbytes : 0, lane);
    {
      const int u = (rank == 2 ? 0 : rank + 1) * 32 + h;
      st_rlx32(&g_fl.pol[u], probe_polarity(g_P + u * 4096, lane) + 1);
    }
#pragma unroll 1
    for (int st = 0; st < NSTEP; st++) {
      const int sg = st - s0;
      const bool act = (unsigned)sg < (unsigned)NSEG;
      mbar_wait(bars + B_OT * 8, st & 1, 70);
      mbar_expect_tx_z(bars + B_T * 8, (unsigned)(sg + 1) < (unsigned)NSEG ? tbytes : 0, lane);
      fence_async_smem();
      const int s1 = rank ? st + 1 : st;
      if (rank && s1 < NSTEP - 1) mbar_wait(bars + B_X * 8, s1 & 1, 71);
      TR(0)
      if (act && lane == 0 && !(expf_ & (rank ? 32 : 16))) {
        bulk_s2g(g_O[st & (OSLOTS - 1)][rank] + h * 8192, sb + C_OT + (st & 1) * 8192, 8192);
        asm volatile("cp.async.bulk.commit_group;" ::: "memory");
        asm volatile("cp.async.bulk.wait_group 0;" ::: "memory");
        asm volatile("fence.acq_rel.gpu;" ::: "memory");
      }
      __syncwarp();
      if (WLAG && s1 < NSTEP - 1) mbar_wait(bars + (FGATE ? B_M0 + FGATE - 1 : B_I) * 8, (s1 + (FGATE > 0)) & 1, 72);
      if (act && lane == 0) asm volatile("red.relaxed.gpu.global.add.u32 [%0], 1;" ::"l"(&g_fl.oflag[rank][sg][h >> 2]) : "memory");
      __syncwarp();
      TR(1)
    }
  } else {
    mbar_arrive_z(bars + B_M0 * 8, lane); mbar_arrive_z(bars + B_M1 * 8, lane); mbar_arrive_z(bars + B_M2 * 8, lane);
    const uint32_t gate_g = GATE_G, gate_m = GATE_M;
#pragma unroll 1
    for (int st = 0; st < NSTEP - 1; st++) {
      mbar_wait(bars + B_X * 8, st & 1, 75);
      if (st < 4) { HD(8 + st) }
      if (st == NSTEP - 2) { HD(12) }
      mbar_wait(bars + B_T * 8, st & 1, 77);
      const uint32_t now = gtime() & ~31u, tag = (st + 1) & 31;
      if (lane == 0) st_rlx32(&g_fl.stamp[blockIdx.x], now | tag);
      __syncwarp();
      wait_clock(clk32() + 550);
      uint32_t s0, s1, s2;
      int it = 0;
#pragma unroll 1
      do {
        s0 = ld_rlx32(&g_fl.stamp[lane]) ^ tag; s1 = ld_rlx32(&g_fl.stamp[32 + lane]) ^ tag; s2 = ld_rlx32(&g_fl.stamp[64 + lane]) ^ tag;
        give_up(it++, SPIN_LIMIT, 76);
      } while (__any_sync(~0u, ((s0 | s1 | s2) & 31) != 0));
      const uint32_t tref = now + __reduce_max_sync(~0u, __vimax3_s32((int)(s0 - now), (int)(s1 - now), (int)(s2 - now)));
      const uint32_t g0 = gtime();
      uint32_t g1, c1;
      it = 0;
      do { g1 = gtime(); c1 = clk32(); } while (g1 == g0 && ++it < 64);
      c1 -= (g1 - tref) * 7 / 4;
      sts32(sb + C_INFO + 12, c1);
      TR(0)
      bar_arrive(NB_TA, 160);
      const int sn = (st + 1) & 3;
      const uint8_t* src = (const uint8_t*)g_M + sn * 65536 + (lds32(sb + C_POL + sn * 4) ? 4096 : 12288);
      c1 += gate_m;
      const int d = (int)(c1 - 600 - clk32());
      if (d > 0) warp_sleep(d / 4);
      mbar_expect_tx_z(bars + (B_M0 + lane) * 8, 8192, lane / 3);
      if (lane == 0) {
#pragma unroll
        for (int g = 0; g < 3; g++) {
          wait_clock(c1 + g * gate_g);
          bulk_g2s(sb + C_M + g * 8192, src + g * 16384, 8192, bars + (B_M0 + g) * 8);
          if (g == IGRP) mbar_arrive_z(bars + B_I * 8, 0);
        }
      }
      __syncwarp();
      TR(3)
    }
  }
}

__global__ void __cluster_dims__(3, 1, 1) __launch_bounds__(512, 1)
chain_kernel(const bf16* __restrict__ Wq, const bf16* __restrict__ Wk, const bf16* __restrict__ Wv,
             const bf16* __restrict__ Wo, const bf16* __restrict__ mem0) {
  extern __shared__ __align__(1024) uint8_t smem_raw[];
  const uint32_t sb = (smem_u32(smem_raw) + 1023) & ~1023u;
  const int tid = threadIdx.x, lane = tid & 31;
  const int w = __shfl_sync(~0u, tid >> 5, 0);
  uint32_t rank;
  asm volatile("mov.u32 %0, %%cluster_ctarank;" : "=r"(rank));
  const int h = blockIdx.x / 3;
  asm volatile("griddepcontrol.launch_dependents;" ::: "memory");
  TG(0)
  if (tid == 0) {
    const uint32_t bars = sb + C_BAR;
    mbar_init(bars + B_M0 * 8, 1); mbar_init(bars + B_M1 * 8, 1); mbar_init(bars + B_M2 * 8, 1);
    for (int i = 0; i < 4; i++) mbar_init(bars + (B_R + i) * 8, 1);
    mbar_init(bars + B_X * 8, 9); mbar_init(bars + B_O * 8, 2); mbar_init(bars + B_T * 8, 1); mbar_init(bars + B_F * 8, 2);
    mbar_init(bars + B_XL * 8, 2); mbar_init(bars + B_XL3 * 8, 1);
    mbar_init(bars + B_P1 * 8, 8); mbar_init(bars + B_P2 * 8, 8); mbar_init(bars + B_P3 * 8, 8); mbar_init(bars + B_OT * 8, 3); mbar_init(bars + B_XF * 8, 8); mbar_init(bars + B_I * 8, 1);
    asm volatile("fence.mbarrier_init.release.cluster;" ::: "memory");
  }
  {
    cp16(sb + C_OT + tid * 16, mem0 + (tid & 7) * DM + (tid >> 3) * 8);
    const bf16* W1 = (rank == 0 ? Wq : rank == 1 ? Wk : Wv) + h * 128;
#pragma unroll 4
    for (int cidx = tid; cidx < 512 * 16; cidx += 512) {
      const int d = cidx >> 4, q = cidx & 15;
      cp16(sb + C_X + d * W_STRIDE + q * 16, W1 + (size_t)d * HD + q * 8);
    }
    const int nt = rank == 2 ? 2 : 3;
    for (int cidx = tid; cidx < nt * 1024; cidx += 512) {
      const int tl = cidx >> 10, e = (cidx >> 3) & 127, q = cidx & 7;
      const int es = (e & ~30) | ((e & 6) << 2) | ((e >> 2) & 6);
      cp16(sb + C_WO + tl * 16384 + e * 128 + ((q ^ (e & 7)) << 4), Wo + (size_t)(h * 128 + es) * DM + (tl * 3 + rank) * 64 + q * 8);
    }
    asm volatile("cp.async.commit_group;" ::: "memory");
    if (w == 0) { HD(0) }
    if (w == 0) { HD(1) }
    asm volatile("cp.async.wait_group 0;" ::: "memory");
    fence_async_smem();
    __syncthreads();
    if (w == 0) { HD(2) }
  }
  if (w < 8) {
    reg_inc<184>();
    chain_proj(sb, w, lane, rank);
    TG(1)
    TRDUMP
    cluster_sync();
  } else if (w < 12) {
    reg_dec<120>();
    chain_mem(sb, w, lane, rank, h, mem0);
    STATDUMP
    TRDUMP
    cluster_sync();
  } else {
    reg_dec<24>();
    chain_dma(sb, w, lane, rank, h);
    TRDUMP
    cluster_sync();
  }
}
#undef TRC
#undef TRS

constexpr int K_BAR = 0, K_LN = 128, K_FH = 320, K_FS = 512, K_FY = 1536;
constexpr int K_W = 3072;
constexpr int K_O = K_W + 3 * 49152;
constexpr int K_ST = K_O + 65536;
constexpr int K_SMEM = K_ST + 16384;
static_assert(K_SMEM <= 232448 && 512 * W_STRIDE <= 3 * 49152, "shared memory");
enum { KB_FULL = 0, KB_EMPTY = 2, KB_OK = 4, KB_GO = 7, KB_ST = 10, KB_REL = 12 };
enum { KN_ST = 1, KN_ST1, KN_REL, KN_FFN, KN_INIT, KN_RES, KN_RES1, KN_CAND, KN_TAKEN };
#define GATE_R 450
struct WorkerParams {
  const bf16 *x0, *Wo, *w_r, *w_gate, *w_up, *w_down;
  bf16* out;
};
#define TRC (96 + blockIdx.x)
#define FT(e)
#define QUIET 4900
__device__ __forceinline__ void quiet_until(uint32_t t) {
  int d;
  while ((d = (int)(t - clk32())) > 0) warp_sleep(min(d / 3 + 20, 1000));
}
#define FOR_UNITS _Pragma("unroll 1") for (int st = 0, n = 0; st < WSTEP; st++) \
                  _Pragma("unroll 1") for (int v = st < NSEG ? 0 : st < WSTEP - 1 ? 1 : 2, sg = v ? st - WD : st; v < (st >= WD ? 3 : 1); v++, n++, sg = st - WD)

template <int ACC>
__device__ __forceinline__ void wg_ss8(float (&d)[4], uint64_t da, uint64_t db) {
  asm volatile("wgmma.mma_async.sync.aligned.m64n8k16.f32.bf16.bf16 {%0,%1,%2,%3}, %4, %5, %6, 1, 1, 1, 0;" : O4(d, 0) : "l"(da), "l"(db), "n"(ACC));
}
template <int NU>
__device__ __forceinline__ void ffn_slice(uint32_t sb, int t, const bf16* yrow, int ev) {
  const int lane = t & 31, c = t >> 5;
  FT(1)
  {
    const uint2 r = ld_rlx64(yrow + t * 4);
    asm volatile("st.shared.v2.b32 [%0], {%1,%2};" ::"r"(sb + K_FY + ((t >> 1) & 31) * 32 + (t >> 6) * 16 + (t & 1) * 8), "r"(r.x), "r"(r.y) : "memory");
  }
  fence_async_smem();
  bar_sync(KN_FFN, 128);
  FT(2)
  {
    float g[NU][4];
    const uint64_t da = mk_desc(sb + K_W, 16384, 512, 2), db = mk_desc(sb + K_FY, 32, 0, 0);
    wg_fence();
#pragma unroll
    for (int i = 0; i < 16; i++)
#pragma unroll
      for (int u = 0; u < NU; u++) { if (i == 0) wg_ss8<0>(g[u], da + u * 3072, db); else wg_ss8<1>(g[u], da + u * 3072 + i * 64, db + i * 4); }
    wg_commit();
    wg_wait<0>();
#pragma unroll
    for (int u = 0; u < NU; u++) {
      acc_fence(g[u]);
      if ((lane & 3) == 0) {
        const uint32_t a = sb + K_FS + u * 256 + c * 64 + lane;
        sts32(a, __float_as_uint(c < 2 ? g[u][0] : g[u][1])); sts32(a + 32, __float_as_uint(c < 2 ? g[u][2] : g[u][3]));
      }
    }
  }
  FT(3)
  bar_sync(KN_FFN, 128);
  {
    const uint32_t pa = sb + K_FS + c * 256 + lane * 4;
    const float gt = round_bf16(__uint_as_float(lds32(pa)) + __uint_as_float(lds32(pa + 128)));
    const float up = __shfl_xor_sync(~0u, gt, 16);
    const uint32_t hv = pack_bf16(round_bf16(__fdividef(gt, 1.f + __expf(-gt))) * up, 0.f);
    if (lane < 16) asm volatile("st.shared.b16 [%0], %1;" ::"r"(sb + K_FH + (c * 16 + lane) * 2), "h"((unsigned short)hv) : "memory");
  }
  fence_async_smem();
  bar_sync(KN_FFN, 128);
  FT(4)
#pragma unroll 1
  for (int hf = 0; hf < 2; hf++) {
    float o[4][4];
    const uint64_t da = mk_desc(sb + K_W + 32768 + hf * 8192, 16, 1024, 1), db = mk_desc(sb + K_FH, 16, 0, 0);
    wg_fence();
#pragma unroll
    for (int u = 0; u < NU; u++)
#pragma unroll
      for (int j = 0; j < 4; j++) { if (u == 0) wg_ss8<0>(o[j], da + j * 128, db); else wg_ss8<1>(o[j], da + u * 3072 + j * 128, db + u * 2); }
    wg_commit();
    wg_wait<0>();
    float lo = 0.f, hi = 0.f;
#pragma unroll
    for (int j = 0; j < 4; j++) {
      acc_fence(o[j]);
      const float a = __shfl_sync(~0u, o[j][0], lane & 28), b = __shfl_sync(~0u, o[j][2], lane & 28);
      if ((lane & 3) == j) { lo = a; hi = b; }
    }
    float* p = &g_fl.upd[ev][hf * 256 + (lane & 3) * 64 + c * 16 + (lane >> 2)];
    asm volatile("red.relaxed.gpu.global.add.f32 [%0], %1; red.relaxed.gpu.global.add.f32 [%0 + 32], %2;" ::"l"(p), "f"(lo), "f"(hi) : "memory");
  }
  FT(5)
  bar_sync(KN_FFN, 128);
  if (t == 96) red_release(g_fl.ffncnt[ev]);
  __syncwarp();
}
__device__ __forceinline__ Row ffn_finish(int ver, int ev, u64 key, int lane) {
  const int tok = key_token(key);
  Row x = load_row(g_rows[tok][ver][0], lane);
  const Row y = load_row(g_rows[tok][ver][1], lane);
  const float sig = round_bf16(1.f / (1.f + __expf(-key_score(key))));
  wait_count(g_fl.ffncnt[ev], NWORK, 80);
#pragma unroll
  for (int q = 0; q < 4; q++) {
    const uint4 u = ld_rlx128(&g_fl.upd[ev][q * 128 + lane * 4]);
    const uint32_t a = pack_bf16(__uint_as_float(u.x), __uint_as_float(u.y)), b = pack_bf16(__uint_as_float(u.z), __uint_as_float(u.w));
    x.w[2 * q] = add_bf16x2(x.w[2 * q], add_bf16x2(y.w[2 * q], pack_bf16(bf_lo(a) * sig, bf_hi(a) * sig)));
    x.w[2 * q + 1] = add_bf16x2(x.w[2 * q + 1], add_bf16x2(y.w[2 * q + 1], pack_bf16(bf_lo(b) * sig, bf_hi(b) * sig)));
  }
  return x;
}
__device__ __forceinline__ uint4 pair_ln(uint4 r, float& e, uint32_t sl, int bar, int t) {
  const float x[8] = {bf_lo(r.x), bf_hi(r.x), bf_lo(r.y), bf_hi(r.y), bf_lo(r.z), bf_hi(r.z), bf_lo(r.w), bf_hi(r.w)};
  const float s = ((x[0] + x[1]) + (x[2] + x[3])) + ((x[4] + x[5]) + (x[6] + x[7]));
  const float q = (fmaf(x[0], x[0], x[1] * x[1]) + fmaf(x[2], x[2], x[3] * x[3])) + (fmaf(x[4], x[4], x[5] * x[5]) + fmaf(x[6], x[6], x[7] * x[7]));
  const bool u16 = t & 16, u8 = t & 8;
  const float a = (u16 ? q : s) + __shfl_xor_sync(~0u, u16 ? s : q, 16), b = e + __shfl_xor_sync(~0u, e, 16);
  float v = (u8 ? b : a) + __shfl_xor_sync(~0u, u8 ? a : b, 8);
  v += __shfl_xor_sync(~0u, v, 4); v += __shfl_xor_sync(~0u, v, 2); v += __shfl_xor_sync(~0u, v, 1);
  sts32(sl + (t >> 3) * 4, __float_as_uint(v));
  bar_sync(bar, 64);
  const uint4 s0 = lds128(sl), s1 = lds128(sl + 16);
  const float m = (__uint_as_float(s0.x) + __uint_as_float(s1.x)) * (1.f / DM), m2 = (__uint_as_float(s0.z) + __uint_as_float(s1.z)) * (1.f / DM);
  e = __uint_as_float(s0.y) + __uint_as_float(s1.y);
  float rs;
  asm("rsqrt.approx.ftz.f32 %0, %1;" : "=f"(rs) : "f"(fmaxf(fmaf(-m, m, m2), 0.f) + 1e-5f));
  return make_uint4(pack_bf16((x[0] - m) * rs, (x[1] - m) * rs), pack_bf16((x[2] - m) * rs, (x[3] - m) * rs),
                    pack_bf16((x[4] - m) * rs, (x[5] - m) * rs), pack_bf16((x[6] - m) * rs, (x[7] - m) * rs));
}
__device__ __forceinline__ uint32_t score_bits(float r) {
  const uint32_t b = pack_bf16(0.f, r);
  return (b & 0x80000000u) ? ~b : (b | 0x80000000u);
}

__global__ void __launch_bounds__(640, 1) worker_kernel(const __grid_constant__ WorkerParams prm) {
  extern __shared__ __align__(1024) uint8_t smem_raw[];
  const uint32_t sb = smem_u32(smem_raw);
  if (sb & 1023) __trap();
  const int tid = threadIdx.x, lane = tid & 31;
  const int w = __shfl_sync(~0u, tid >> 5, 0);
  const int me = blockIdx.x, kb = me >> 2, cb = me & 3;
  const bool full = me < 32;
  const uint32_t bars = sb + K_BAR;
  TG(0)
  if (tid == 0) {
    for (int i = 0; i < 2; i++) { mbar_init(bars + (KB_FULL + i) * 8, 1); mbar_init(bars + (KB_EMPTY + i) * 8, 1); }
    for (int i = 0; i < 9; i++) mbar_init(bars + (KB_OK + i) * 8, i < 3 ? 2 : 1);
    sts32(sb + K_LN + 144, 0);
    asm volatile("fence.mbarrier_init.release.cluster;" ::: "memory");
  }
  if (full) {
    const bf16* W1 = prm.Wo + (size_t)kb * 512 * DM + cb * 128;
#pragma unroll 4
    for (int cidx = tid; cidx < 512 * 16; cidx += 640) {
      const int d = cidx >> 4, q = cidx & 15;
      cp16(sb + K_W + d * W_STRIDE + q * 16, W1 + (size_t)d * DM + q * 8);
    }
    asm volatile("cp.async.commit_group;" ::: "memory");
    asm volatile("cp.async.wait_group 0;" ::: "memory");
  }
  fence_async_smem();
  __syncthreads();
  if (w < 8) {
    reg_inc<176>();
    if (full) {
      uint32_t wA[32][4];
      load_wfrags(wA, sb + K_W, w, lane);
      bar_arrive(KN_INIT, 384);
      const uint32_t sp = pin(sb + K_ST + ((lane >> 4) * 8 + (lane & 7)) * 256 + (((2 * w + ((lane >> 3) & 1)) ^ (lane & 7)) << 4));
      const uint32_t tm = pin(lane < 4 ? 0x00010001u : 0u);
      FOR_UNITS {
        float d[16];
        mbar_wait(bars + (KB_FULL + (n & 1)) * 8, (n >> 1) & 1, 81);
        TR(4 * v)
        const uint64_t db = mk_desc(sb + K_O + (n & 1) * 32768, 128, 2048, 0);
        wg_fence();
#pragma unroll
        for (int ks = 0; ks < 32; ks++) {
          if (ks == 0) wg_rs32<0, 0>(d, wA[ks], db);
          else wg_rs32<0, 1>(d, wA[ks], db + (ks >> 3) * 512 + (ks & 7) * 16);
        }
        wg_commit();
        mbar_wait(bars + (KB_ST + (n & 1)) * 8, ((n >> 1) & 1) ^ 1, 82);
        wg_wait<0>();
        acc_fence(d);
        TR(4 * v + 1)
        const uint32_t tag = (sg & 2) ? 0u : tm;
        uint32_t pk[8];
#pragma unroll
        for (int i = 0; i < 8; i++) pk[i] = (pack_bf16(d[2 * i], d[2 * i + 1]) & ~tm) | tag;
        stsm4t(sp + (n & 1) * 8192, pk[0], pk[1], pk[2], pk[3]);
        stsm4t(sp + (n & 1) * 8192 + 4096, pk[4], pk[5], pk[6], pk[7]);
        bar_arrive(KN_ST + (n & 1), 288);
        TR(4 * v + 2)
      }
    }
  } else if (w < 12) {
    reg_dec<56>();
    if (full) {
      const int ly = (w >> 1) & 1, t = pin(tid & 63);
      const uint32_t so = pin((t >> 4) * 8192 + me * 256 + (((t & 15) ^ (me & 7)) << 4));
      int sstar = -1;
      uint32_t sl = sb + K_LN + ly * 64;
      float rr = 0.f;
      int kprev = -1;
#pragma unroll 1
      for (int n = 0; n < (ly ? 2 * NSEG : NSEG); n++) {
        if (n == 2 * NSEG - 2) n++;
        const int v = ly ? 1 + (n & 1) : 0, sg = ly ? n >> 1 : n, tok = sg * 32 + me, st = ly ? sg + WD : sg;
        const bf16* xin = ly ? g_rows[tok][0][2] : prm.x0 + tok * DM;
        const bool known = v == 1 && st == NSEG;
        if (v == 2 || known) {
          int it = 0;
          while (__any_sync(~0u, (int)lds32(sb + K_LN + 144) <= (known ? NSEG - 1 : sg))) { give_up(++it, SPIN_LIMIT, 86); warp_sleep(50); }
          const uint32_t r = lds32(sb + K_LN + (known ? 156 : 148 + (sg >> 5) * 4));
          if (__builtin_expect(known, 0)) {
            sstar = r;
            const int nc = min(sstar, sg);
#pragma unroll 1
            for (int s0 = 0; s0 < nc; s0 += 5) {
              uint4 q[5];
#pragma unroll
              for (int i = 0; i < 5; i++) q[i] = ld_rlx128(g_rows[min(s0 + i, nc - 1) * 32 + me][1][2] + t * 8);
#pragma unroll
              for (int i = 0; i < 5; i++) *(uint4*)(prm.out + (min(s0 + i, nc - 1) * 32 + me) * DM + t * 8) = q[i];
            }
          } else if ((r >> (sg & 31)) & 1) {
            xin = g_x2p + sg * DM;
          }
        }
        const uint8_t* src = g_part[v] + (sg & 1) * (32 * 8192) + so;
        const uint32_t flip = (sg & 2) ? ~0u : 0u;
        mbar_wait(bars + (KB_GO + v) * 8, sg & 1, 87);
        TR(4 * v)
        uint4 p[8], x;
        int it = 0;
#pragma unroll 1
        do {
#pragma unroll
          for (int k = 0; k < 8; k++) p[k] = ld_rlx128(src + k * 32768);
          x = ld_rlx128(((WEXP & 2) ? prm.x0 : xin) + t * 8);
          give_up(it++, SPIN_LIMIT, 85);
        } while (__builtin_expect(!__all_sync(~0u, (int)and3(and3(and_x(p[0].x, p[1].x, flip), and_x(p[2].x, p[3].x, flip), 1u),
                                                             and_x(p[4].x, p[5].x, flip), and_x(p[6].x, p[7].x, flip))), 0));
        mbar_arrive_z(bars + (KB_OK + v) * 8, t & 31);
#define P8(h, f) (((h(p[0].f) + h(p[1].f)) + (h(p[2].f) + h(p[3].f))) + ((h(p[4].f) + h(p[5].f)) + (h(p[6].f) + h(p[7].f))))
#define X8(f) x.f = add_bf16x2(x.f, pack_bf16(P8(bf_lo, f), P8(bf_hi, f)));
        X8(x) X8(y) X8(z) X8(w)
#undef X8
#undef P8
        TRV(12 + v, it - 1)
        TR(4 * v + 1)
        bf16* dst = g_rows[tok][v][0] + t * 8;
        *(uint4*)dst = x;
        const uint4 wr = ld_rlx128(prm.w_r + t * 8);
        sl ^= 32;
        uint4 y = pair_ln(x, rr, sl, KN_RES + ly, t);
        *(uint4*)(dst + DM) = y;
        x = make_uint4(add_bf16x2(x.x, y.x), add_bf16x2(x.y, y.y), add_bf16x2(x.z, y.z), add_bf16x2(x.w, y.w));
        *(uint4*)(v == (sg < sstar ? 1 : 2) ? prm.out + tok * DM + t * 8 : dst + 2 * DM) = x;
        asm volatile("{ .reg .pred p; setp.eq.u32 p, %2, 0; @p st.relaxed.gpu.global.u64 [%0], %1; }" ::"l"(&g_fl.key[0][0][0] + max(kprev, 0)),
                     "l"((u64)score_bits(rr) << 32 | (uint32_t)~(kprev & (NTOK - 1))), "r"(t | (kprev < 0)) : "memory");
        kprev = v * NTOK + tok;
        rr = (fmaf(bf_lo(y.x), bf_lo(wr.x), bf_hi(y.x) * bf_hi(wr.x)) + fmaf(bf_lo(y.y), bf_lo(wr.y), bf_hi(y.y) * bf_hi(wr.y))) +
             (fmaf(bf_lo(y.z), bf_lo(wr.z), bf_hi(y.z) * bf_hi(wr.z)) + fmaf(bf_lo(y.w), bf_lo(wr.w), bf_hi(y.w) * bf_hi(wr.w)));
        if (v == 0 || (v == 2 && st >= NSEG)) {
          sl ^= 32;
          y = pair_ln(x, rr, sl, KN_RES + ly, t);
          if (v == 0) *(uint4*)(g_xs[1] + sg * 32768 + (t >> 3) * 4096 + me * 128 + (((t ^ me) & 7) << 4)) = y;
          sts32(sb + K_LN + 128, score_bits(rr));
          bar_arrive(KN_REL, 96);
          kprev = -1;
        }
        TR(4 * v + 2)
      }
    }
  } else if (w < 16) {
    reg_dec<48>();
    const int t = tid - 384, nu = full ? 3 : 4;
    if (full) bar_sync(KN_INIT, 384);
    {
      const int j0 = (full ? me * 3 : 96 + (me - 32) * 4) * 16;
#pragma unroll 1
      for (int i = t; i < nu * 3072; i += 128) {
        const int u = i / 3072, r = i - u * 3072;
        const int q = (r ^ (r >> 3)) & 3, r2 = r - 2048;
        const bf16* src = r < 2048 ? ((q & 2) ? prm.w_up : prm.w_gate) + (size_t)(r >> 2) * FF + j0 + u * 16 + (q & 1) * 8
                                   : prm.w_down + (size_t)(j0 + u * 16 + ((r2 >> 3) & 15)) * DM + (r2 >> 7) * 64 + ((r2 ^ (r2 >> 3)) & 7) * 8;
        cp16(sb + K_W + i * 16, src);
      }
      asm volatile("cp.async.wait_all;" ::: "memory");
    }
    bar_arrive(KN_TAKEN, 160);
#pragma unroll 1
    while (true) {
      bar_sync(KN_CAND, 160);
      const uint4 cand = lds128(sb + K_LN + 160);
      const u64 k = (u64)cand.y << 32 | cand.x;
      const int ev = cand.z, ver = cand.w & 3, tok = key_token(k);
      const bool last = cand.w & 4;
      if (!last) {
        bar_arrive(KN_TAKEN, 160);
        FT(0)
        if (full) ffn_slice<3>(sb, t, g_rows[tok][ver][1], ev); else ffn_slice<4>(sb, t, g_rows[tok][ver][1], ev);
      }
      if ((tok & 31) == me && (ver == 0 || last)) {
        uint8_t* dst = g_patch + (size_t)(tok >> 5) * 8192;
        if (w == 12) {
          FT(6)
          const Row x = ffn_finish(ver, ev, k, lane);
          FT(7)
          store_row(ver ? prm.out + (size_t)tok * DM : g_x2p + ev * DM, lane, x);
          if (ver == 0) store_row_img<1024>(dst, tok & 7, lane, warp_ln(x));
        } else if (w < 15 && ver == 0) {
          const uint8_t* src = g_xs[1] + (size_t)(tok >> 5) * 32768 + (tok & 24) * 128 + (t - 32) * 16;
#pragma unroll 1
          for (int i0 = 0; i0 < 8; i0 += 4) {
            uint4 q[4];
#pragma unroll
            for (int i = 0; i < 4; i++) q[i] = ld_rlx128(src + (i0 + i) * 4096);
            if (((t - 32) >> 3) != (tok & 7)) {
#pragma unroll
              for (int i = 0; i < 4; i++) *(uint4*)(dst + (t - 32) * 16 + (i0 + i) * 1024) = q[i];
            }
          }
        }
        bar_sync(KN_FFN, 128);
        if (t == 0 && ver == 0) st_release32(g_fl.patch[ev], 1);
        __syncwarp();
      }
      FT(8)
      if (last) break;
    }
  } else {
    reg_dec<24>();
    if (w == 16) {
      u64 best = 0, mask = 0;
      int sstar = 0;
      uint32_t ver = 0, ev = 0;
      auto post = [&](uint32_t cmd) {
        bar_sync(KN_TAKEN, 160);
        sts128(sb + K_LN + 160, make_uint4((uint32_t)best, (uint32_t)(best >> 32), ev, ver | cmd));
        bar_arrive(KN_CAND, 160);
      };
      u64 accn = 0, acca = 0;
      uint32_t recs = 0;
      int j = 0;
      uint32_t tq = clk32();
#pragma unroll 1
      for (int st = 0; st < WSTEP; st++) {
        const u64* keys = st < NSEG ? g_fl.key[0][st] : g_fl.key[2][st - WD];
        const bool early = __any_sync(~0u, ld_rlx32(keys + lane) == 0);
        if (early && st < NSEG) quiet_until(tq);
        u64 k = wait_keys(keys, lane, 91);
        if (early) tq = clk32() + QUIET;
        if (st < NSEG) {
          const bool rec = k > best;
          recs &= ~(1u << (st & 31));
          if (rec) {
            best = k; ev = sstar = st;
            recs |= 1u << (st & 31);
            if ((key_token(k) & 31) == me) mask |= 1ull << st;
          }
          if (lane == 0) sts128(sb + K_LN + 144, make_uint4(st + 1, (uint32_t)mask, (uint32_t)(mask >> 32), sstar));
          __syncwarp();
          if (rec) post(0);
        }
#pragma unroll 1
        for (; j <= st - WD - (st < NSEG ? 2 : 0); j++) {
          u64 kn = 1, kc;
          int it = 0;
          do {
            if (j < NSEG - 1) asm volatile("ld.relaxed.gpu.global.u64 %0, [%1];" : "=l"(kn) : "l"(&g_fl.key[1][j][lane]) : "memory");
            asm volatile("ld.relaxed.gpu.global.u64 %0, [%1];" : "=l"(kc) : "l"(&g_fl.key[2][j][lane]) : "memory");
            give_up(it++, SPIN_LIMIT, 92);
          } while (__any_sync(~0u, kn == 0 || kc == 0));
          if ((recs >> (j & 31)) & 1) acca = accn;
          if (kc > acca) acca = kc;
          if (kn > accn) accn = kn;
        }
        if (st >= NSEG) {
          const u64 m = j <= sstar ? accn : acca;
          const uint32_t hi = __reduce_max_sync(~0u, (uint32_t)(m >> 32));
          k = (u64)hi << 32 | __reduce_max_sync(~0u, (uint32_t)(m >> 32) == hi ? (uint32_t)m : 0u);
          if (st == NSEG || k != best) {
            best = k; ev = st;
            ver = (key_token(k) >> 5) < sstar ? 1 : 2;
            post(0);
          }
        }
      }
      HD(6)
      post(4);
    } else if (!full) {
    } else if (w == 17) {
      uint32_t tq = clk32();
      FOR_UNITS {
        if (ld_rlx32(&g_fl.oflag[v][sg][kb]) < 4) {
          if (v == (st < NSEG ? 0 : 1) && st < WSTEP - 3) quiet_until(tq);
          wait_count(&g_fl.oflag[v][sg][kb], 4, 84);
          if (v == (st < NSEG ? 0 : 1)) tq = clk32() + QUIET;
        }
        mbar_wait(bars + (KB_EMPTY + (n & 1)) * 8, ((n >> 1) & 1) ^ 1, 83);
        TR(v)
        if (st == WSTEP - 1) { HD(v) }
        if (lane == 0) {
          fence_async_glb();
          mbar_expect_tx(bars + (KB_FULL + (n & 1)) * 8, (WEXP & 4) ? 4096 : 32768);
          bulk_g2s(sb + K_O + (n & 1) * 32768, g_O[(v ? sg + DELTA : sg) & (OSLOTS - 1)][v] + kb * 32768, (WEXP & 4) ? 4096 : 32768, bars + (KB_FULL + (n & 1)) * 8);
        }
        __syncwarp();
      }
    } else if (w == 18) {
      FOR_UNITS {
        if (sg > 0) mbar_wait(bars + (KB_OK + v) * 8, (sg - 1) & 1, 90);
        bar_sync(KN_ST + (n & 1), 288);
        fence_async_smem();
        if (lane == 0) {
          bulk_s2g(g_part[v] + ((sg & 1) * 32 + me) * 8192, sb + K_ST + (n & 1) * 8192, 8192);
          asm volatile("cp.async.bulk.commit_group;" ::: "memory");
          mbar_arrive_z(bars + (KB_EMPTY + (n & 1)) * 8, 0);
          asm volatile("cp.async.bulk.wait_group.read 0;" ::: "memory");
        }
        __syncwarp();
        mbar_arrive_z(bars + (KB_ST + (n & 1)) * 8, lane);
        TR(v)
        const uint32_t tg = clk32() + GATE_R;
        if (v == (st < NSEG ? 0 : 2) && st > 0) mbar_wait(bars + KB_REL * 8, (st - 1) & 1, 93);
        wait_clock(tg);
        if (st == WSTEP - 1) { HD(2 + v) }
        mbar_arrive_z(bars + (KB_GO + v) * 8, lane);
      }
    } else {
#pragma unroll 1
      for (int st = 0; st < WSTEP; st++) {
        const int sg = st < NSEG ? st : st - WD;
        bar_sync(KN_REL, 96);
        const uint32_t ob = __shfl_sync(~0u, lds32(sb + K_LN + 128), 0);
        mbar_arrive_z(bars + KB_REL * 8, lane);
        if (st == WSTEP - 1) { HD(5) }
        if (WEXP & 8) { warp_sleep(500); if (lane == 0) asm volatile("st.relaxed.gpu.global.u64 [%0], %1;" ::"l"(&g_fl.key[st < NSEG ? 0 : 2][sg][me]), "l"((u64)ob << 32 | (uint32_t)~(sg * 32 + me)) : "memory"); }
        else if (lane == 0) st_release_u64(&g_fl.key[st < NSEG ? 0 : 2][sg][me], (u64)ob << 32 | (uint32_t)~(sg * 32 + me));
        __syncwarp();
        TR(0)
      }
    }
  }
}
#undef TRC

bool g_ready;

}

extern "C" void kernel_launch(void* const* d_in, const int* in_sizes, int n_in, void* d_out, int out_size) {
  (void)in_sizes; (void)n_in; (void)out_size;
  const bf16* x0 = (const bf16*)d_in[0];
  const bf16* mem0 = (const bf16*)d_in[1];
  const bf16* Wq = (const bf16*)d_in[2];
  const bf16* Wk = (const bf16*)d_in[3];
  const bf16* Wv = (const bf16*)d_in[4];
  const bf16* Wo = (const bf16*)d_in[5];
  if (!g_ready) {
    cudaFuncSetAttribute(worker_kernel, cudaFuncAttributeMaxDynamicSharedMemorySize, K_SMEM);
    cudaFuncSetAttribute(chain_kernel, cudaFuncAttributeMaxDynamicSharedMemorySize, C_SMEM);
    g_ready = true;
  }
  cudaStream_t st = cudaStreamPerThread;
  prep_kernel<<<NTOK / 8, 256, 0, st>>>(x0, Wq, Wk, Wv, Wo);
  chain_kernel<<<96, 512, C_SMEM, st>>>(Wq, Wk, Wv, Wo, mem0);
  cudaLaunchAttribute pdl[1];
  pdl[0].id = cudaLaunchAttributeProgrammaticStreamSerialization;
  pdl[0].val.programmaticStreamSerializationAllowed = 1;
  WorkerParams wp;
  wp.x0 = x0; wp.Wo = Wo; wp.w_r = (const bf16*)d_in[8]; wp.w_gate = (const bf16*)d_in[9]; wp.w_up = (const bf16*)d_in[10];
  wp.w_down = (const bf16*)d_in[11]; wp.out = (bf16*)d_out;
  cudaLaunchConfig_t cfg = {};
  cfg.gridDim = dim3(NWORK); cfg.blockDim = dim3(640); cfg.dynamicSmemBytes = K_SMEM; cfg.stream = st;
  cfg.attrs = pdl; cfg.numAttrs = 1;
  cudaLaunchKernelEx(&cfg, worker_kernel, wp);
}
```

```cpp
#include <cuda_runtime.h>
#include <cuda_bf16.h>
#include <stdint.h>

namespace {

typedef __nv_bfloat16 bf16;
typedef unsigned long long u64;

constexpr int NTOK = 2048, DM = 512, HD = 4096, NSEG = 64, FF = 1792;
#define DELTA 5
constexpr int NSTEP = NSEG + DELTA;
#define WLAG 1
constexpr int WD = DELTA + WLAG, WSTEP = NSEG + WD;
constexpr int SPIN_LIMIT = 40000;
constexpr int MBAR_LIMIT = 20000;
constexpr int NWORK = 36;
constexpr int OSLOTS = 8;
#define SLP_C 100
#define SLP_K 200
#define WEXP 0

__device__ __align__(1024) uint8_t g_xs[2][NSEG * 32768];
__device__ __align__(1024) uint8_t g_O[OSLOTS][3][32 * 8192];
__device__ __align__(1024) uint8_t g_part[3][2 * 32 * 8192];
__device__ __align__(1024) bf16 g_rows[NTOK][3][3][DM];
__device__ __align__(1024) bf16 g_x2p[NSEG][2][DM];
struct Flags {
  uint32_t pol[96];
  uint32_t stamp[96];
  uint32_t oflag[3][NSEG][8];
  uint32_t ffncnt[WSTEP][8];
  uint32_t patch[NSEG][8];
  u64 key[3][NSEG][32];
  float upd[WSTEP][DM];
};
struct Exchange { uint32_t M[4 * 16384], P[96 * 4096]; Flags fl; };
__device__ __align__(65536) Exchange g_ex;
#define g_M g_ex.M
#define g_P g_ex.P
#define g_fl g_ex.fl
#define TR(e)
#define TRV(e, v)
#define TG(i)
#define HD(e)
#define TRDUMP
#define TREXTRA 0

#define STAT(e, v)
#define STATC(n)
#define STATDUMP
__device__ __forceinline__ uint32_t smem_u32(const void* p) { return (uint32_t)__cvta_generic_to_shared(p); }
__device__ __forceinline__ uint32_t pack_bf16(float lo, float hi) {
  uint32_t r;
  asm("cvt.rn.bf16x2.f32 %0, %1, %2;" : "=r"(r) : "f"(hi), "f"(lo));
  return r;
}
__device__ __forceinline__ float bf_lo(uint32_t v) { return __uint_as_float(v << 16); }
__device__ __forceinline__ float bf_hi(uint32_t v) { return __uint_as_float(v & 0xffff0000u); }
__device__ __forceinline__ float ex2_fast(float x) { float y; asm("ex2.approx.ftz.f32 %0, %1;" : "=f"(y) : "f"(x)); return y; }
__device__ __forceinline__ float round_bf16(float x) { return __bfloat162float(__float2bfloat16_rn(x)); }
__device__ __forceinline__ uint32_t clk32() { uint32_t t; asm volatile("mov.u32 %0, %%clock;" : "=r"(t) :: "memory"); return t; }

__device__ __forceinline__ void mma16816(float (&d)[4], uint32_t a0, uint32_t a1, uint32_t a2, uint32_t a3,
                                         uint32_t b0, uint32_t b1) {
  asm("mma.sync.aligned.m16n8k16.row.col.f32.bf16.bf16.f32 {%0,%1,%2,%3}, {%4,%5,%6,%7}, {%8,%9}, {%0,%1,%2,%3};"
      : "+f"(d[0]), "+f"(d[1]), "+f"(d[2]), "+f"(d[3])
      : "r"(a0), "r"(a1), "r"(a2), "r"(a3), "r"(b0), "r"(b1));
}
__device__ __forceinline__ void ldsm4t(uint32_t (&r)[4], uint32_t addr) {
  asm volatile("ldmatrix.sync.aligned.m8n8.x4.trans.shared.b16 {%0,%1,%2,%3}, [%4];"
               : "=r"(r[0]), "=r"(r[1]), "=r"(r[2]), "=r"(r[3]) : "r"(addr) : "memory");
}
__device__ __forceinline__ void stsm4(uint32_t addr, uint32_t a, uint32_t b, uint32_t c, uint32_t d) {
  asm volatile("stmatrix.sync.aligned.m8n8.x4.shared.b16 [%0], {%1,%2,%3,%4};" ::"r"(addr), "r"(a), "r"(b), "r"(c), "r"(d) : "memory");
}
__device__ __forceinline__ void stsm4t(uint32_t addr, uint32_t a, uint32_t b, uint32_t c, uint32_t d) {
  asm volatile("stmatrix.sync.aligned.m8n8.x4.trans.shared.b16 [%0], {%1,%2,%3,%4};" ::"r"(addr), "r"(a), "r"(b), "r"(c), "r"(d) : "memory");
}
__device__ __forceinline__ uint4 lds128(uint32_t a) {
  uint4 v; asm volatile("ld.shared.v4.b32 {%0,%1,%2,%3}, [%4];" : "=r"(v.x), "=r"(v.y), "=r"(v.z), "=r"(v.w) : "r"(a) : "memory"); return v;
}
__device__ __forceinline__ uint32_t lds32(uint32_t a) { uint32_t v; asm volatile("ld.shared.b32 %0, [%1];" : "=r"(v) : "r"(a) : "memory"); return v; }
__device__ __forceinline__ void sts32(uint32_t a, uint32_t x) { asm volatile("st.shared.b32 [%0], %1;" ::"r"(a), "r"(x) : "memory"); }
__device__ __forceinline__ void sts128(uint32_t a, uint4 v) {
  asm volatile("st.shared.v4.b32 [%0], {%1,%2,%3,%4};" ::"r"(a), "r"(v.x), "r"(v.y), "r"(v.z), "r"(v.w) : "memory");
}
__device__ __forceinline__ void cp16(uint32_t dst, const void* src) {
  asm volatile("cp.async.cg.shared.global [%0], [%1], 16;" ::"r"(dst), "l"(src) : "memory");
}
__device__ __forceinline__ void mbar_init(uint32_t mbar, uint32_t cnt) {
  asm volatile("mbarrier.init.shared.b64 [%0], %1;" ::"r"(mbar), "r"(cnt) : "memory");
}
__device__ __forceinline__ void mbar_expect_tx(uint32_t mbar, uint32_t bytes) {
  asm volatile("mbarrier.arrive.expect_tx.shared.b64 _, [%0], %1;" ::"r"(mbar), "r"(bytes) : "memory");
}
__device__ __forceinline__ void mbar_arrive_z(uint32_t mbar, uint32_t z) {
  asm volatile("{ .reg .pred p; setp.eq.u32 p, %1, 0; @p mbarrier.arrive.shared.b64 _, [%0]; }" ::"r"(mbar), "r"(z) : "memory");
}
__device__ __forceinline__ void mbar_expect_tx_z(uint32_t mbar, uint32_t bytes, uint32_t z) {
  asm volatile("{ .reg .pred p; setp.eq.u32 p, %2, 0; @p mbarrier.arrive.expect_tx.shared.b64 _, [%0], %1; }" ::"r"(mbar), "r"(bytes), "r"(z) : "memory");
}
__device__ __forceinline__ void mbar_arrive_remote_z(uint32_t mbar, uint32_t z) {
  asm volatile("{ .reg .pred p; setp.eq.u32 p, %1, 0; @p mbarrier.arrive.shared::cluster.b64 _, [%0]; }" ::"r"(mbar), "r"(z) : "memory");
}
__device__ __forceinline__ void warp_sleep(uint32_t ns) { __nanosleep(ns); __syncwarp(); }
__device__ __forceinline__ void fail(int) { __trap(); }
__device__ __forceinline__ void give_up(int it, int limit, int code) { if (it > limit) fail(code); }
__device__ __forceinline__ void mbar_wait(uint32_t mbar, uint32_t par, int code) {
  asm volatile("{ .reg .pred p; .reg .b32 n; mov.b32 n, %2;\n"
               "W: mbarrier.try_wait.parity.shared::cta.b64 p, [%0], %1; @p bra D;\n"
               "add.s32 n, n, -1; setp.eq.s32 p, n, 0; @p trap; bra W;\n"
               "D: }" ::"r"(mbar), "r"(par), "n"(MBAR_LIMIT) : "memory");
}
__device__ __forceinline__ void bulk_g2s(uint32_t dst, const void* src, uint32_t bytes, uint32_t mbar) {
  asm volatile("cp.async.bulk.shared::cluster.global.mbarrier::complete_tx::bytes [%0], [%1], %2, [%3];"
               ::"r"(dst), "l"(src), "r"(bytes), "r"(mbar) : "memory");
}
__device__ __forceinline__ void bulk_s2r(uint32_t dst, uint32_t src, uint32_t bytes, uint32_t mbar) {
  asm volatile("cp.async.bulk.shared::cluster.shared::cta.mbarrier::complete_tx::bytes [%0], [%1], %2, [%3];"
               ::"r"(dst), "r"(src), "r"(bytes), "r"(mbar) : "memory");
}
__device__ __forceinline__ void bulk_s2g(void* dst, uint32_t src, uint32_t bytes) {
  asm volatile("cp.async.bulk.global.shared::cta.bulk_group [%0], [%1], %2;" ::"l"(dst), "r"(src), "r"(bytes) : "memory");
}
__device__ __forceinline__ void fence_async_smem() { asm volatile("fence.proxy.async.shared::cta;" ::: "memory"); }
__device__ __forceinline__ void fence_async_glb() { asm volatile("fence.proxy.async.global;" ::: "memory"); }
__device__ __forceinline__ void bar_sync(int id, int n) { asm volatile("bar.sync %0, %1;" ::"r"(id), "r"(n) : "memory"); }
__device__ __forceinline__ void bar_arrive(int id, int n) { asm volatile("bar.arrive %0, %1;" ::"r"(id), "r"(n) : "memory"); }
__device__ __forceinline__ void cluster_sync() { asm volatile("barrier.cluster.arrive.release; barrier.cluster.wait.acquire;" ::: "memory"); }
__device__ __forceinline__ uint32_t mapa_u32(uint32_t a, uint32_t r) {
  uint32_t o;
  asm("mapa.shared::cluster.u32 %0, %1, %2;" : "=r"(o) : "r"(a), "r"(r));
  return o;
}
template <int OFF>
__device__ __forceinline__ void st_async32(uint32_t a, uint32_t x, uint32_t mbar) {
  asm volatile("st.async.weak.shared::cluster.mbarrier::complete_tx::bytes.b32 [%0 + %3], %1, [%2];" ::"r"(a), "r"(x), "r"(mbar), "n"(OFF) : "memory");
}
__device__ __forceinline__ uint4 ld_rlx128(const void* p) {
  uint4 v;
  asm volatile("ld.relaxed.gpu.global.v4.u32 {%0,%1,%2,%3}, [%4];" : "=r"(v.x), "=r"(v.y), "=r"(v.z), "=r"(v.w) : "l"(p) : "memory");
  return v;
}
__device__ __forceinline__ uint2 ld_rlx64(const void* p) {
  uint2 v; asm volatile("ld.relaxed.gpu.global.v2.u32 {%0,%1}, [%2];" : "=r"(v.x), "=r"(v.y) : "l"(p) : "memory"); return v;
}
__device__ __forceinline__ uint32_t ld_rlx32(const void* p) {
  uint32_t v; asm volatile("ld.relaxed.gpu.global.u32 %0, [%1];" : "=r"(v) : "l"(p) : "memory"); return v;
}
__device__ __forceinline__ void st_rlx32(void* p, uint32_t a) { asm volatile("st.relaxed.gpu.global.u32 [%0], %1;" ::"l"(p), "r"(a) : "memory"); }
__device__ __forceinline__ void red_release(uint32_t* p) { asm volatile("red.release.gpu.global.add.u32 [%0], 1;" ::"l"(p) : "memory"); }
__device__ __forceinline__ void st_release32(void* p, uint32_t a) { asm volatile("st.release.gpu.global.u32 [%0], %1;" ::"l"(p), "r"(a) : "memory"); }
__device__ __forceinline__ void st_release_u64(void* p, u64 a) { asm volatile("st.release.gpu.global.u64 [%0], %1;" ::"l"(p), "l"(a) : "memory"); }
__device__ __forceinline__ void wait_count(const uint32_t* p, uint32_t val, int code) {
  int it = 0;
  while (ld_rlx32(p) < val) {
    give_up(++it, SPIN_LIMIT, code);
    warp_sleep(SLP_C);
  }
}
__device__ __forceinline__ u64 wait_keys(const u64* keys, int lane, int code) {
  u64 k;
  int it = 0;
  while (true) {
    asm volatile("ld.relaxed.gpu.global.u64 %0, [%1];" : "=l"(k) : "l"(keys + lane) : "memory");
    if (__all_sync(~0u, k != 0)) break;
    give_up(++it, SPIN_LIMIT, code);
    warp_sleep(SLP_K);
  }
  const uint32_t hi = __reduce_max_sync(~0u, (uint32_t)(k >> 32));
  const uint32_t lo = __reduce_max_sync(~0u, (uint32_t)(k >> 32) == hi ? (uint32_t)k : 0u);
  return (u64)hi << 32 | lo;
}
__device__ __forceinline__ int key_token(u64 k) { return (int)(~(uint32_t)k) & (NTOK - 1); }
__device__ __forceinline__ float key_score(u64 k) {
  const uint32_t ob = (uint32_t)(k >> 32);
  return __uint_as_float((ob & 0x80000000u) ? (ob & 0x7fffffffu) : ~ob);
}

__device__ __forceinline__ uint64_t mk_desc(uint32_t saddr, uint32_t lbo, uint32_t sbo, uint32_t sw) {
  return (uint64_t)((saddr & 0x3FFFF) >> 4) | (uint64_t)(lbo >> 4) << 16 | (uint64_t)(sbo >> 4) << 32 | (uint64_t)sw << 62;
}
template <int N> __device__ __forceinline__ void reg_inc() { asm volatile("setmaxnreg.inc.sync.aligned.u32 %0;" ::"n"(N)); }
template <int N> __device__ __forceinline__ void reg_dec() { asm volatile("setmaxnreg.dec.sync.aligned.u32 %0;" ::"n"(N)); }
__device__ __forceinline__ void wg_fence() { asm volatile("wgmma.fence.sync.aligned;" ::: "memory"); }
__device__ __forceinline__ void wg_commit() { asm volatile("wgmma.commit_group.sync.aligned;" ::: "memory"); }
template <int N> __device__ __forceinline__ void wg_wait() { asm volatile("wgmma.wait_group.sync.aligned %0;" ::"n"(N) : "memory"); }
template <int N> __device__ __forceinline__ void acc_fence(float (&d)[N]) {
#pragma unroll
  for (int i = 0; i < N; i++) asm volatile("" : "+f"(d[i]) :: "memory");
}
#define O4(d, i) "+f"(d[i]), "+f"(d[i + 1]), "+f"(d[i + 2]), "+f"(d[i + 3])
template <int TB, int ACC>
__device__ __forceinline__ void wg_rs24(float (&d)[12], const uint32_t (&a)[4], uint64_t db) {
  asm volatile("wgmma.mma_async.sync.aligned.m64n24k16.f32.bf16.bf16 {%0,%1,%2,%3,%4,%5,%6,%7,%8,%9,%10,%11}, {%12,%13,%14,%15}, %16, %17, 1, 1, %18;"
               : O4(d, 0), O4(d, 4), O4(d, 8) : "r"(a[0]), "r"(a[1]), "r"(a[2]), "r"(a[3]), "l"(db), "n"(ACC), "n"(TB));
}
template <int TB, int ACC>
__device__ __forceinline__ void wg_rs32(float (&d)[16], const uint32_t (&a)[4], uint64_t db) {
  asm volatile("wgmma.mma_async.sync.aligned.m64n32k16.f32.bf16.bf16 {%0,%1,%2,%3,%4,%5,%6,%7,%8,%9,%10,%11,%12,%13,%14,%15}, {%16,%17,%18,%19}, %20, %21, 1, 1, %22;"
               : O4(d, 0), O4(d, 4), O4(d, 8), O4(d, 12) : "r"(a[0]), "r"(a[1]), "r"(a[2]), "r"(a[3]), "l"(db), "n"(ACC), "n"(TB));
}
template <int ACC>
__device__ __forceinline__ void wg_rs64(float (&d)[32], uint32_t a0, uint32_t a1, uint32_t a2, uint32_t a3, uint64_t db) {
  asm volatile("wgmma.mma_async.sync.aligned.m64n64k16.f32.bf16.bf16 {%0,%1,%2,%3,%4,%5,%6,%7,%8,%9,%10,%11,%12,%13,%14,%15,"
               "%16,%17,%18,%19,%20,%21,%22,%23,%24,%25,%26,%27,%28,%29,%30,%31}, {%32,%33,%34,%35}, %36, %37, 1, 1, 0;"
               : O4(d, 0), O4(d, 4), O4(d, 8), O4(d, 12), O4(d, 16), O4(d, 20), O4(d, 24), O4(d, 28)
               : "r"(a0), "r"(a1), "r"(a2), "r"(a3), "l"(db), "n"(ACC));
}
template <int ACC>
__device__ __forceinline__ void wg_ss24(float (&d)[12], uint64_t da, uint64_t db) {
  asm volatile("wgmma.mma_async.sync.aligned.m64n24k16.f32.bf16.bf16 {%0,%1,%2,%3,%4,%5,%6,%7,%8,%9,%10,%11}, %12, %13, %14, 1, 1, 1, 0;"
               : O4(d, 0), O4(d, 4), O4(d, 8) : "l"(da), "l"(db), "n"(ACC));
}
template <int ACC>
__device__ __forceinline__ void wg_rs40(float (&d)[20], const uint32_t (&a)[4], uint64_t db) {
  asm volatile("wgmma.mma_async.sync.aligned.m64n40k16.f32.bf16.bf16 {%0,%1,%2,%3,%4,%5,%6,%7,%8,%9,%10,%11,%12,%13,%14,%15,%16,%17,%18,%19}, {%20,%21,%22,%23}, %24, %25, 1, 1, 1;"
               : O4(d, 0), O4(d, 4), O4(d, 8), O4(d, 12), O4(d, 16) : "r"(a[0]), "r"(a[1]), "r"(a[2]), "r"(a[3]), "l"(db), "n"(ACC));
}

struct Row { uint32_t w[8]; };
__device__ __forceinline__ uint32_t add_bf16x2(uint32_t a, uint32_t b) {
  uint32_t d; asm("add.rn.bf16x2 %0, %1, %2;" : "=r"(d) : "r"(a), "r"(b)); return d;
}
__device__ __forceinline__ Row warp_ln(const Row& r, float& extra) {
  float x[16];
#pragma unroll
  for (int i = 0; i < 8; i++) { x[2 * i] = bf_lo(r.w[i]); x[2 * i + 1] = bf_hi(r.w[i]); }
  float m = (((x[0] + x[1]) + (x[2] + x[3])) + ((x[4] + x[5]) + (x[6] + x[7]))) + (((x[8] + x[9]) + (x[10] + x[11])) + ((x[12] + x[13]) + (x[14] + x[15])));
  m *= (1.f / 16);
  float v0 = 0.f, v1 = 0.f;
#pragma unroll
  for (int i = 0; i < 16; i += 2) { const float d0 = x[i] - m, d1 = x[i + 1] - m; v0 = fmaf(d0, d0, v0); v1 = fmaf(d1, d1, v1); }
  float v = v0 + v1;
#pragma unroll
  for (int o = 1; o <= 16; o <<= 1) {
    const float mo = __shfl_xor_sync(~0u, m, o), vo = __shfl_xor_sync(~0u, v, o);
    extra += __shfl_xor_sync(~0u, extra, o);
    const float d = mo - m;
    v = fmaf(d * d, 8.f * o, v + vo);
    m = 0.5f * (m + mo);
  }
  const float var = fmaf(v, 1.f / DM, 1e-5f);
  float rs = rsqrtf(var);
  rs = rs * fmaf(-0.5f * var * rs, rs, 1.5f);
  Row y;
#pragma unroll
  for (int i = 0; i < 8; i++) y.w[i] = pack_bf16((x[2 * i] - m) * rs, (x[2 * i + 1] - m) * rs);
  return y;
}
__device__ __forceinline__ Row warp_ln(const Row& r) { float e = 0.f; return warp_ln(r, e); }
__device__ __forceinline__ Row load_row(const bf16* p, int lane) {
  Row r;
#pragma unroll
  for (int q = 0; q < 4; q++) { const uint2 v = ld_rlx64(p + lane * 4 + q * 128); r.w[2 * q] = v.x; r.w[2 * q + 1] = v.y; }
  return r;
}
__device__ __forceinline__ void store_row_img(uint8_t* img, int rr, int lane, const Row& r) {
  uint8_t* p = img + (lane >> 4) * 4096 + rr * 128 + ((((lane & 15) >> 1) ^ (rr & 7)) << 4) + (lane & 1) * 8;
#pragma unroll
  for (int q = 0; q < 4; q++) *(uint2*)(p + q * 8192) = make_uint2(r.w[2 * q], r.w[2 * q + 1]);
}

__global__ void __launch_bounds__(256) prep_kernel(const bf16* __restrict__ x0, const bf16* Wq, const bf16* Wk, const bf16* Wv, const bf16* Wo) {
  const int lane = threadIdx.x & 31, row = blockIdx.x * 8 + (threadIdx.x >> 5);
  const Row r = load_row(x0 + (size_t)row * DM, lane);
  const int gt = blockIdx.x * 256 + threadIdx.x, nt = gridDim.x * 256;
  asm volatile("prefetch.global.L2 [%0];" ::"l"((gt & 1 ? Wk : Wq) + (gt >> 1) * 64));
  asm volatile("prefetch.global.L2 [%0];" ::"l"((gt & 1 ? Wo : Wv) + (gt >> 1) * 64));
  uint4* M = (uint4*)g_M;
  for (int i = gt; i < 4 * 16384 / 4; i += nt) M[i] = make_uint4(~0u, ~0u, ~0u, ~0u);
  uint4* P = (uint4*)g_P;
  for (int i = gt; i < 96 * 4096 / 4; i += nt) P[i] = make_uint4(0, 0, 0, 0);
  if (gt < 16384) ((uint4*)(g_part[1] + 32 * 8192))[gt] = make_uint4(0, 0, 0, 0);
  uint4* F = (uint4*)&g_fl;
  for (int i = gt; i < (int)(sizeof(Flags) / 16); i += nt) F[i] = make_uint4(0, 0, 0, 0);
  store_row_img(g_xs[0] + (size_t)(row >> 5) * 32768, row & 31, lane, warp_ln(r));
}

constexpr int W_STRIDE = 272;
constexpr int C_WO = 0;
constexpr int C_X = 49152;
constexpr int C_M = C_X + 65536;
constexpr int C_Q = C_M + 24576;
constexpr int C_K = C_Q + 10240, C_V = C_K + 10240;
constexpr int C_SA = C_V + 10240, C_SB = C_SA + 8192;
constexpr int C_O = C_SB + 8192;
constexpr int C_OT = C_O + 6144;
constexpr int C_BAR = C_OT + 16384;
constexpr int C_SMEM = C_BAR + 256 + 1024 + TREXTRA;
static_assert(C_X + 512 * W_STRIDE <= C_OT, "staging");
enum { B_M0 = 0, B_M1, B_M2, B_R, B_X = B_R + 4, B_O, B_T, B_F, B_XL, B_U, B_P1, B_P2, B_OT, B_XF, B_I, B_NUM };
constexpr int C_INFO = C_BAR + 176, C_POL = C_BAR + 208;
enum { NB_ALL = 0, NB_M0, NB_PV, NB_W0, NB_TA, NB_X1, NB_M1, NB_M2, NB_RD, NB_XB };
constexpr float SCALE_LOG2E = 0.08838834764831845f * 1.4426950408889634f;
#define N0STEPS 9
#define N2STEPS 11
#define FGATE 1
constexpr int K3 = 32 - N0STEPS - N2STEPS;
static_assert(K3 % 4 == 0, "the rows of layer 1 are refilled in two parts");
#define BGATE 0
#define IGRP 0
#define SHIPLATE 7
#define SHIP 1024
#define GATE_P 2300
#define GATE_W 200
#define EXPF 0
#define GATE_G 200
#define GATE_M 3400
#define HOLE0 24
#define HOLE1 32
#define HOLE2 32
__device__ __forceinline__ uint32_t gtime() { uint32_t t; asm volatile("mov.u32 %0, %%globaltimer_lo;" : "=r"(t) :: "memory"); return t; }
__device__ __forceinline__ void wait_clock(uint32_t t) {
  asm volatile("{ .reg .pred p; .reg .b32 c; .reg .b64 cc;\nL: mov.u64 cc, %%clock64; cvt.u32.u64 c, cc; sub.u32 c, c, %0; setp.lt.s32 p, c, 0; @p bra L; }" ::"r"(t) : "memory");
}
__device__ __forceinline__ bool bar_or(int id, int n, uint32_t v) {
  uint32_t r;
  asm volatile("{ .reg .pred p, q; setp.ne.u32 p, %1, 0; bar.red.or.pred q, %2, %3, p; vote.sync.any.pred q, q, 0xffffffff; selp.u32 %0, 1, 0, q; }"
               : "=r"(r) : "r"(v), "r"(id), "r"(n) : "memory");
  return r;
}
__device__ __forceinline__ void bar_sync_z(int id, int n, uint32_t z) {
  asm volatile("{ .reg .pred p; setp.eq.u32 p, %2, 0; @p bar.sync %0, %1; }" ::"r"(id), "r"(n), "r"(z) : "memory");
}

__device__ __forceinline__ uint32_t probe_polarity(uint32_t* p, int lane) {
  uint32_t best[2] = {~0u, ~0u};
#pragma unroll 1
  for (int rep = 0; rep < 3; rep++) {
#pragma unroll
    for (int pg = 0; pg < 2; pg++) {
      uint32_t t0, t1, v = 0;
      asm volatile("mov.u32 %0, %%clock;" : "=r"(t0) :: "memory");
      asm volatile("{ .reg .pred p; setp.eq.u32 p, %2, 0; @p atom.relaxed.gpu.global.add.u32 %0, [%1], 0; }" : "+r"(v) : "l"(p + pg * 1024), "r"(lane) : "memory");
      asm volatile("{ .reg .pred p; setp.ne.u32 p, %1, 0x13572468; mov.u32 %0, 0; @p mov.u32 %0, %%clock; }" : "=r"(t1) : "r"(v) : "memory");
      if (rep > 0) best[pg] = min(best[pg], t1 - t0);
    }
  }
  return __shfl_sync(~0u, best[1] < best[0] ? 1u : 0u, 0);
}
__device__ __forceinline__ uint32_t ppage(uint32_t lp, uint32_t pol) { return lp ? 3 - pol : pol; }
__device__ __forceinline__ uint32_t and_x(uint32_t a, uint32_t b, uint32_t m) {
  uint32_t d; asm("lop3.b32 %0, %1, %2, %3, 0x42;" : "=r"(d) : "r"(a), "r"(b), "r"(m)); return d;
}
__device__ __forceinline__ uint32_t and3(uint32_t a, uint32_t b, uint32_t c) {
  uint32_t d; asm("lop3.b32 %0, %1, %2, %3, 0x80;" : "=r"(d) : "r"(a), "r"(b), "r"(c)); return d;
}

template <int N> struct IC { static constexpr int value = N; };
template <class F> __device__ __forceinline__ void static_for2(F f) { f(IC<0>()); f(IC<1>()); }
template <class F> __device__ __forceinline__ void static_for3(F f) { f(IC<0>()); f(IC<1>()); f(IC<2>()); }
__device__ __forceinline__ void load_wfrags(uint32_t (&wA)[32][4], uint32_t stage, int w, int lane) {
  const int mi = lane >> 3, r = lane & 7;
#pragma unroll
  for (int ks = 0; ks < 32; ks++) ldsm4t(wA[ks], stage + (ks * 16 + (mi >> 1) * 8 + r) * W_STRIDE + (w * 16 + (mi & 1) * 8) * 2);
}
template <int K0, int K1>
__device__ __forceinline__ void tok_seq(float (&d)[16], const uint32_t (&wA)[32][4], uint64_t desc, uint32_t wave) {
#pragma unroll
  for (int k = K0; k < K1; k++) {
    const int ks = k & 31;
    constexpr int HM0 = 1, HM1 = 2, HM2 = 4;
    const int hm = (k == HOLE0 ? HM0 : 0) | (k == HOLE1 ? HM1 : 0) | (k == HOLE2 ? HM2 : 0);
    if (hm) bar_sync_z(NB_RD, 384, ((hm >> wave) & 1) ^ 1);
    if (ks == 0) wg_rs32<0, 0>(d, wA[ks], desc);
    else wg_rs32<0, 1>(d, wA[ks], desc + (ks >> 2) * 256 + (ks & 3) * 2);
  }
}
template <int K0, int K1>
__device__ __forceinline__ void mem_part(float (&d)[12], const uint32_t (&wA)[32][4], uint64_t desc) {
#pragma unroll
  for (int ks = K0; ks < K1; ks++) {
    if (ks == 0) wg_rs24<1, 0>(d, wA[ks], desc);
    else wg_rs24<1, 1>(d, wA[ks], desc + ks * 48);
  }
}
__device__ __forceinline__ void out_tile(float (&d)[12], uint64_t da, uint64_t db) {
#pragma unroll
  for (int i = 0; i < 8; i++) { if (i == 0) wg_ss24<0>(d, da, db); else wg_ss24<1>(d, da + i * 128, db + (i >> 1) * 32 + (i & 1) * 2); }
}
__device__ __forceinline__ void tok_pack(uint32_t (&p)[8], const float (&d)[16]) {
#pragma unroll
  for (int i = 0; i < 8; i++) p[i] = pack_bf16(d[2 * i], d[2 * i + 1]);
}
__device__ __forceinline__ void tok_store(uint32_t dst, const uint32_t (&p)[8]) {
  stsm4(dst, p[0], p[1], p[2], p[3]);
  stsm4(dst + 4096, p[4], p[5], p[6], p[7]);
}
template <class T> __device__ __forceinline__ T keep(T v) { asm volatile("" : "+r"(v)); return v; }
__device__ __forceinline__ uint32_t pin(uint32_t v) { return __shfl_sync(~0u, v, threadIdx.x & 31); }

#define TRC blockIdx.x
#define TRS (C_BAR + 256)
__device__ __forceinline__ void chain_proj(const uint32_t sb, const int w, const int lane_, const uint32_t rank) {
  uint32_t wA[32][4];
  load_wfrags(wA, sb + C_X, w, lane_);
  bar_sync(NB_ALL, 512);
  bar_sync(NB_ALL, 512);
  cluster_sync();
  const int lane = pin(lane_);
  const uint32_t bars = sb + C_BAR;
  const uint32_t quad = pin(sb + (lane_ >> 4) * 2048 + (lane_ & 15) * 16);
  const uint32_t own = C_Q + rank * 10240;
  const uint64_t dX1 = mk_desc(sb + C_X, 16, 1024, 1), dX2 = dX1 + 2048;
  const uint64_t dM = mk_desc(sb + C_M, 128, 256, 0);
  const uint32_t r1 = rank == 0 ? 1 : 0, r2 = rank == 2 ? 1 : 2;
  const uint32_t xa = pin(sb + own + 8192 + w * 256 + lane_ * 4);
  const uint32_t a1x = pin(mapa_u32(xa, r1)), a2x = pin(mapa_u32(xa, r2));
  const uint32_t b1x = pin(mapa_u32(bars + B_X * 8, r1)), b2x = pin(mapa_u32(bars + B_X * 8, r2));
  const uint32_t wave = rank == 2 ? 0 : rank + 1;
  float a[16];
  bar_sync(NB_X1, 288);
  wg_fence();
  tok_seq<32, 32 + K3>(a, wA, dX1, 3);
  wg_commit();
  wg_wait<0>();
#pragma unroll 1
  for (int st = 0; st < NSTEP; st++) {
    uint32_t pk[8];
    bar_sync(NB_XB, 288);
    wg_fence();
    tok_seq<32 + K3, 32 + K3 + N0STEPS>(a, wA, dX1, 3);
    TR(0)
    bar_sync(NB_PV, 384);
    tok_seq<32 + K3 + N0STEPS, 64>(a, wA, dX1, 3);
    wg_commit();
    wg_wait<0>();
    acc_fence(a);
    mbar_arrive_z(bars + B_XF * 8, lane);
    tok_pack(pk, a);
    TR(1)
    bar_sync(NB_W0, 416);
    tok_store(quad + w * 256 + (rank == 0 ? own : C_SA), pk);
    __syncwarp();
    mbar_arrive_z(bars + B_P1 * 8, lane);
    wg_fence();
    tok_seq<0, 32>(a, wA, dX2, wave);
    wg_commit();
    const uint32_t info = lds32(sb + C_INFO + (st & 1) * 4);
    TR(2)
    wg_wait<0>();
    acc_fence(a);
    TR(3)
    tok_pack(pk, a);
    tok_store(quad + w * 256 + (rank == 0 ? C_SA : own), pk);
    if (rank == 2) tok_store(quad + w * 256 + C_SB, pk);
    __syncwarp();
    mbar_arrive_z(bars + B_P2 * 8, lane);
    TR(4)
    wg_fence();
    tok_seq<32, 32 + K3>(a, wA, dX1, wave);
    TR(6)
    {
      float am[12];
      bar_sync(NB_M0, 384);
      mem_part<0, 10>(am, wA, dM);
      TR(7)
      bar_sync(NB_M1, 384);
      mem_part<10, 21>(am, wA, dM);
      const bool redo = bar_or(NB_M2, 384, 0);
      mem_part<21, 32>(am, wA, dM);
      wg_commit();
      wg_wait<0>();
      if (__builtin_expect(redo, 0)) {
        bar_sync(NB_M0, 384);
        wg_fence();
        mem_part<0, 32>(am, wA, dM);
        wg_commit();
        wg_wait<0>();
      }
      acc_fence(am);
      TR(8)
      const uint32_t x00 = pack_bf16(am[0], am[1]), x01 = pack_bf16(am[2], am[3]), x10 = pack_bf16(am[4], am[5]), x11 = pack_bf16(am[6], am[7]);
      const uint32_t y0 = pack_bf16(am[8], am[9]), y1 = pack_bf16(am[10], am[11]), x20 = info ? x10 : y0, x21 = info ? x11 : y1;
      st_async32<0>(a1x, rank == 0 ? x10 : x00, b1x); st_async32<0>(a2x, rank == 2 ? x10 : x20, b2x);
      st_async32<128>(a1x, rank == 0 ? x11 : x01, b1x); st_async32<128>(a2x, rank == 2 ? x11 : x21, b2x);
      sts32(xa, rank == 0 ? x00 : rank == 2 ? x20 : x10); sts32(xa + 128, rank == 0 ? x01 : rank == 2 ? x21 : x11);
      if (__builtin_expect(info, 0)) {
        const uint32_t o = (info & 3) * 2048 - 8192;
        if (rank == 2) { sts32(xa + o, y0); sts32(xa + o + 128, y1); }
        else { st_async32<0>(a2x + o, y0, b2x + (B_T - B_X) * 8); st_async32<128>(a2x + o, y1, b2x + (B_T - B_X) * 8); }
      }
      __syncwarp();
      mbar_arrive_z(bars + B_X * 8, lane);
    }
    TR(9)
  }
}

__device__ __forceinline__ void chain_mem(const uint32_t sb, const int w, const int lane_, const uint32_t rank, const int h,
                                          const bf16* __restrict__ mem0) {
  const int lane = pin(lane_);
  const int wave = rank == 2 ? 0 : rank + 1;
  const int c = w - 8, t = c * 32 + lane, b = wave * 32 + h;
  const uint32_t bars = sb + C_BAR;
  const int wi = (lane & 1) * 2 + (lane >> 4), cq = (lane >> 2) & 3;
  bar_sync(NB_ALL, 512);
#pragma unroll 1
  for (int i = c; i < 16; i += 4) {
    uint32_t r[4];
    ldsm4t(r, sb + C_OT + i * 512 + lane * 16);
    const uint32_t a = sb + C_M + (2 * i + (lane >> 4)) * 768 + (lane & 15) * 16;
    stsm4(a, r[0], r[1], r[2], r[3]); stsm4(a + 256, r[0], r[1], r[2], r[3]); stsm4(a + 512, r[0], r[1], r[2], r[3]);
  }
  fence_async_smem();
  mbar_expect_tx_z(bars + B_X * 8, 4096, t); mbar_expect_tx_z(bars + B_O * 8, 4096, t);
  bar_sync(NB_ALL, 512);
  cluster_sync();
  bar_arrive(NB_PV, 384); bar_arrive(NB_W0, 416); bar_arrive(NB_M0, 384); bar_arrive(NB_M1, 384);
  bar_arrive(NB_RD, 384);

  sts32(sb + C_POL + c * 4, probe_polarity(g_M + c * 16384 + (blockIdx.x & 31) * 32, lane));
  uint32_t pgbits, polP;
  {
    const int tl = lane / 3, u = ((tl * 3 + rank) * 4 + c) * 3 + (lane - tl * 3);
    uint32_t pol;
    int it = 0;
    do { pol = ld_rlx32(&g_fl.pol[lane < 9 && u < 96 ? u : b]); give_up(it++, SPIN_LIMIT, 40); } while (__any_sync(~0u, pol == 0));
    pgbits = __reduce_or_sync(~0u, lane < 9 ? ppage(h >> 4, (pol - 1) & 1) << (2 * lane) : 0u);
    polP = __shfl_sync(~0u, pol - 1, 9);
  }
  const int mi = lane >> 3;
  const uint32_t l16 = pin(sb + lane * 16);
  const uint32_t r1 = rank == 2 ? 0 : rank + 1, r2 = rank == 0 ? 2 : rank - 1;
  const uint32_t oa = pin(sb + C_O + rank * 2048 + (lane >> 2) * 64 + (((lane & 3) ^ (lane >> 3)) << 4));
  const uint32_t a1 = mapa_u32(oa, r1), b1 = mapa_u32(bars + B_O * 8, r1), a2 = mapa_u32(oa, r2), b2 = mapa_u32(bars + B_O * 8, r2);
  const uint64_t dWo = mk_desc(sb + C_WO, 8192, 1024, 1), dO = mk_desc(sb + C_O, 16, 2048, 2);
  const uint64_t dK = mk_desc(sb + C_K, 128, 2048, 0);
  const uint64_t dV = mk_desc(sb + C_V, 2048, 128, 0), dVm = mk_desc(sb + C_V + 8192, 0, 128, 0);
  const uint32_t qa = pin(sb + C_Q + (c ? c + 1 : mi & 1) * 2048 + (mi >> 1) * 128 + (lane & 7) * 16);
  const uint32_t dg = ((lane >> 2) < 2 * (lane & 3) ? 1 : 0) | ((lane >> 2) < 2 * (lane & 3) + 1 ? 2 : 0);
  const uint32_t msk = pin(c == 0 ? dg | dg << 4 : c == 1 ? dg << 2 | 3 << 4 : c == 2 ? dg << 4 : 0);
  uint8_t* Pw = (uint8_t*)g_P + (rank * 4 + c) * 3 * 16384 + (h & 15) * 256 + lane * 4;
  const uint8_t* Pr0 = (const uint8_t*)g_P + b * 16384 + ((lane >> 4) * 4 + (lane & 3)) * 256 + c * 64 + cq * 16 + ppage(0, polP) * 4096;
  const uint8_t* Pr1 = Pr0 + (3 - 2 * polP) * 4096;
  uint8_t* Mw = (uint8_t*)g_M + (b >> 5) * 16384 + ((lane & 2) ? 4096 : 12288) + (b & 31) * 256 + c * 64 + cq * 16 + wi * 4;
  uint32_t nretry = 0, nupd = 0;
  const uint32_t gate_p = GATE_P + wave * GATE_W;

  (void)bar_or(NB_M2, 384, 0);
#pragma unroll 1
  for (int st = 0;; st++) {
    mbar_wait(bars + B_T * 8, st & 1, 42);
    STAT(10, clk32())
    {
      float s[20];
      {
        uint32_t q[8][4];
        if (c == 3) mbar_wait(bars + B_X * 8, st & 1, 41);
#pragma unroll
        for (int i = 0; i < 8; i++) ldsm4t(q[i], qa + i * 256);
        if (c != 3) mbar_wait(bars + B_X * 8, st & 1, 41);
        STAT(11, clk32())
        fence_async_smem();
        TR(0)
        wg_fence();
#pragma unroll
        for (int i = 0; i < 8; i++) { if (i == 0) wg_rs40<0>(s, q[i], dK); else wg_rs40<1>(s, q[i], dK + i * 16); }
        wg_commit();
        wg_wait<0>();
        acc_fence(s);
      }
      TR(1)
      const bool w0 = c == 0;
      float z[10] = {s[16], s[17], s[0], s[1], w0 ? s[18] : s[4], w0 ? s[19] : s[5], w0 ? s[2] : s[8], w0 ? s[3] : s[9], w0 ? s[6] : s[12], w0 ? s[7] : s[13]};
      if (msk & 1) z[2] = -INFINITY;
      if (msk & 2) z[3] = -INFINITY;
      if (msk & 4) z[6] = -INFINITY;
      if (msk & 8) z[7] = -INFINITY;
      if (msk & 16) z[8] = -INFINITY;
      if (msk & 32) z[9] = -INFINITY;
      float m0 = fmaxf(fmaxf(z[0], z[1]), fmaxf(z[2], z[3])), m1 = fmaxf(fmaxf(fmaxf(z[4], z[5]), fmaxf(z[6], z[7])), fmaxf(z[8], z[9]));
      m0 = fmaxf(m0, __shfl_xor_sync(~0u, m0, 1)); m1 = fmaxf(m1, __shfl_xor_sync(~0u, m1, 1));
      m0 = fmaxf(m0, __shfl_xor_sync(~0u, m0, 2)); m1 = fmaxf(m1, __shfl_xor_sync(~0u, m1, 2));
      if (!w0) m0 = m1 = fmaxf(m0, m1);
      m0 *= -SCALE_LOG2E; m1 *= -SCALE_LOG2E;
      uint32_t p[5];
#pragma unroll
      for (int k = 0; k < 5; k++) {
        z[2 * k] = ex2_fast(fmaf(z[2 * k], SCALE_LOG2E, k < 2 ? m0 : m1)); z[2 * k + 1] = ex2_fast(fmaf(z[2 * k + 1], SCALE_LOG2E, k < 2 ? m0 : m1));
        p[k] = pack_bf16(z[2 * k], z[2 * k + 1]);
      }
      const uint32_t p2 = w0 ? 0 : p[2], p3 = w0 ? 0 : p[3], p4 = w0 ? 0 : p[4];
      float oA[32], oB[32];
      wg_fence();
      wg_rs64<0>(oA, p[0], p[2], 0, 0, dVm); wg_rs64<1>(oA, p[1], p[3], p2, p[4], dV); wg_rs64<1>(oA, p3, 0, p4, 0, dV + 256);
      wg_commit();
      wg_rs64<0>(oB, p[0], p[2], 0, 0, dVm + 64); wg_rs64<1>(oB, p[1], p[3], p2, p[4], dV + 64); wg_rs64<1>(oB, p3, 0, p4, 0, dV + 320);
      wg_commit();
      float l0 = (z[0] + z[1]) + (z[2] + z[3]), l1 = ((z[4] + z[5]) + (z[6] + z[7])) + (z[8] + z[9]);
      if (!w0) l0 += l1;
      l0 += __shfl_xor_sync(~0u, l0, 1); l1 += __shfl_xor_sync(~0u, l1, 1);
      l0 += __shfl_xor_sync(~0u, l0, 2); l1 += __shfl_xor_sync(~0u, l1, 2);
      float i0, i1;
      asm volatile("rcp.approx.ftz.f32 %0, %2; rcp.approx.ftz.f32 %1, %3;" : "=f"(i0), "=f"(i1) : "f"(l0), "f"(l1));
      const bool mrows = c == 3 && st < NSTEP - 1;
      auto send = [&](const float (&o)[32], auto hc) {
        constexpr int H = decltype(hc)::value;
        static_for2([&](auto bc) {
          constexpr int B = decltype(bc)::value, J = 16 * B;
          asm volatile("st.async.weak.shared::cluster.mbarrier::complete_tx::bytes.v4.b32 [%0 + %9], {%5,%6,%7,%8}, [%1];\n"
                       "st.async.weak.shared::cluster.mbarrier::complete_tx::bytes.v4.b32 [%2 + %9], {%5,%6,%7,%8}, [%3];\n"
                       "st.shared.v4.b32 [%4 + %9], {%5,%6,%7,%8};"
                       ::"r"(a1), "r"(b1), "r"(a2), "r"(b2), "r"(oa), "r"(pack_bf16(o[J] * i0, o[J + 1] * i0)), "r"(pack_bf16(o[J + 4] * i0, o[J + 5] * i0)),
                         "r"(pack_bf16(o[J + 8] * i0, o[J + 9] * i0)), "r"(pack_bf16(o[J + 12] * i0, o[J + 13] * i0)), "n"(H * 1024 + B * 512) : "memory");
        });
      };
      auto keep_tok = [&](uint32_t ta, int R, float iv) {
#pragma unroll
        for (int k = 0; k < 4; k++) {
          const float (&o)[32] = k < 2 ? oA : oB;
          const int J = (k & 1) * 16 + R;
          stsm4(ta + k * 512, pack_bf16(o[J] * iv, o[J + 1] * iv), pack_bf16(o[J + 4] * iv, o[J + 5] * iv),
                pack_bf16(o[J + 8] * iv, o[J + 9] * iv), pack_bf16(o[J + 12] * iv, o[J + 13] * iv));
        }
      };
      wg_wait<1>();
      acc_fence(oA);
      if (mrows) send(oA, IC<0>());
      wg_wait<0>();
      acc_fence(oB);
      if (mrows) {
        send(oB, IC<1>());
        bar_arrive(NB_PV, 384);
        __syncwarp();
        mbar_arrive_z(bars + B_O * 8, lane);
      } else if (c < 3) {
        if (st < NSTEP - 1) bar_arrive(NB_PV, 384);
        const uint32_t ta = l16 + C_OT + (st & 1) * 8192;
        keep_tok(ta + (c ? c + 1 : 0) * 2048, 0, i0);
        if (w0) keep_tok(ta + 2048, 2, i1);
        __syncwarp();
        mbar_arrive_z(bars + B_OT * 8, lane);
      }
      TR(2)
      if (st == NSTEP - 1) break;
      mbar_expect_tx_z(bars + B_X * 8, 4096, t);
    }
    uint32_t tref, info;
    {
      const uint32_t tag = (st & 1) ^ 1;
      float oc0[12], oc1[12], oc2[12];
      mbar_wait(bars + B_O * 8, st & 1, 43);
      fence_async_smem();
      TR(3)
      wg_fence();
      out_tile(oc0, dWo, dO);
      wg_commit();
      out_tile(oc1, dWo + 1024, dO);
      wg_commit();
      asm volatile("" : "+r"(pgbits));
      auto put = [&](const float (&oc)[12], auto tlc) {
        constexpr int TL = decltype(tlc)::value;
        static_for3([&](auto jc) {
          constexpr int j = decltype(jc)::value;
          uint8_t* p = Pw + ((pgbits >> (2 * (TL * 3 + j))) & 3) * 4096;
          asm volatile("st.relaxed.gpu.global.u32 [%0 + %3], %1; st.relaxed.gpu.global.u32 [%0 + %3 + 128], %2;" ::"l"(p),
                       "r"((pack_bf16(oc[4 * j], oc[4 * j + 1]) & ~1u) | tag), "r"((pack_bf16(oc[4 * j + 2], oc[4 * j + 3]) & ~1u) | tag),
                       "n"((TL * 36 + j) * 16384) : "memory");
        });
      };
      wg_wait<1>();
      acc_fence(oc0);
      put(oc0, IC<0>());
      sts32(sb + C_INFO + 24, clk32());
      TR(4)
      out_tile(oc2, dWo + 2048, dO);
      wg_commit();
      wg_wait<1>();
      acc_fence(oc1);
      put(oc1, IC<1>());
      bar_sync(NB_TA, 192);
      tref = lds32(sb + C_INFO + 12);
      info = lds32(sb + C_INFO + ((st + 1) & 1) * 4);
      TR(5)
      wg_wait<0>();
      bar_arrive(NB_W0, 416);
      acc_fence(oc2);
      if (rank != 2) put(oc2, IC<2>());
      mbar_arrive_remote_z(((t & 1) ? b2 : b1) + (B_F - B_O) * 8, t >> 1);
      mbar_expect_tx_z(bars + B_O * 8, 4096, t);
      TR(6)
    }
    const int sn = (st + 1) & 3;
    uint8_t* mw = Mw + sn * 65536;
    asm volatile("" : "+l"(mw));
    if (__builtin_expect((st < DELTA && b % 3 != 0) || (info && b % 3 == 2), 0)) {
      bar_arrive(NB_RD, 384);
      const int col = b / 3 * 16 + c * 4 + ((lane >> 2) & 3), r0 = (lane & 1) * 4 + (lane >> 4) * 2;
      const bool upd = info && b % 3 == 2;
      if (upd) mbar_wait(bars + B_U * 8, nupd & 1, 39);
      uint32_t hv[2];
#pragma unroll
      for (int i = 0; i < 2; i++) {
        const int r = r0 + i, sg = st + 1 - DELTA;
        const void* p = !upd ? (const void*)(mem0 + r * DM + col) : r == (int)(info >> 4) ? (const void*)(g_x2p[sg][1] + col)
                      : (const void*)(g_xs[1] + sg * 32768 + (col >> 6) * 4096 + ((info & 3) * 8 + r) * 128 + ((((col >> 3) ^ r) & 7) << 4) + (col & 7) * 2);
        asm volatile("ld.relaxed.gpu.global.u16 %0, [%1];" : "=r"(hv[i]) : "l"(p) : "memory");
      }
      st_rlx32(mw, hv[0] | hv[1] << 16);
      STAT(1, 0) STAT(2, 0) STAT(4, 0)
    } else {
      const uint32_t flip = (st & 1) ? ~0u : 0u;
      const bool u16 = lane & 16;
      const uint32_t bs = (lane & 4) ? 0x3f800000u : 0x00003f80u, bs0 = (lane & 8) ? 0u : bs, bs1 = (lane & 8) ? bs : 0u;
      STATC(c_rdy)
      wait_clock(tref + gate_p);
      TR(7)
      int it = 0;
      bool all;
#pragma unroll 1
      do {
        const uint4 q0 = ld_rlx128(Pr0), q1 = ld_rlx128(Pr0 + 2048), q2 = ld_rlx128(Pr1), q3 = ld_rlx128(Pr1 + 2048);
        float d0[4] = {0.f, 0.f, 0.f, 0.f}, d1[4] = {0.f, 0.f, 0.f, 0.f};
        mma16816(d0, q0.x, q0.y, q0.z, q0.w, bs0, bs1);
        mma16816(d1, q1.x, q1.y, q1.z, q1.w, bs0, bs1);
        mma16816(d0, q2.x, q2.y, q2.z, q2.w, bs0, bs1);
        mma16816(d1, q3.x, q3.y, q3.z, q3.w, bs0, bs1);
        all = __all_sync(~0u, (int)and3(and_x(q0.x, q1.x, flip), and_x(q2.x, q3.x, flip), 1u));
        const float a0 = d0[0] + d1[0], a1 = d0[1] + d1[1], a2 = d0[2] + d1[2], a3 = d0[3] + d1[3];
        const uint32_t mword = pack_bf16((u16 ? a2 : a0) + __shfl_xor_sync(~0u, u16 ? a0 : a2, 16), (u16 ? a3 : a1) + __shfl_xor_sync(~0u, u16 ? a1 : a3, 16));
        asm volatile("{ .reg .pred p; setp.ne.u32 p, %2, 0; @p st.relaxed.gpu.global.u32 [%0], %1; }" ::"l"(mw), "r"(mword), "r"((uint32_t)all) : "memory");
      } while (__builtin_expect(!all, 0) && ++it < SPIN_LIMIT);
      bar_arrive(NB_RD, 384);
      STATC(c_mst)
      STAT(1, c_rdy - tref) STAT(2, c_mst - tref) STAT(4, it)
      if (!all) fail(44);
      TRV(14, it)
    }
    STAT(0, lds32(sb + C_INFO + 24) - tref) STAT(3, tref)
    nupd += info != 0;
    TR(9)
    {
      const uint32_t ma = l16 + C_M + c * 2048 + mi * 4;
      auto scan = [&](uint32_t m, uint32_t a) { return __vimax3_u32(__vimax3_u32(m, lds32(a), lds32(a + 512)), lds32(a + 1024), lds32(a + 1536)); };
      mbar_wait(bars + B_M0 * 8, (st + 1) & 1, 45);
      bar_arrive(NB_M0, 384);
      STATC(c_g0)
      TR(10)
      uint32_t m = scan(0, ma);
      mbar_wait(bars + B_M1 * 8, (st + 1) & 1, 46);
      bar_arrive(NB_M1, 384);
      STATC(c_g1)
      TR(11)
      m = scan(m, ma + 8192);
      mbar_wait(bars + B_M2 * 8, (st + 1) & 1, 47);
      STATC(c_g2)
      TR(12)
      int it = 0;
      const bool redo = bar_or(NB_M2, 384, scan(m, ma + 16384) == ~0u);
      if (__builtin_expect(redo, 0)) {
#pragma unroll 1
        for (int g = 0; g < 3;) {
          if (!__any_sync(~0u, scan(0, ma + g * 8192) == ~0u)) { g++; continue; }
          give_up(++it, SPIN_LIMIT, 48);
          if (lane == 0) {
            mbar_expect_tx(bars + (B_R + c) * 8, 2048);
            bulk_g2s(sb + C_M + g * 8192 + c * 2048, (const uint8_t*)g_M + sn * 65536 + (lds32(sb + C_POL + sn * 4) ? 4096 : 12288) + g * 16384 + c * 2048,
                     2048, bars + (B_R + c) * 8);
          }
          __syncwarp();
          mbar_wait(bars + (B_R + c) * 8, nretry++ & 1, 49);
        }
        bar_arrive(NB_M0, 384);
      }
      STAT(5, c_g0 - tref) STAT(7, c_g1 - tref) STAT(8, c_g2 - tref)
      STAT(9, clk32() - tref) STAT(6, it + redo * 256)
      TR(13)
      TRV(15, it)
      st_rlx32(Mw + (st & 3) * 65536, ~0u);
    }
  }
}

__device__ __forceinline__ void chain_dma(const uint32_t sb, const int w, const int lane, const uint32_t rank, const int h) {
  const uint32_t bars = sb + C_BAR;
  bar_sync(NB_ALL, 512);
  if (w == 12) { HD(3) }
  bar_sync(NB_ALL, 512);
  if (w == 12) { HD(4) }
  cluster_sync();
  if (w == 12) { HD(5) }
  const int expf_ = EXPF;
  if (w == 12) {
    u64 best = 0;
    uint32_t nx = 0;
    auto load = [&](uint32_t dst, const uint8_t* src, uint32_t bytes) {
      mbar_expect_tx_z(bars + B_XL * 8, bytes, lane >> 1);
      if (lane < 2 && bytes) {
        fence_async_glb();
        bulk_g2s(sb + dst, src, bytes, bars + B_XL * 8);
      }
      __syncwarp();
      mbar_wait(bars + B_XL * 8, nx++ & 1, 52);
    };
    load(C_X + lane * 16384, g_xs[0] + lane * 16384, 16384);
    HD(6)
    bar_arrive(NB_X1, 288); bar_arrive(NB_XB, 288);
#pragma unroll 1
    for (int st = 0; st < NSTEP; st++) {
      const int sg = st - DELTA;
      const bool more = st + 1 < NSEG && !(expf_ & 4);
      uint32_t info = 0;
      if (sg >= 0) {
        const u64 k = wait_keys(g_fl.key[0][sg], lane, 50);
        if (k > best) { best = k; info = 4 | ((key_token(k) >> 3) & 3) | (key_token(k) & 7) << 4; }
      }
      TR(0)
      mbar_wait(bars + (st ? B_X : B_XF) * 8, (st - 1 + !st) & 1, 58);
      sts32(sb + C_INFO + (st & 1) * 4, info);
      if (st > 0) bar_arrive(NB_TA, 192);
      TR(1)
      load(lane ? C_X : C_X + 32768, lane ? g_xs[0] + (st + 1) * 32768 : g_xs[1] + sg * 32768, lane ? (more ? K3 * 1024 : 0) : (sg >= 0 && !(expf_ & 8) ? 32768 : 0));
      bar_arrive(NB_W0, 416);
      TR(2)
      if (__builtin_expect(info, 0)) {
        int it = 0;
        while (ld_rlx32(g_fl.patch[sg]) == 0) { give_up(++it, SPIN_LIMIT, 56); warp_sleep(250); }
        mbar_arrive_z(bars + B_U * 8, lane);
      }
      if (st == NSTEP - 1) break;
      mbar_wait(bars + B_XF * 8, st & 1, 53);
      mbar_wait(bars + (B_M0 + BGATE) * 8, st & 1, 54);
      load(C_X + K3 * 1024, g_xs[0] + (st + 1) * 32768 + K3 * 1024, more && lane == 0 ? 32768 - K3 * 1024 : 0);
      TR(3)
      bar_arrive(NB_XB, 288);
    }
  } else if (w == 13) {
    constexpr uint32_t NP = 8192 / SHIP;
    const uint32_t o = (lane >> 1) * SHIP, own = sb + C_Q + rank * 10240, bt = bars + B_T * 8;
    const uint32_t d2 = 1 + (lane & 1);
    const uint32_t src2 = (rank == 0 ? sb + C_SA : rank == 1 ? own : sb + C_SB) + o;
    const uint32_t skip = (lane & 1) ? 4 | (o >> 11) : 8;
#pragma unroll 1
    for (int st = 0; st < NSTEP; st++) {
      mbar_wait(bars + B_P1 * 8, st & 1, 61);
      fence_async_smem();
      if (st > 0) mbar_wait(bars + B_F * 8, (st - 1) & 1, 60);
      const uint32_t info = lds32(sb + C_INFO + (st & 1) * 4);
      TR(2)
      if (st < NSEG && rank != 0 && lane < 2 * NP && d2 == 1 && !(expf_ & 1)) bulk_s2r(mapa_u32(own + o, 0), sb + C_SA + o, SHIP, mapa_u32(bt, 0));
      __syncwarp();
      TR(3)
      mbar_wait(bars + B_P2 * 8, st & 1, 62);
      fence_async_smem();
      if (st > 0 && (SHIPLATE >> rank & 1)) mbar_wait(bars + B_I * 8, (st - 1) & 1, 64);
      TR(0)
      if (st >= DELTA && lane < 2 * NP && d2 != rank && (info & 7) != skip && !(expf_ & 2)) bulk_s2r(mapa_u32(own + o, d2), src2, SHIP, mapa_u32(bt, d2));
      __syncwarp();
      TR(1)
    }
  } else if (w == 14) {
    const int s0 = rank == 0 ? 0 : DELTA;
    const uint32_t tbytes = (expf_ & (rank ? 2 : 1)) ? 0 : 16384;
    mbar_expect_tx_z(bars + B_T * 8, s0 == 0 ? tbytes : 0, lane);
    {
      const int u = (rank == 2 ? 0 : rank + 1) * 32 + h;
      st_rlx32(&g_fl.pol[u], probe_polarity(g_P + u * 4096, lane) + 1);
    }
#pragma unroll 1
    for (int st = 0; st < NSTEP; st++) {
      const int sg = st - s0;
      const bool act = (unsigned)sg < (unsigned)NSEG;
      mbar_wait(bars + B_OT * 8, st & 1, 70);
      mbar_expect_tx_z(bars + B_T * 8, (unsigned)(sg + 1) < (unsigned)NSEG ? tbytes : 0, lane);
      fence_async_smem();
      const int s1 = rank && st < NSEG - 1 ? st + 1 : st;
      if (s1 != st) mbar_wait(bars + B_X * 8, s1 & 1, 71);
      TR(0)
      if (act && lane == 0 && !(expf_ & (rank ? 32 : 16))) {
        bulk_s2g(g_O[st & (OSLOTS - 1)][rank] + h * 8192, sb + C_OT + (st & 1) * 8192, 8192);
        asm volatile("cp.async.bulk.commit_group;" ::: "memory");
        asm volatile("cp.async.bulk.wait_group 0;" ::: "memory");
        asm volatile("fence.acq_rel.gpu;" ::: "memory");
      }
      __syncwarp();
      if (WLAG && s1 < NSTEP - 1) mbar_wait(bars + (FGATE ? B_M0 + FGATE - 1 : B_I) * 8, (s1 + (FGATE > 0)) & 1, 72);
      if (act && lane == 0) asm volatile("red.relaxed.gpu.global.add.u32 [%0], 1;" ::"l"(&g_fl.oflag[rank][sg][h >> 2]) : "memory");
      __syncwarp();
      TR(1)
    }
  } else {
    mbar_arrive_z(bars + B_M0 * 8, lane); mbar_arrive_z(bars + B_M1 * 8, lane); mbar_arrive_z(bars + B_M2 * 8, lane);
    const uint32_t gate_g = GATE_G, gate_m = GATE_M;
    uint32_t nupd = 0, late = 0;
#pragma unroll 1
    for (int st = 0; st < NSTEP - 1; st++) {
      mbar_wait(bars + B_X * 8, st & 1, 75);
      if (st < 4) { HD(8 + st) }
      if (st == NSTEP - 2) { HD(12) }
      mbar_wait(bars + B_T * 8, st & 1, 77);
      const uint32_t now = gtime() & ~31u, tag = (st + 1) & 31;
      if (lane == 0) st_rlx32(&g_fl.stamp[blockIdx.x], (now + late) | tag);
      late = 0;
      __syncwarp();
      wait_clock(clk32() + 550);
      uint32_t s0, s1, s2;
      int it = 0;
#pragma unroll 1
      do {
        s0 = ld_rlx32(&g_fl.stamp[lane]) ^ tag; s1 = ld_rlx32(&g_fl.stamp[32 + lane]) ^ tag; s2 = ld_rlx32(&g_fl.stamp[64 + lane]) ^ tag;
        give_up(it++, SPIN_LIMIT, 76);
      } while (__any_sync(~0u, ((s0 | s1 | s2) & 31) != 0));
      const uint32_t tref = now + __reduce_max_sync(~0u, __vimax3_s32((int)(s0 - now), (int)(s1 - now), (int)(s2 - now)));
      const uint32_t g0 = gtime();
      uint32_t g1, c1;
      it = 0;
      do { g1 = gtime(); c1 = clk32(); } while (g1 == g0 && ++it < 64);
      c1 -= (g1 - tref) * 7 / 4;
      sts32(sb + C_INFO + 12, c1);
      TR(0)
      bar_sync(NB_TA, 192);
      const int sn = (st + 1) & 3;
      const uint8_t* src = (const uint8_t*)g_M + sn * 65536 + (lds32(sb + C_POL + sn * 4) ? 4096 : 12288);
      c1 += gate_m;
      if (__builtin_expect(lds32(sb + C_INFO + ((st + 1) & 1) * 4), 0)) {
        late = rank == 2 ? 160 : 0;
        mbar_wait(bars + B_U * 8, nupd++ & 1, 78);
        const uint32_t c2 = clk32() + 1300;
        if ((int)(c2 - c1) > 0) c1 = c2;
      }
      const int d = (int)(c1 - 600 - clk32());
      if (d > 0) warp_sleep(d / 4);
      mbar_expect_tx_z(bars + (B_M0 + lane) * 8, 8192, lane / 3);
      if (lane == 0) {
#pragma unroll
        for (int g = 0; g < 3; g++) {
          wait_clock(c1 + g * gate_g);
          bulk_g2s(sb + C_M + g * 8192, src + g * 16384, 8192, bars + (B_M0 + g) * 8);
          if (g == IGRP) mbar_arrive_z(bars + B_I * 8, 0);
        }
      }
      __syncwarp();
      TR(3)
    }
  }
}

__global__ void __cluster_dims__(3, 1, 1) __launch_bounds__(512, 1)
chain_kernel(const bf16* __restrict__ Wq, const bf16* __restrict__ Wk, const bf16* __restrict__ Wv,
             const bf16* __restrict__ Wo, const bf16* __restrict__ mem0) {
  extern __shared__ __align__(1024) uint8_t smem_raw[];
  const uint32_t sb = (smem_u32(smem_raw) + 1023) & ~1023u;
  const int tid = threadIdx.x, lane = tid & 31;
  const int w = __shfl_sync(~0u, tid >> 5, 0);
  uint32_t rank;
  asm volatile("mov.u32 %0, %%cluster_ctarank;" : "=r"(rank));
  const int h = blockIdx.x / 3;
  asm volatile("griddepcontrol.launch_dependents;" ::: "memory");
  TG(0)
  if (tid == 0) {
    const uint32_t bars = sb + C_BAR;
    mbar_init(bars + B_M0 * 8, 1); mbar_init(bars + B_M1 * 8, 1); mbar_init(bars + B_M2 * 8, 1);
    for (int i = 0; i < 4; i++) mbar_init(bars + (B_R + i) * 8, 1);
    mbar_init(bars + B_X * 8, 9); mbar_init(bars + B_O * 8, 2); mbar_init(bars + B_T * 8, 1); mbar_init(bars + B_F * 8, 2);
    mbar_init(bars + B_XL * 8, 2); mbar_init(bars + B_U * 8, 1);
    mbar_init(bars + B_P1 * 8, 8); mbar_init(bars + B_P2 * 8, 8); mbar_init(bars + B_OT * 8, 3); mbar_init(bars + B_XF * 8, 8); mbar_init(bars + B_I * 8, 1);
    asm volatile("fence.mbarrier_init.release.cluster;" ::: "memory");
  }
  {
    cp16(sb + C_OT + tid * 16, mem0 + (tid & 7) * DM + (tid >> 3) * 8);
    const bf16* W1 = (rank == 0 ? Wq : rank == 1 ? Wk : Wv) + h * 128;
#pragma unroll 4
    for (int cidx = tid; cidx < 512 * 16; cidx += 512) {
      const int d = cidx >> 4, q = cidx & 15;
      cp16(sb + C_X + d * W_STRIDE + q * 16, W1 + (size_t)d * HD + q * 8);
    }
    const int nt = rank == 2 ? 2 : 3;
    for (int cidx = tid; cidx < nt * 1024; cidx += 512) {
      const int tl = cidx >> 10, e = (cidx >> 3) & 127, q = cidx & 7;
      const int es = (e & ~30) | ((e & 6) << 2) | ((e >> 2) & 6);
      cp16(sb + C_WO + tl * 16384 + e * 128 + ((q ^ (e & 7)) << 4), Wo + (size_t)(h * 128 + es) * DM + (tl * 3 + rank) * 64 + q * 8);
    }
    asm volatile("cp.async.commit_group;" ::: "memory");
    if (w == 0) { HD(0) }
    if (w == 0) { HD(1) }
    asm volatile("cp.async.wait_group 0;" ::: "memory");
    fence_async_smem();
    __syncthreads();
    if (w == 0) { HD(2) }
  }
  if (w < 8) {
    reg_inc<184>();
    chain_proj(sb, w, lane, rank);
    TG(1)
    TRDUMP
    cluster_sync();
  } else if (w < 12) {
    reg_dec<120>();
    chain_mem(sb, w, lane, rank, h, mem0);
    STATDUMP
    TRDUMP
    cluster_sync();
  } else {
    reg_dec<24>();
    chain_dma(sb, w, lane, rank, h);
    TRDUMP
    cluster_sync();
  }
}
#undef TRC
#undef TRS

constexpr int K_BAR = 0, K_LN = 128, K_FH = 320, K_FS = 512, K_FY = 1536;
constexpr int K_W = 3072;
constexpr int K_O = K_W + 3 * 49152;
constexpr int K_ST = K_O + 65536;
constexpr int K_SMEM = K_ST + 16384;
static_assert(K_SMEM <= 232448 && 512 * W_STRIDE <= 3 * 49152, "shared memory");
enum { KB_FULL = 0, KB_EMPTY = 2, KB_OK = 4, KB_GO = 7, KB_ST = 10, KB_REL = 12 };
enum { KN_ST = 1, KN_ST1, KN_REL, KN_FFN, KN_INIT, KN_RES, KN_RES1, KN_CAND, KN_TAKEN, KN_FF2 };
#define GATE_R 850
struct WorkerParams {
  const bf16 *x0, *Wo, *w_r, *w_gate, *w_up, *w_down;
  bf16* out;
};
#define TRC (96 + blockIdx.x)
#define FT(e)
#define QUIET 4900
__device__ __forceinline__ void quiet_until(uint32_t t) {
  int d;
  while ((d = (int)(t - clk32())) > 0) warp_sleep(min(d / 3 + 20, 1000));
}
#define FOR_UNITS _Pragma("unroll 1") for (int st = 0, n = 0; st < WSTEP; st++) \
                  _Pragma("unroll 1") for (int v = st < NSEG ? 0 : st < WSTEP - 1 ? 1 : 2, sg = v ? st - WD : st; v < (st >= WD ? 3 : 1); v++, n++, sg = st - WD)

template <int ACC>
__device__ __forceinline__ void wg_ss8(float (&d)[4], uint64_t da, uint64_t db) {
  asm volatile("wgmma.mma_async.sync.aligned.m64n8k16.f32.bf16.bf16 {%0,%1,%2,%3}, %4, %5, %6, 1, 1, 1, 0;" : O4(d, 0) : "l"(da), "l"(db), "n"(ACC));
}
template <int NU>
__device__ __forceinline__ void ffn_slice(uint32_t sb, int t, const bf16* yrow, int ev) {
  const int lane = t & 31, c = t >> 5;
  FT(1)
  {
    const uint2 r = ld_rlx64(yrow + t * 4);
    asm volatile("st.shared.v2.b32 [%0], {%1,%2};" ::"r"(sb + K_FY + ((t >> 1) & 31) * 32 + (t >> 6) * 16 + (t & 1) * 8), "r"(r.x), "r"(r.y) : "memory");
  }
  fence_async_smem();
  bar_sync(KN_FFN, 128);
  FT(2)
  {
    float g[NU][4];
    const uint64_t da = mk_desc(sb + K_W, 16384, 512, 2), db = mk_desc(sb + K_FY, 32, 0, 0);
    wg_fence();
#pragma unroll
    for (int i = 0; i < 16; i++)
#pragma unroll
      for (int u = 0; u < NU; u++) { if (i == 0) wg_ss8<0>(g[u], da + u * 3072, db); else wg_ss8<1>(g[u], da + u * 3072 + i * 64, db + i * 4); }
    wg_commit();
    wg_wait<0>();
#pragma unroll
    for (int u = 0; u < NU; u++) {
      acc_fence(g[u]);
      if ((lane & 3) == 0) {
        const uint32_t a = sb + K_FS + u * 256 + c * 64 + lane;
        sts32(a, __float_as_uint(c < 2 ? g[u][0] : g[u][1])); sts32(a + 32, __float_as_uint(c < 2 ? g[u][2] : g[u][3]));
      }
    }
  }
  FT(3)
  bar_sync(KN_FFN, 128);
  {
    const uint32_t pa = sb + K_FS + c * 256 + lane * 4;
    const float gt = round_bf16(__uint_as_float(lds32(pa)) + __uint_as_float(lds32(pa + 128)));
    const float up = __shfl_xor_sync(~0u, gt, 16);
    const uint32_t hv = pack_bf16(round_bf16(__fdividef(gt, 1.f + __expf(-gt))) * up, 0.f);
    if (lane < 16) asm volatile("st.shared.b16 [%0], %1;" ::"r"(sb + K_FH + (c * 16 + lane) * 2), "h"((unsigned short)hv) : "memory");
  }
  fence_async_smem();
  bar_sync(KN_FFN, 128);
  FT(4)
#pragma unroll 1
  for (int hf = 0; hf < 2; hf++) {
    float o[4][4];
    const uint64_t da = mk_desc(sb + K_W + 32768 + hf * 8192, 16, 1024, 1), db = mk_desc(sb + K_FH, 16, 0, 0);
    wg_fence();
#pragma unroll
    for (int u = 0; u < NU; u++)
#pragma unroll
      for (int j = 0; j < 4; j++) { if (u == 0) wg_ss8<0>(o[j], da + j * 128, db); else wg_ss8<1>(o[j], da + u * 3072 + j * 128, db + u * 2); }
    wg_commit();
    wg_wait<0>();
    float lo = 0.f, hi = 0.f;
#pragma unroll
    for (int j = 0; j < 4; j++) {
      acc_fence(o[j]);
      const float a = __shfl_sync(~0u, o[j][0], lane & 28), b = __shfl_sync(~0u, o[j][2], lane & 28);
      if ((lane & 3) == j) { lo = a; hi = b; }
    }
    float* p = &g_fl.upd[ev][hf * 256 + (lane & 3) * 64 + c * 16 + (lane >> 2)];
    asm volatile("red.relaxed.gpu.global.add.f32 [%0], %1; red.relaxed.gpu.global.add.f32 [%0 + 32], %2;" ::"l"(p), "f"(lo), "f"(hi) : "memory");
  }
  FT(5)
  bar_sync(KN_FFN, 128);
  if (t == 96) red_release(g_fl.ffncnt[ev]);
  __syncwarp();
}
__device__ __forceinline__ uint4 pair_ln(uint4 r, float& e, uint32_t sl, int bar, int t) {
  const float x[8] = {bf_lo(r.x), bf_hi(r.x), bf_lo(r.y), bf_hi(r.y), bf_lo(r.z), bf_hi(r.z), bf_lo(r.w), bf_hi(r.w)};
  const float s = ((x[0] + x[1]) + (x[2] + x[3])) + ((x[4] + x[5]) + (x[6] + x[7]));
  const float q = (fmaf(x[0], x[0], x[1] * x[1]) + fmaf(x[2], x[2], x[3] * x[3])) + (fmaf(x[4], x[4], x[5] * x[5]) + fmaf(x[6], x[6], x[7] * x[7]));
  const bool u16 = t & 16, u8 = t & 8;
  const float a = (u16 ? q : s) + __shfl_xor_sync(~0u, u16 ? s : q, 16), b = e + __shfl_xor_sync(~0u, e, 16);
  float v = (u8 ? b : a) + __shfl_xor_sync(~0u, u8 ? a : b, 8);
  v += __shfl_xor_sync(~0u, v, 4); v += __shfl_xor_sync(~0u, v, 2); v += __shfl_xor_sync(~0u, v, 1);
  sts32(sl + (t >> 3) * 4, __float_as_uint(v));
  bar_sync(bar, 64);
  const uint4 s0 = lds128(sl), s1 = lds128(sl + 16);
  const float m = (__uint_as_float(s0.x) + __uint_as_float(s1.x)) * (1.f / DM), m2 = (__uint_as_float(s0.z) + __uint_as_float(s1.z)) * (1.f / DM);
  e = __uint_as_float(s0.y) + __uint_as_float(s1.y);
  float rs;
  asm("rsqrt.approx.ftz.f32 %0, %1;" : "=f"(rs) : "f"(fmaxf(fmaf(-m, m, m2), 0.f) + 1e-5f));
  return make_uint4(pack_bf16((x[0] - m) * rs, (x[1] - m) * rs), pack_bf16((x[2] - m) * rs, (x[3] - m) * rs),
                    pack_bf16((x[4] - m) * rs, (x[5] - m) * rs), pack_bf16((x[6] - m) * rs, (x[7] - m) * rs));
}
__device__ __forceinline__ uint32_t score_bits(float r) {
  const uint32_t b = pack_bf16(0.f, r);
  return (b & 0x80000000u) ? ~b : (b | 0x80000000u);
}

__global__ void __launch_bounds__(640, 1) worker_kernel(const __grid_constant__ WorkerParams prm) {
  extern __shared__ __align__(1024) uint8_t smem_raw[];
  const uint32_t sb = smem_u32(smem_raw);
  if (sb & 1023) __trap();
  const int tid = threadIdx.x, lane = tid & 31;
  const int w = __shfl_sync(~0u, tid >> 5, 0);
  const int me = blockIdx.x, kb = me >> 2, cb = me & 3;
  const bool full = me < 32;
  const uint32_t bars = sb + K_BAR;
  TG(0)
  if (tid == 0) {
    for (int i = 0; i < 2; i++) { mbar_init(bars + (KB_FULL + i) * 8, 1); mbar_init(bars + (KB_EMPTY + i) * 8, 1); }
    for (int i = 0; i < 9; i++) mbar_init(bars + (KB_OK + i) * 8, i < 3 ? 2 : 1);
    sts32(sb + K_LN + 144, 0);
    asm volatile("fence.mbarrier_init.release.cluster;" ::: "memory");
  }
  if (full) {
    const bf16* W1 = prm.Wo + (size_t)kb * 512 * DM + cb * 128;
#pragma unroll 4
    for (int cidx = tid; cidx < 512 * 16; cidx += 640) {
      const int d = cidx >> 4, q = cidx & 15;
      cp16(sb + K_W + d * W_STRIDE + q * 16, W1 + (size_t)d * DM + q * 8);
    }
    asm volatile("cp.async.commit_group;" ::: "memory");
    asm volatile("cp.async.wait_group 0;" ::: "memory");
  }
  fence_async_smem();
  __syncthreads();
  if (w < 8) {
    reg_inc<176>();
    if (full) {
      uint32_t wA[32][4];
      load_wfrags(wA, sb + K_W, w, lane);
      bar_arrive(KN_INIT, 384);
      const uint32_t sp = pin(sb + K_ST + ((lane >> 4) * 8 + (lane & 7)) * 256 + (((2 * w + ((lane >> 3) & 1)) ^ (lane & 7)) << 4));
      const uint32_t tm = pin(lane < 4 ? 0x00010001u : 0u);
      FOR_UNITS {
        float d[16];
        mbar_wait(bars + (KB_FULL + (n & 1)) * 8, (n >> 1) & 1, 81);
        TR(4 * v)
        const uint64_t db = mk_desc(sb + K_O + (n & 1) * 32768, 128, 2048, 0);
        wg_fence();
#pragma unroll
        for (int ks = 0; ks < 32; ks++) {
          if (ks == 0) wg_rs32<0, 0>(d, wA[ks], db);
          else wg_rs32<0, 1>(d, wA[ks], db + (ks >> 3) * 512 + (ks & 7) * 16);
        }
        wg_commit();
        mbar_wait(bars + (KB_ST + (n & 1)) * 8, ((n >> 1) & 1) ^ 1, 82);
        wg_wait<0>();
        acc_fence(d);
        TR(4 * v + 1)
        const uint32_t tag = (sg & 2) ? 0u : tm;
        uint32_t pk[8];
#pragma unroll
        for (int i = 0; i < 8; i++) pk[i] = (pack_bf16(d[2 * i], d[2 * i + 1]) & ~tm) | tag;
        stsm4t(sp + (n & 1) * 8192, pk[0], pk[1], pk[2], pk[3]);
        stsm4t(sp + (n & 1) * 8192 + 4096, pk[4], pk[5], pk[6], pk[7]);
        bar_arrive(KN_ST + (n & 1), 288);
        TR(4 * v + 2)
      }
    }
  } else if (w < 12) {
    reg_dec<56>();
    if (full) {
      const int ly = (w >> 1) & 1, t = pin(tid & 63);
      const uint32_t so = pin((t >> 4) * 8192 + me * 256 + (((t & 15) ^ (me & 7)) << 4));
      int sstar = -1;
      uint32_t sl = sb + K_LN + ly * 64;
      float rr = 0.f;
      int kprev = -1;
      auto records = [&](int sg, uint32_t off) {
        int it = 0;
        while (__any_sync(~0u, (int)lds32(sb + K_LN + 144) <= sg)) { give_up(++it, SPIN_LIMIT, 86); warp_sleep(50); }
        return lds32(sb + K_LN + off);
      };
#pragma unroll 1
      for (int n = ly ? 2 * WD : 0; n < 2 * WSTEP; n++) {
        const int st = n >> 1, v = (n & 1) ? 2 : ly, sg = v ? st - WD : st, tok = sg * 32 + me;
        if (n == 2 * NSEG) bar_sync(KN_INIT, 128);
        if (n == 2 * NSEG + 2) sstar = records(NSEG - 1, 156);
        if (v == 2 ? sg < 0 || (st < NSEG ? st & 1 : 0) != ly : sg >= NSEG - v) continue;
        const bf16* xin = v ? g_rows[tok][0][2] : prm.x0 + tok * DM;
        if (v == 2 && ((records(sg, 148 + (sg >> 5) * 4) >> (sg & 31)) & 1)) xin = g_x2p[sg][0];
        const uint8_t* src = g_part[v] + (sg & 1) * (32 * 8192) + so;
        const uint32_t flip = (sg & 2) ? ~0u : 0u;
        mbar_wait(bars + (KB_GO + v) * 8, sg & 1, 87);
        TR(4 * v)
        uint4 p[8], x;
        int it = 0;
#pragma unroll 1
        do {
#pragma unroll
          for (int k = 0; k < 8; k++) p[k] = ld_rlx128(src + k * 32768);
          x = ld_rlx128(((WEXP & 2) ? prm.x0 : xin) + t * 8);
          give_up(it++, SPIN_LIMIT, 85);
        } while (__builtin_expect(!__all_sync(~0u, (int)and3(and3(and_x(p[0].x, p[1].x, flip), and_x(p[2].x, p[3].x, flip), 1u),
                                                             and_x(p[4].x, p[5].x, flip), and_x(p[6].x, p[7].x, flip))), 0));
        mbar_arrive_z(bars + (KB_OK + v) * 8, t & 31);
#define P8(h, f) (((h(p[0].f) + h(p[1].f)) + (h(p[2].f) + h(p[3].f))) + ((h(p[4].f) + h(p[5].f)) + (h(p[6].f) + h(p[7].f))))
#define X8(f) x.f = add_bf16x2(x.f, pack_bf16(P8(bf_lo, f), P8(bf_hi, f)));
        X8(x) X8(y) X8(z) X8(w)
#undef X8
#undef P8
        TRV(12 + v, it - 1)
        TR(4 * v + 1)
        bf16* dst = g_rows[tok][v][0] + t * 8;
        *(uint4*)dst = x;
        const uint4 wr = ld_rlx128(prm.w_r + t * 8);
        sl ^= 32;
        uint4 y = pair_ln(x, rr, sl, KN_RES + ly, t);
        *(uint4*)(dst + DM) = y;
        x = make_uint4(add_bf16x2(x.x, y.x), add_bf16x2(x.y, y.y), add_bf16x2(x.z, y.z), add_bf16x2(x.w, y.w));
        *(uint4*)(v == (sg < sstar ? 1 : 2) ? prm.out + tok * DM + t * 8 : dst + 2 * DM) = x;
        asm volatile("{ .reg .pred p; setp.eq.u32 p, %2, 0; @p st.relaxed.gpu.global.u64 [%0], %1; }" ::"l"(&g_fl.key[0][0][0] + max(kprev, 0)),
                     "l"((u64)score_bits(rr) << 32 | (uint32_t)~(kprev & (NTOK - 1))), "r"(t | (kprev < 0)) : "memory");
        kprev = v * NTOK + tok;
        rr = (fmaf(bf_lo(y.x), bf_lo(wr.x), bf_hi(y.x) * bf_hi(wr.x)) + fmaf(bf_lo(y.y), bf_lo(wr.y), bf_hi(y.y) * bf_hi(wr.y))) +
             (fmaf(bf_lo(y.z), bf_lo(wr.z), bf_hi(y.z) * bf_hi(wr.z)) + fmaf(bf_lo(y.w), bf_lo(wr.w), bf_hi(y.w) * bf_hi(wr.w)));
        if (v == 0 || st >= NSEG) {
          sl ^= 32;
          y = pair_ln(x, rr, sl, KN_RES + ly, t);
          if (v == 0) *(uint4*)(g_xs[1] + sg * 32768 + (t >> 3) * 4096 + me * 128 + (((t ^ me) & 7) << 4)) = y;
          sts32(sb + K_LN + 128 + ly * 4, score_bits(rr));
          bar_arrive(KN_REL, v == 0 || st == WSTEP - 1 ? 96 : 160);
          kprev = -1;
        }
        TR(4 * v + 2)
      }
    }
  } else if (w < 16) {
    reg_dec<48>();
    const int t = tid - 384, nu = full ? 3 : 4;
    if (full) bar_sync(KN_INIT, 384);
    {
      const int j0 = (full ? me * 3 : 96 + (me - 32) * 4) * 16;
#pragma unroll 1
      for (int i = t; i < nu * 3072; i += 128) {
        const int u = i / 3072, r = i - u * 3072;
        const int q = (r ^ (r >> 3)) & 3, r2 = r - 2048;
        const bf16* src = r < 2048 ? ((q & 2) ? prm.w_up : prm.w_gate) + (size_t)(r >> 2) * FF + j0 + u * 16 + (q & 1) * 8
                                   : prm.w_down + (size_t)(j0 + u * 16 + ((r2 >> 3) & 15)) * DM + (r2 >> 7) * 64 + ((r2 ^ (r2 >> 3)) & 7) * 8;
        cp16(sb + K_W + i * 16, src);
      }
      asm volatile("cp.async.wait_all;" ::: "memory");
    }
    bar_arrive(KN_TAKEN, 160);
#pragma unroll 1
    while (true) {
      bar_sync(KN_CAND, 160);
      const uint4 cand = lds128(sb + K_LN + 160);
      const u64 k = (u64)cand.y << 32 | cand.x;
      const int ev = cand.z, ver = cand.w & 3, tok = key_token(k);
      const bool last = cand.w & 4;
      if (!last) {
        bar_arrive(KN_TAKEN, 160);
        FT(0)
        if (full) ffn_slice<3>(sb, t, g_rows[tok][ver][1], ev); else ffn_slice<4>(sb, t, g_rows[tok][ver][1], ev);
      }
      if ((tok & 31) == me && (ver == 0 || last)) {
        if (t < 64) {
          FT(6)
          uint4 x = ld_rlx128(g_rows[tok][ver][0] + t * 8);
          const uint4 y = ld_rlx128(g_rows[tok][ver][1] + t * 8);
          const float sig = round_bf16(__fdividef(1.f, 1.f + __expf(-key_score(k))));
          int it = 0;
          while (ld_rlx32(g_fl.ffncnt[ev]) < NWORK) { give_up(++it, SPIN_LIMIT, 80); warp_sleep(40); }
          const uint4 u0 = ld_rlx128(&g_fl.upd[ev][t * 8]), u1 = ld_rlx128(&g_fl.upd[ev][t * 8 + 4]);
          auto upd = [&](uint32_t xw, uint32_t yw, uint32_t a, uint32_t b) {
            const uint32_t r = pack_bf16(__uint_as_float(a), __uint_as_float(b));
            return add_bf16x2(xw, add_bf16x2(yw, pack_bf16(bf_lo(r) * sig, bf_hi(r) * sig)));
          };
          x = make_uint4(upd(x.x, y.x, u0.x, u0.y), upd(x.y, y.y, u0.z, u0.w), upd(x.z, y.z, u1.x, u1.y), upd(x.w, y.w, u1.z, u1.w));
          FT(7)
          *(uint4*)((ver ? prm.out + tok * DM : g_x2p[ev][0]) + t * 8) = x;
          if (ver == 0) {
            float e = 0.f;
            *(uint4*)(g_x2p[ev][1] + t * 8) = pair_ln(x, e, sb + K_FS, KN_FF2, t);
            bar_sync(KN_FF2, 64);
            if (t == 0) st_release32(g_fl.patch[ev], 1);
            __syncwarp();
          }
        }
      }
      if (ev == NSEG && !last && full) {
        const int nc = min((int)lds32(sb + K_LN + 156), NSEG + 1 - WD);
#pragma unroll 1
        for (int s0 = (t >> 6) * 4; s0 < nc; s0 += 8) {
          uint4 q[4];
#pragma unroll
          for (int i = 0; i < 4; i++) q[i] = ld_rlx128(g_rows[min(s0 + i, nc - 1) * 32 + me][1][2] + (t & 63) * 8);
#pragma unroll
          for (int i = 0; i < 4; i++) *(uint4*)(prm.out + (min(s0 + i, nc - 1) * 32 + me) * DM + (t & 63) * 8) = q[i];
        }
      }
      FT(8)
      if (last) break;
    }
  } else {
    reg_dec<24>();
    if (w == 16) {
      u64 best = 0, mask = 0;
      int sstar = 0;
      uint32_t ver = 0, ev = 0;
      auto post = [&](uint32_t cmd) {
        bar_sync(KN_TAKEN, 160);
        sts128(sb + K_LN + 160, make_uint4((uint32_t)best, (uint32_t)(best >> 32), ev, ver | cmd));
        bar_arrive(KN_CAND, 160);
      };
      u64 accn = 0, acca = 0;
      uint32_t recs = 0;
      int j = 0;
      uint32_t tq = clk32();
#pragma unroll 1
      for (int st = 0; st < WSTEP; st++) {
        const u64* keys = st < NSEG ? g_fl.key[0][st] : g_fl.key[2][st - WD];
        const bool early = __any_sync(~0u, ld_rlx32(keys + lane) == 0);
        if (early && st < NSEG) quiet_until(tq);
        u64 k = wait_keys(keys, lane, 91);
        if (early) tq = clk32() + QUIET;
        if (st < NSEG) {
          const bool rec = k > best;
          recs &= ~(1u << (st & 31));
          if (rec) {
            best = k; ev = sstar = st;
            recs |= 1u << (st & 31);
            if ((key_token(k) & 31) == me) mask |= 1ull << st;
          }
          if (lane == 0) sts128(sb + K_LN + 144, make_uint4(st + 1, (uint32_t)mask, (uint32_t)(mask >> 32), sstar));
          __syncwarp();
          if (rec) post(0);
        }
#pragma unroll 1
        for (; j <= st - WD - (st < NSEG ? 2 : 0); j++) {
          u64 kn = 1, kc;
          int it = 0;
          do {
            if (j < NSEG - 1) asm volatile("ld.relaxed.gpu.global.u64 %0, [%1];" : "=l"(kn) : "l"(&g_fl.key[1][j][lane]) : "memory");
            asm volatile("ld.relaxed.gpu.global.u64 %0, [%1];" : "=l"(kc) : "l"(&g_fl.key[2][j][lane]) : "memory");
            give_up(it++, SPIN_LIMIT, 92);
          } while (__any_sync(~0u, kn == 0 || kc == 0));
          if ((recs >> (j & 31)) & 1) acca = accn;
          if (kc > acca) acca = kc;
          if (kn > accn) accn = kn;
        }
        if (st >= NSEG) {
          const u64 m = j <= sstar ? accn : acca;
          const uint32_t hi = __reduce_max_sync(~0u, (uint32_t)(m >> 32));
          k = (u64)hi << 32 | __reduce_max_sync(~0u, (uint32_t)(m >> 32) == hi ? (uint32_t)m : 0u);
          if (st == NSEG || k != best) {
            best = k; ev = st;
            ver = (key_token(k) >> 5) < sstar ? 1 : 2;
            post(0);
          }
        }
      }
      HD(6)
      post(4);
    } else if (!full) {
    } else if (w == 17) {
      uint32_t tq = clk32();
      FOR_UNITS {
        if (ld_rlx32(&g_fl.oflag[v][sg][kb]) < 4) {
          if (v == (st < NSEG ? 0 : 1) && st < WSTEP - 3) quiet_until(tq);
          wait_count(&g_fl.oflag[v][sg][kb], 4, 84);
          if (v == (st < NSEG ? 0 : 1)) tq = clk32() + QUIET;
        }
        mbar_wait(bars + (KB_EMPTY + (n & 1)) * 8, ((n >> 1) & 1) ^ 1, 83);
        TR(v)
        if (st == WSTEP - 1) { HD(v) }
        if (lane == 0) {
          fence_async_glb();
          mbar_expect_tx(bars + (KB_FULL + (n & 1)) * 8, (WEXP & 4) ? 4096 : 32768);
          bulk_g2s(sb + K_O + (n & 1) * 32768, g_O[(v ? sg + DELTA : sg) & (OSLOTS - 1)][v] + kb * 32768, (WEXP & 4) ? 4096 : 32768, bars + (KB_FULL + (n & 1)) * 8);
        }
        __syncwarp();
      }
    } else if (w == 18) {
      FOR_UNITS {
        if (sg > 0) mbar_wait(bars + (KB_OK + v) * 8, (sg - 1) & 1, 90);
        bar_sync(KN_ST + (n & 1), 288);
        fence_async_smem();
        const uint32_t tg = clk32() + GATE_R;
        if (lane == 0) {
          bulk_s2g(g_part[v] + ((sg & 1) * 32 + me) * 8192, sb + K_ST + (n & 1) * 8192, 8192);
          asm volatile("cp.async.bulk.commit_group;" ::: "memory");
          mbar_arrive_z(bars + (KB_EMPTY + (n & 1)) * 8, 0);
          asm volatile("cp.async.bulk.wait_group.read 0;" ::: "memory");
        }
        __syncwarp();
        mbar_arrive_z(bars + (KB_ST + (n & 1)) * 8, lane);
        TR(v)
        if (v == (st < NSEG ? 0 : st < WSTEP - 1 ? 1 : 2) && st > 0) mbar_wait(bars + KB_REL * 8, (st - 1) & 1, 93);
        wait_clock(tg);
        if (st == WSTEP - 1) { HD(2 + v) }
        mbar_arrive_z(bars + (KB_GO + v) * 8, lane);
      }
    } else {
#pragma unroll 1
      for (int st = 0; st < WSTEP; st++) {
        const int sg = st < NSEG ? st : st - WD;
        const bool both = st >= NSEG && st < WSTEP - 1;
        bar_sync(KN_REL, both ? 160 : 96);
        const uint32_t ob = __shfl_sync(~0u, lds32(sb + K_LN + 128), 0), obn = __shfl_sync(~0u, lds32(sb + K_LN + 132), 0);
        mbar_arrive_z(bars + KB_REL * 8, lane);
        if (st == WSTEP - 1) { HD(5) }
        if (lane == 0) {
          if (both) asm volatile("st.relaxed.gpu.global.u64 [%0], %1;" ::"l"(&g_fl.key[1][sg][me]), "l"((u64)obn << 32 | (uint32_t)~(sg * 32 + me)) : "memory");
          st_release_u64(&g_fl.key[st < NSEG ? 0 : 2][sg][me], (u64)ob << 32 | (uint32_t)~(sg * 32 + me));
        }
        __syncwarp();
        TR(0)
      }
    }
  }
}
#undef TRC

bool g_ready;

}

extern "C" void kernel_launch(void* const* d_in, const int* in_sizes, int n_in, void* d_out, int out_size) {
  (void)in_sizes; (void)n_in; (void)out_size;
  const bf16* x0 = (const bf16*)d_in[0];
  const bf16* mem0 = (const bf16*)d_in[1];
  const bf16* Wq = (const bf16*)d_in[2];
  const bf16* Wk = (const bf16*)d_in[3];
  const bf16* Wv = (const bf16*)d_in[4];
  const bf16* Wo = (const bf16*)d_in[5];
  if (!g_ready) {
    cudaFuncSetAttribute(worker_kernel, cudaFuncAttributeMaxDynamicSharedMemorySize, K_SMEM);
    cudaFuncSetAttribute(chain_kernel, cudaFuncAttributeMaxDynamicSharedMemorySize, C_SMEM);
    g_ready = true;
  }
  cudaStream_t st = cudaStreamPerThread;
  prep_kernel<<<NTOK / 8, 256, 0, st>>>(x0, Wq, Wk, Wv, Wo);
  chain_kernel<<<96, 512, C_SMEM, st>>>(Wq, Wk, Wv, Wo, mem0);
  cudaLaunchAttribute pdl[1];
  pdl[0].id = cudaLaunchAttributeProgrammaticStreamSerialization;
  pdl[0].val.programmaticStreamSerializationAllowed = 1;
  WorkerParams wp;
  wp.x0 = x0; wp.Wo = Wo; wp.w_r = (const bf16*)d_in[8]; wp.w_gate = (const bf16*)d_in[9]; wp.w_up = (const bf16*)d_in[10];
  wp.w_down = (const bf16*)d_in[11]; wp.out = (bf16*)d_out;
  cudaLaunchConfig_t cfg = {};
  cfg.gridDim = dim3(NWORK); cfg.blockDim = dim3(640); cfg.dynamicSmemBytes = K_SMEM; cfg.stream = st;
  cfg.attrs = pdl; cfg.numAttrs = 1;
  cudaLaunchKernelEx(&cfg, worker_kernel, wp);
}
```

```cpp
#include <cuda_runtime.h>
#include <cuda_bf16.h>
#include <stdint.h>

namespace {

typedef __nv_bfloat16 bf16;
typedef unsigned long long u64;

constexpr int NTOK = 2048, DM = 512, HD = 4096, NSEG = 64, FF = 1792;
#define DELTA 5
constexpr int NSTEP = NSEG + DELTA;
#define WLAG 1
constexpr int WD = DELTA + WLAG, WSTEP = NSEG + WD;
constexpr int SPIN_LIMIT = 40000;
constexpr int MBAR_LIMIT = 20000;
constexpr int NWORK = 36;
constexpr int OSLOTS = 8;
#define SLP_C 100
#define SLP_K 200
#define WEXP 0

__device__ __align__(1024) uint8_t g_xs[2][NSEG * 32768];
__device__ __align__(1024) uint8_t g_O[OSLOTS][3][32 * 8192];
__device__ __align__(1024) uint8_t g_part[3][2 * 32 * 8192];
__device__ __align__(1024) bf16 g_rows[NTOK][3][3][DM];
__device__ __align__(1024) bf16 g_x2p[NSEG][2][DM];
struct Flags {
  uint32_t pol[96];
  uint32_t stamp[96];
  uint32_t oflag[3][NSEG][8];
  uint32_t ffncnt[WSTEP][8];
  uint32_t patch[NSEG][8];
  u64 key[3][NSEG][32];
  float upd[WSTEP][DM];
};
struct Exchange { uint32_t M[4 * 16384], P[96 * 4096]; Flags fl; };
__device__ __align__(65536) Exchange g_ex;
#define g_M g_ex.M
#define g_P g_ex.P
#define g_fl g_ex.fl
#define TR(e)
#define TRV(e, v)
#define TG(i)
#define HD(e)
#define TRDUMP
#define TREXTRA 0

#define STAT(e, v)
#define STATC(n)
#define STATDUMP
__device__ __forceinline__ uint32_t smem_u32(const void* p) { return (uint32_t)__cvta_generic_to_shared(p); }
__device__ __forceinline__ uint32_t pack_bf16(float lo, float hi) {
  uint32_t r;
  asm("cvt.rn.bf16x2.f32 %0, %1, %2;" : "=r"(r) : "f"(hi), "f"(lo));
  return r;
}
__device__ __forceinline__ float bf_lo(uint32_t v) { return __uint_as_float(v << 16); }
__device__ __forceinline__ float bf_hi(uint32_t v) { return __uint_as_float(v & 0xffff0000u); }
__device__ __forceinline__ float ex2_fast(float x) { float y; asm("ex2.approx.ftz.f32 %0, %1;" : "=f"(y) : "f"(x)); return y; }
__device__ __forceinline__ float round_bf16(float x) { return __bfloat162float(__float2bfloat16_rn(x)); }
__device__ __forceinline__ uint32_t clk32() { uint32_t t; asm volatile("mov.u32 %0, %%clock;" : "=r"(t) :: "memory"); return t; }

__device__ __forceinline__ void mma16816(float (&d)[4], uint32_t a0, uint32_t a1, uint32_t a2, uint32_t a3,
                                         uint32_t b0, uint32_t b1) {
  asm("mma.sync.aligned.m16n8k16.row.col.f32.bf16.bf16.f32 {%0,%1,%2,%3}, {%4,%5,%6,%7}, {%8,%9}, {%0,%1,%2,%3};"
      : "+f"(d[0]), "+f"(d[1]), "+f"(d[2]), "+f"(d[3])
      : "r"(a0), "r"(a1), "r"(a2), "r"(a3), "r"(b0), "r"(b1));
}
__device__ __forceinline__ void ldsm4t(uint32_t (&r)[4], uint32_t addr) {
  asm volatile("ldmatrix.sync.aligned.m8n8.x4.trans.shared.b16 {%0,%1,%2,%3}, [%4];"
               : "=r"(r[0]), "=r"(r[1]), "=r"(r[2]), "=r"(r[3]) : "r"(addr) : "memory");
}
__device__ __forceinline__ void stsm4(uint32_t addr, uint32_t a, uint32_t b, uint32_t c, uint32_t d) {
  asm volatile("stmatrix.sync.aligned.m8n8.x4.shared.b16 [%0], {%1,%2,%3,%4};" ::"r"(addr), "r"(a), "r"(b), "r"(c), "r"(d) : "memory");
}
__device__ __forceinline__ void stsm4t(uint32_t addr, uint32_t a, uint32_t b, uint32_t c, uint32_t d) {
  asm volatile("stmatrix.sync.aligned.m8n8.x4.trans.shared.b16 [%0], {%1,%2,%3,%4};" ::"r"(addr), "r"(a), "r"(b), "r"(c), "r"(d) : "memory");
}
__device__ __forceinline__ uint4 lds128(uint32_t a) {
  uint4 v; asm volatile("ld.shared.v4.b32 {%0,%1,%2,%3}, [%4];" : "=r"(v.x), "=r"(v.y), "=r"(v.z), "=r"(v.w) : "r"(a) : "memory"); return v;
}
__device__ __forceinline__ uint32_t lds32(uint32_t a) { uint32_t v; asm volatile("ld.shared.b32 %0, [%1];" : "=r"(v) : "r"(a) : "memory"); return v; }
__device__ __forceinline__ void sts32(uint32_t a, uint32_t x) { asm volatile("st.shared.b32 [%0], %1;" ::"r"(a), "r"(x) : "memory"); }
__device__ __forceinline__ void sts128(uint32_t a, uint4 v) {
  asm volatile("st.shared.v4.b32 [%0], {%1,%2,%3,%4};" ::"r"(a), "r"(v.x), "r"(v.y), "r"(v.z), "r"(v.w) : "memory");
}
__device__ __forceinline__ void cp16(uint32_t dst, const void* src) {
  asm volatile("cp.async.cg.shared.global [%0], [%1], 16;" ::"r"(dst), "l"(src) : "memory");
}
__device__ __forceinline__ void mbar_init(uint32_t mbar, uint32_t cnt) {
  asm volatile("mbarrier.init.shared.b64 [%0], %1;" ::"r"(mbar), "r"(cnt) : "memory");
}
__device__ __forceinline__ void mbar_expect_tx(uint32_t mbar, uint32_t bytes) {
  asm volatile("mbarrier.arrive.expect_tx.shared.b64 _, [%0], %1;" ::"r"(mbar), "r"(bytes) : "memory");
}
__device__ __forceinline__ void mbar_arrive_z(uint32_t mbar, uint32_t z) {
  asm volatile("{ .reg .pred p; setp.eq.u32 p, %1, 0; @p mbarrier.arrive.shared.b64 _, [%0]; }" ::"r"(mbar), "r"(z) : "memory");
}
__device__ __forceinline__ void mbar_expect_tx_z(uint32_t mbar, uint32_t bytes, uint32_t z) {
  asm volatile("{ .reg .pred p; setp.eq.u32 p, %2, 0; @p mbarrier.arrive.expect_tx.shared.b64 _, [%0], %1; }" ::"r"(mbar), "r"(bytes), "r"(z) : "memory");
}
__device__ __forceinline__ void mbar_arrive_remote_z(uint32_t mbar, uint32_t z) {
  asm volatile("{ .reg .pred p; setp.eq.u32 p, %1, 0; @p mbarrier.arrive.shared::cluster.b64 _, [%0]; }" ::"r"(mbar), "r"(z) : "memory");
}
__device__ __forceinline__ void warp_sleep(uint32_t ns) { __nanosleep(ns); __syncwarp(); }
__device__ __forceinline__ void fail(int) { __trap(); }
__device__ __forceinline__ void give_up(int it, int limit, int code) { if (it > limit) fail(code); }
__device__ __forceinline__ void mbar_wait(uint32_t mbar, uint32_t par, int code) {
  asm volatile("{ .reg .pred p; .reg .b32 n; mov.b32 n, %2;\n"
               "W: mbarrier.try_wait.parity.shared::cta.b64 p, [%0], %1; @p bra D;\n"
               "add.s32 n, n, -1; setp.eq.s32 p, n, 0; @p trap; bra W;\n"
               "D: }" ::"r"(mbar), "r"(par), "n"(MBAR_LIMIT) : "memory");
}
__device__ __forceinline__ void bulk_g2s(uint32_t dst, const void* src, uint32_t bytes, uint32_t mbar) {
  asm volatile("cp.async.bulk.shared::cluster.global.mbarrier::complete_tx::bytes [%0], [%1], %2, [%3];"
               ::"r"(dst), "l"(src), "r"(bytes), "r"(mbar) : "memory");
}
__device__ __forceinline__ void bulk_s2r(uint32_t dst, uint32_t src, uint32_t bytes, uint32_t mbar) {
  asm volatile("cp.async.bulk.shared::cluster.shared::cta.mbarrier::complete_tx::bytes [%0], [%1], %2, [%3];"
               ::"r"(dst), "r"(src), "r"(bytes), "r"(mbar) : "memory");
}
__device__ __forceinline__ void bulk_s2g(void* dst, uint32_t src, uint32_t bytes) {
  asm volatile("cp.async.bulk.global.shared::cta.bulk_group [%0], [%1], %2;" ::"l"(dst), "r"(src), "r"(bytes) : "memory");
}
__device__ __forceinline__ void fence_async_smem() { asm volatile("fence.proxy.async.shared::cta;" ::: "memory"); }
__device__ __forceinline__ void fence_async_glb() { asm volatile("fence.proxy.async.global;" ::: "memory"); }
__device__ __forceinline__ void bar_sync(int id, int n) { asm volatile("bar.sync %0, %1;" ::"r"(id), "r"(n) : "memory"); }
__device__ __forceinline__ void bar_arrive(int id, int n) { asm volatile("bar.arrive %0, %1;" ::"r"(id), "r"(n) : "memory"); }
__device__ __forceinline__ void cluster_sync() { asm volatile("barrier.cluster.arrive.release; barrier.cluster.wait.acquire;" ::: "memory"); }
__device__ __forceinline__ uint32_t mapa_u32(uint32_t a, uint32_t r) {
  uint32_t o;
  asm("mapa.shared::cluster.u32 %0, %1, %2;" : "=r"(o) : "r"(a), "r"(r));
  return o;
}
template <int OFF>
__device__ __forceinline__ void st_async32(uint32_t a, uint32_t x, uint32_t mbar) {
  asm volatile("st.async.weak.shared::cluster.mbarrier::complete_tx::bytes.b32 [%0 + %3], %1, [%2];" ::"r"(a), "r"(x), "r"(mbar), "n"(OFF) : "memory");
}
__device__ __forceinline__ uint4 ld_rlx128(const void* p) {
  uint4 v;
  asm volatile("ld.relaxed.gpu.global.v4.u32 {%0,%1,%2,%3}, [%4];" : "=r"(v.x), "=r"(v.y), "=r"(v.z), "=r"(v.w) : "l"(p) : "memory");
  return v;
}
__device__ __forceinline__ uint2 ld_rlx64(const void* p) {
  uint2 v; asm volatile("ld.relaxed.gpu.global.v2.u32 {%0,%1}, [%2];" : "=r"(v.x), "=r"(v.y) : "l"(p) : "memory"); return v;
}
__device__ __forceinline__ uint32_t ld_rlx32(const void* p) {
  uint32_t v; asm volatile("ld.relaxed.gpu.global.u32 %0, [%1];" : "=r"(v) : "l"(p) : "memory"); return v;
}
__device__ __forceinline__ void st_rlx32(void* p, uint32_t a) { asm volatile("st.relaxed.gpu.global.u32 [%0], %1;" ::"l"(p), "r"(a) : "memory"); }
__device__ __forceinline__ void red_release(uint32_t* p) { asm volatile("red.release.gpu.global.add.u32 [%0], 1;" ::"l"(p) : "memory"); }
__device__ __forceinline__ void st_release32(void* p, uint32_t a) { asm volatile("st.release.gpu.global.u32 [%0], %1;" ::"l"(p), "r"(a) : "memory"); }
__device__ __forceinline__ void st_release_u64(void* p, u64 a) { asm volatile("st.release.gpu.global.u64 [%0], %1;" ::"l"(p), "l"(a) : "memory"); }
__device__ __forceinline__ void wait_count(const uint32_t* p, uint32_t val, int code) {
  int it = 0;
  while (ld_rlx32(p) < val) {
    give_up(++it, SPIN_LIMIT, code);
    warp_sleep(SLP_C);
  }
}
__device__ __forceinline__ u64 wait_keys(const u64* keys, int lane, int code) {
  u64 k;
  int it = 0;
  while (true) {
    asm volatile("ld.relaxed.gpu.global.u64 %0, [%1];" : "=l"(k) : "l"(keys + lane) : "memory");
    if (__all_sync(~0u, k != 0)) break;
    give_up(++it, SPIN_LIMIT, code);
    warp_sleep(SLP_K);
  }
  const uint32_t hi = __reduce_max_sync(~0u, (uint32_t)(k >> 32));
  const uint32_t lo = __reduce_max_sync(~0u, (uint32_t)(k >> 32) == hi ? (uint32_t)k : 0u);
  return (u64)hi << 32 | lo;
}
__device__ __forceinline__ int key_token(u64 k) { return (int)(~(uint32_t)k) & (NTOK - 1); }
__device__ __forceinline__ float key_score(u64 k) {
  const uint32_t ob = (uint32_t)(k >> 32);
  return __uint_as_float((ob & 0x80000000u) ? (ob & 0x7fffffffu) : ~ob);
}

__device__ __forceinline__ uint64_t mk_desc(uint32_t saddr, uint32_t lbo, uint32_t sbo, uint32_t sw) {
  return (uint64_t)((saddr & 0x3FFFF) >> 4) | (uint64_t)(lbo >> 4) << 16 | (uint64_t)(sbo >> 4) << 32 | (uint64_t)sw << 62;
}
template <int N> __device__ __forceinline__ void reg_inc() { asm volatile("setmaxnreg.inc.sync.aligned.u32 %0;" ::"n"(N)); }
template <int N> __device__ __forceinline__ void reg_dec() { asm volatile("setmaxnreg.dec.sync.aligned.u32 %0;" ::"n"(N)); }
__device__ __forceinline__ void wg_fence() { asm volatile("wgmma.fence.sync.aligned;" ::: "memory"); }
__device__ __forceinline__ void wg_commit() { asm volatile("wgmma.commit_group.sync.aligned;" ::: "memory"); }
template <int N> __device__ __forceinline__ void wg_wait() { asm volatile("wgmma.wait_group.sync.aligned %0;" ::"n"(N) : "memory"); }
template <int N> __device__ __forceinline__ void acc_fence(float (&d)[N]) {
#pragma unroll
  for (int i = 0; i < N; i++) asm volatile("" : "+f"(d[i]) :: "memory");
}
#define O4(d, i) "+f"(d[i]), "+f"(d[i + 1]), "+f"(d[i + 2]), "+f"(d[i + 3])
template <int TB, int ACC>
__device__ __forceinline__ void wg_rs24(float (&d)[12], const uint32_t (&a)[4], uint64_t db) {
  asm volatile("wgmma.mma_async.sync.aligned.m64n24k16.f32.bf16.bf16 {%0,%1,%2,%3,%4,%5,%6,%7,%8,%9,%10,%11}, {%12,%13,%14,%15}, %16, %17, 1, 1, %18;"
               : O4(d, 0), O4(d, 4), O4(d, 8) : "r"(a[0]), "r"(a[1]), "r"(a[2]), "r"(a[3]), "l"(db), "n"(ACC), "n"(TB));
}
template <int TB, int ACC>
__device__ __forceinline__ void wg_rs32(float (&d)[16], const uint32_t (&a)[4], uint64_t db) {
  asm volatile("wgmma.mma_async.sync.aligned.m64n32k16.f32.bf16.bf16 {%0,%1,%2,%3,%4,%5,%6,%7,%8,%9,%10,%11,%12,%13,%14,%15}, {%16,%17,%18,%19}, %20, %21, 1, 1, %22;"
               : O4(d, 0), O4(d, 4), O4(d, 8), O4(d, 12) : "r"(a[0]), "r"(a[1]), "r"(a[2]), "r"(a[3]), "l"(db), "n"(ACC), "n"(TB));
}
template <int ACC>
__device__ __forceinline__ void wg_rs64(float (&d)[32], uint32_t a0, uint32_t a1, uint32_t a2, uint32_t a3, uint64_t db) {
  asm volatile("wgmma.mma_async.sync.aligned.m64n64k16.f32.bf16.bf16 {%0,%1,%2,%3,%4,%5,%6,%7,%8,%9,%10,%11,%12,%13,%14,%15,"
               "%16,%17,%18,%19,%20,%21,%22,%23,%24,%25,%26,%27,%28,%29,%30,%31}, {%32,%33,%34,%35}, %36, %37, 1, 1, 0;"
               : O4(d, 0), O4(d, 4), O4(d, 8), O4(d, 12), O4(d, 16), O4(d, 20), O4(d, 24), O4(d, 28)
               : "r"(a0), "r"(a1), "r"(a2), "r"(a3), "l"(db), "n"(ACC));
}
template <int ACC>
__device__ __forceinline__ void wg_ss24(float (&d)[12], uint64_t da, uint64_t db) {
  asm volatile("wgmma.mma_async.sync.aligned.m64n24k16.f32.bf16.bf16 {%0,%1,%2,%3,%4,%5,%6,%7,%8,%9,%10,%11}, %12, %13, %14, 1, 1, 1, 0;"
               : O4(d, 0), O4(d, 4), O4(d, 8) : "l"(da), "l"(db), "n"(ACC));
}
template <int ACC>
__device__ __forceinline__ void wg_rs40(float (&d)[20], const uint32_t (&a)[4], uint64_t db) {
  asm volatile("wgmma.mma_async.sync.aligned.m64n40k16.f32.bf16.bf16 {%0,%1,%2,%3,%4,%5,%6,%7,%8,%9,%10,%11,%12,%13,%14,%15,%16,%17,%18,%19}, {%20,%21,%22,%23}, %24, %25, 1, 1, 1;"
               : O4(d, 0), O4(d, 4), O4(d, 8), O4(d, 12), O4(d, 16) : "r"(a[0]), "r"(a[1]), "r"(a[2]), "r"(a[3]), "l"(db), "n"(ACC));
}

struct Row { uint32_t w[8]; };
__device__ __forceinline__ uint32_t add_bf16x2(uint32_t a, uint32_t b) {
  uint32_t d; asm("add.rn.bf16x2 %0, %1, %2;" : "=r"(d) : "r"(a), "r"(b)); return d;
}
__device__ __forceinline__ Row warp_ln(const Row& r, float& extra) {
  float x[16];
#pragma unroll
  for (int i = 0; i < 8; i++) { x[2 * i] = bf_lo(r.w[i]); x[2 * i + 1] = bf_hi(r.w[i]); }
  float m = (((x[0] + x[1]) + (x[2] + x[3])) + ((x[4] + x[5]) + (x[6] + x[7]))) + (((x[8] + x[9]) + (x[10] + x[11])) + ((x[12] + x[13]) + (x[14] + x[15])));
  m *= (1.f / 16);
  float v0 = 0.f, v1 = 0.f;
#pragma unroll
  for (int i = 0; i < 16; i += 2) { const float d0 = x[i] - m, d1 = x[i + 1] - m; v0 = fmaf(d0, d0, v0); v1 = fmaf(d1, d1, v1); }
  float v = v0 + v1;
#pragma unroll
  for (int o = 1; o <= 16; o <<= 1) {
    const float mo = __shfl_xor_sync(~0u, m, o), vo = __shfl_xor_sync(~0u, v, o);
    extra += __shfl_xor_sync(~0u, extra, o);
    const float d = mo - m;
    v = fmaf(d * d, 8.f * o, v + vo);
    m = 0.5f * (m + mo);
  }
  const float var = fmaf(v, 1.f / DM, 1e-5f);
  float rs = rsqrtf(var);
  rs = rs * fmaf(-0.5f * var * rs, rs, 1.5f);
  Row y;
#pragma unroll
  for (int i = 0; i < 8; i++) y.w[i] = pack_bf16((x[2 * i] - m) * rs, (x[2 * i + 1] - m) * rs);
  return y;
}
__device__ __forceinline__ Row warp_ln(const Row& r) { float e = 0.f; return warp_ln(r, e); }
__device__ __forceinline__ Row load_row(const bf16* p, int lane) {
  Row r;
#pragma unroll
  for (int q = 0; q < 4; q++) { const uint2 v = ld_rlx64(p + lane * 4 + q * 128); r.w[2 * q] = v.x; r.w[2 * q + 1] = v.y; }
  return r;
}
__device__ __forceinline__ void store_row_img(uint8_t* img, int rr, int lane, const Row& r) {
  uint8_t* p = img + (lane >> 4) * 4096 + rr * 128 + ((((lane & 15) >> 1) ^ (rr & 7)) << 4) + (lane & 1) * 8;
#pragma unroll
  for (int q = 0; q < 4; q++) *(uint2*)(p + q * 8192) = make_uint2(r.w[2 * q], r.w[2 * q + 1]);
}

__global__ void __launch_bounds__(256) prep_kernel(const bf16* __restrict__ x0, const bf16* Wq, const bf16* Wk, const bf16* Wv, const bf16* Wo) {
  const int lane = threadIdx.x & 31, row = blockIdx.x * 8 + (threadIdx.x >> 5);
#define TRC (blockIdx.x & 127)
  if (threadIdx.x == 0 && blockIdx.x < 128) { HD(13) }
  const Row r = load_row(x0 + (size_t)row * DM, lane);
  const int gt = blockIdx.x * 256 + threadIdx.x, nt = gridDim.x * 256;
  asm volatile("prefetch.global.L2 [%0];" ::"l"((gt & 1 ? Wk : Wq) + (gt >> 1) * 64));
  asm volatile("prefetch.global.L2 [%0];" ::"l"((gt & 1 ? Wo : Wv) + (gt >> 1) * 64));
  uint4* M = (uint4*)g_M;
  for (int i = gt; i < 4 * 16384 / 4; i += nt) M[i] = make_uint4(~0u, ~0u, ~0u, ~0u);
  uint4* P = (uint4*)g_P;
  for (int i = gt; i < 96 * 4096 / 4; i += nt) P[i] = make_uint4(0, 0, 0, 0);
  if (gt < 16384) ((uint4*)(g_part[1] + 32 * 8192))[gt] = make_uint4(0, 0, 0, 0);
  uint4* F = (uint4*)&g_fl;
  for (int i = gt; i < (int)(sizeof(Flags) / 16); i += nt) F[i] = make_uint4(0, 0, 0, 0);
  store_row_img(g_xs[0] + (size_t)(row >> 5) * 32768, row & 31, lane, warp_ln(r));
  if (threadIdx.x == 0 && blockIdx.x >= 128) { HD(14) }
#undef TRC
}

constexpr int W_STRIDE = 272;
constexpr int C_WO = 0;
constexpr int C_X = 49152;
constexpr int C_M = C_X + 65536;
constexpr int C_Q = C_M + 24576;
constexpr int C_K = C_Q + 10240, C_V = C_K + 10240;
constexpr int C_SA = C_V + 10240, C_SB = C_SA + 8192;
constexpr int C_O = C_SB + 8192;
constexpr int C_OT = C_O + 6144;
constexpr int C_PI = C_OT + 16384;
constexpr int C_BAR = C_PI + 8192;
constexpr int C_SMEM = C_BAR + 384 + 1024 + TREXTRA;
static_assert(C_X + 512 * W_STRIDE <= C_OT, "staging");
enum { B_M0 = 0, B_M1, B_M2, B_R, B_X = B_R + 4, B_O, B_T, B_F, B_XL, B_U, B_P1, B_P2, B_OT, B_XF, B_XA, B_I, B_PI, B_J, B_NUM };
constexpr int C_POL = C_BAR + 192, C_INFO = C_BAR + 208;
enum { NB_ALL = 0, NB_M0, NB_PV, NB_W0, NB_TA, NB_X1, NB_M1, NB_M2, NB_RD, NB_V, NB_SM };
constexpr float SCALE_LOG2E = 0.08838834764831845f * 1.4426950408889634f;
#define N0STEPS 9
#define N2STEPS 12
#define FGATE 1
#define NSSTEPS 0
constexpr int KA = 32 - NSSTEPS - N2STEPS, K3 = KA - N0STEPS;
static_assert(KA % 4 == 0, "the rows of layer 1 are refilled in two parts");
#define BGATE 0
#define W0EARLY 0
#define PVEARLY 1
#define S1GATE 0
#define IGRP 0
#define SHIPLATE 7
#define SHIP 1024
#define GATE_P 2250
#define GATE_W 170
#define EXPF 0
#define GATE_G 200
#define GATE_M 3230
#define HOLE0 22
#define HOLE1 28
#define HOLE2 32
__device__ __forceinline__ uint32_t gtime() { uint32_t t; asm volatile("mov.u32 %0, %%globaltimer_lo;" : "=r"(t) :: "memory"); return t; }
__device__ __forceinline__ void wait_clock(uint32_t t) {
  asm volatile("{ .reg .pred p; .reg .b32 c; .reg .b64 cc;\nL: mov.u64 cc, %%clock64; cvt.u32.u64 c, cc; sub.u32 c, c, %0; setp.lt.s32 p, c, 0; @p bra L; }" ::"r"(t) : "memory");
}
__device__ __forceinline__ void bar_sync_z(int id, int n, uint32_t z) {
  asm volatile("{ .reg .pred p; setp.eq.u32 p, %2, 0; @p bar.sync %0, %1; }" ::"r"(id), "r"(n), "r"(z) : "memory");
}

__device__ __forceinline__ int probe_home(uint32_t* p, int lane) {
  int vote = 0;
#pragma unroll 1
  for (int rep = 0; rep < 4; rep++) {
    uint32_t d[2];
#pragma unroll
    for (int pg = 0; pg < 2; pg++) {
      uint32_t t0, t1, v = 0;
      asm volatile("mov.u32 %0, %%clock;" : "=r"(t0) :: "memory");
      asm volatile("{ .reg .pred p; setp.eq.u32 p, %2, 0; @p atom.relaxed.gpu.global.add.u32 %0, [%1], 0; }" : "+r"(v) : "l"(p + pg * 1024 + rep * 256), "r"(lane) : "memory");
      asm volatile("{ .reg .pred p; setp.ne.u32 p, %1, 0x13572468; mov.u32 %0, 0; @p mov.u32 %0, %%clock; }" : "=r"(t1) : "r"(v) : "memory");
      d[pg] = t1 - t0;
    }
    if (rep > 0) vote += max(-150, min(150, (int)(d[0] - d[1])));
  }
  return __shfl_sync(~0u, vote, 0);
}
__device__ __forceinline__ uint32_t home_flip(const void* p) { const uint32_t a = (uint32_t)(size_t)p; return ((a >> 16) ^ (a >> 17) ^ (a >> 19)) & 1; }
__device__ __forceinline__ uint32_t ppage(uint32_t lp, uint32_t pol) { return lp ? 3 - pol : pol; }
__device__ __forceinline__ uint32_t and_x(uint32_t a, uint32_t b, uint32_t m) {
  uint32_t d; asm("lop3.b32 %0, %1, %2, %3, 0x42;" : "=r"(d) : "r"(a), "r"(b), "r"(m)); return d;
}
__device__ __forceinline__ uint32_t and3(uint32_t a, uint32_t b, uint32_t c) {
  uint32_t d; asm("lop3.b32 %0, %1, %2, %3, 0x80;" : "=r"(d) : "r"(a), "r"(b), "r"(c)); return d;
}

template <int N> struct IC { static constexpr int value = N; };
template <class F> __device__ __forceinline__ void static_for2(F f) { f(IC<0>()); f(IC<1>()); }
template <class F> __device__ __forceinline__ void static_for3(F f) { f(IC<0>()); f(IC<1>()); f(IC<2>()); }
__device__ __forceinline__ void load_wfrags(uint32_t (&wA)[32][4], uint32_t stage, int w, int lane) {
  const int mi = lane >> 3, r = lane & 7;
#pragma unroll
  for (int ks = 0; ks < 32; ks++) ldsm4t(wA[ks], stage + (ks * 16 + (mi >> 1) * 8 + r) * W_STRIDE + (w * 16 + (mi & 1) * 8) * 2);
}
template <int K0, int K1>
__device__ __forceinline__ void tok_seq(float (&d)[16], const uint32_t (&wA)[32][4], uint64_t desc, uint32_t wave) {
#pragma unroll
  for (int k = K0; k < K1; k++) {
    const int ks = k & 31;
    constexpr int HM0 = 1, HM1 = 2, HM2 = 4;
    const int hm = (k == HOLE0 ? HM0 : 0) | (k == HOLE1 ? HM1 : 0) | (k == HOLE2 ? HM2 : 0);
    if (hm) bar_sync_z(NB_RD, 384, ((hm >> wave) & 1) ^ 1);
    if (ks == 0) wg_rs32<0, 0>(d, wA[ks], desc);
    else wg_rs32<0, 1>(d, wA[ks], desc + (ks >> 2) * 256 + (ks & 3) * 2);
  }
}
template <int K0, int K1>
__device__ __forceinline__ void mem_part(float (&d)[12], const uint32_t (&wA)[32][4], uint64_t desc) {
#pragma unroll
  for (int ks = K0; ks < K1; ks++) {
    if (ks == 0) wg_rs24<1, 0>(d, wA[ks], desc);
    else wg_rs24<1, 1>(d, wA[ks], desc + ks * 48);
  }
}
__device__ __forceinline__ void out_tile(float (&d)[12], uint64_t da, uint64_t db) {
#pragma unroll
  for (int i = 0; i < 8; i++) { if (i == 0) wg_ss24<0>(d, da, db); else wg_ss24<1>(d, da + i * 128, db + (i >> 1) * 32 + (i & 1) * 2); }
}
__device__ __forceinline__ void tok_pack(uint32_t (&p)[8], const float (&d)[16]) {
#pragma unroll
  for (int i = 0; i < 8; i++) p[i] = pack_bf16(d[2 * i], d[2 * i + 1]);
}
__device__ __forceinline__ void tok_store(uint32_t dst, const uint32_t (&p)[8]) {
  stsm4(dst, p[0], p[1], p[2], p[3]);
  stsm4(dst + 4096, p[4], p[5], p[6], p[7]);
}
template <class T> __device__ __forceinline__ T keep(T v) { asm volatile("" : "+r"(v)); return v; }
__device__ __forceinline__ uint32_t pin(uint32_t v) { return __shfl_sync(~0u, v, threadIdx.x & 31); }

#define TRC blockIdx.x
#define TRS (C_BAR + 384)
__device__ __forceinline__ void chain_proj(const uint32_t sb, const int w, const int lane_, const uint32_t rank) {
  uint32_t wA[32][4];
  load_wfrags(wA, sb + C_X, w, lane_);
  bar_sync(NB_ALL, 512);
  bar_sync(NB_ALL, 512);
  cluster_sync();
  const int lane = pin(lane_);
  const uint32_t bars = sb + C_BAR;
  const uint32_t quad = pin(sb + (lane_ >> 4) * 2048 + (lane_ & 15) * 16);
  const uint32_t own = C_Q + rank * 10240;
  const uint64_t dX1 = mk_desc(sb + C_X, 16, 1024, 1), dX2 = dX1 + 2048;
  const uint64_t dM = mk_desc(sb + C_M, 128, 256, 0);
  const uint32_t r1 = rank == 0 ? 1 : 0, r2 = rank == 2 ? 1 : 2;
  const uint32_t xa = pin(sb + own + 8192 + w * 256 + lane_ * 4);
  const uint32_t a1x = pin(mapa_u32(xa, r1)), a2x = pin(mapa_u32(xa, r2));
  const uint32_t b1x = pin(mapa_u32(bars + B_X * 8, r1)), b2x = pin(mapa_u32(bars + B_X * 8, r2));
  const uint32_t wave = rank == 2 ? 0 : rank + 1;
  float a[16];
  bar_sync(NB_X1, 288);
  wg_fence();
  tok_seq<32, 32 + KA>(a, wA, mk_desc(__shfl_sync(~0u, sb, 0) + C_X, 16, 1024, 1), 3);
  wg_commit();
  wg_wait<0>();
  mbar_arrive_z(bars + B_XA * 8, lane);
#pragma unroll 1
  for (int st = 0;; st++) {
    uint32_t pk[8];
    wg_fence();
    if (NSSTEPS) bar_sync(NB_SM, 416);
    tok_seq<32 + KA, 32 + KA + NSSTEPS>(a, wA, dX1, 3);
    bar_sync(NB_PV, NSSTEPS ? 384 : 416);
    tok_seq<32 + KA + NSSTEPS, 64>(a, wA, dX1, 3);
    wg_commit();
    wg_wait<0>();
    acc_fence(a);
    mbar_arrive_z(bars + B_XF * 8, lane);
    tok_pack(pk, a);
    TR(1)
    bar_sync(NB_W0, 416);
    tok_store(quad + w * 256 + (rank == 0 ? own : C_SA), pk);
    __syncwarp();
    mbar_arrive_z(bars + B_P1 * 8, lane);
    wg_fence();
    tok_seq<0, 32>(a, wA, dX2, wave);
    wg_commit();
    const uint32_t info = lds32(sb + C_INFO + (st & 1) * 4);
    TR(2)
    wg_wait<0>();
    acc_fence(a);
    TR(3)
    tok_pack(pk, a);
    tok_store(quad + w * 256 + (rank == 0 ? C_SA : own), pk);
    if (rank == 2) tok_store(quad + w * 256 + C_SB, pk);
    __syncwarp();
    mbar_arrive_z(bars + B_P2 * 8, lane);
    TR(4)
    wg_fence();
    tok_seq<32, 32 + K3>(a, wA, dX1, wave);
    TR(6)
    {
      float am[12];
      bar_sync(NB_M0, 384);
      mem_part<0, 10>(am, wA, dM);
      TR(7)
      bar_sync(NB_M1, 384);
      mem_part<10, 21>(am, wA, dM);
      bar_sync(NB_M2, 384);
      mem_part<21, 32>(am, wA, dM);
      wg_commit();
      bar_sync(NB_V, 384);
      const bool redo = __any_sync(~0u, lds32(sb + C_INFO + 16 + (lane & 3) * 32) != 0);
      if (__builtin_expect(redo, 0)) {
        wg_wait<0>();
        wg_fence();
        mem_part<0, 32>(am, wA, dM);
        wg_commit();
      }
      wg_wait<0>();
      acc_fence(am);
      TR(8)
      const uint32_t x00 = pack_bf16(am[0], am[1]), x01 = pack_bf16(am[2], am[3]), x10 = pack_bf16(am[4], am[5]), x11 = pack_bf16(am[6], am[7]);
      const uint32_t y0 = pack_bf16(am[8], am[9]), y1 = pack_bf16(am[10], am[11]), x20 = info ? x10 : y0, x21 = info ? x11 : y1;
      st_async32<0>(a1x, rank == 0 ? x10 : x00, b1x); st_async32<0>(a2x, rank == 2 ? x10 : x20, b2x);
      st_async32<128>(a1x, rank == 0 ? x11 : x01, b1x); st_async32<128>(a2x, rank == 2 ? x11 : x21, b2x);
      sts32(xa, rank == 0 ? x00 : rank == 2 ? x20 : x10); sts32(xa + 128, rank == 0 ? x01 : rank == 2 ? x21 : x11);
      if (__builtin_expect(info, 0)) {
        const uint32_t o = (info & 3) * 2048 - 8192;
        if (rank == 2) { sts32(xa + o, y0); sts32(xa + o + 128, y1); }
        else { st_async32<0>(a2x + o, y0, b2x + (B_T - B_X) * 8); st_async32<128>(a2x + o, y1, b2x + (B_T - B_X) * 8); }
      }
      __syncwarp();
      mbar_arrive_z(bars + B_X * 8, lane);
    }
    TR(9)
    wg_fence();
    tok_seq<32 + K3, 32 + KA>(a, wA, dX1, 3);
    wg_commit();
    TR(0)
    wg_wait<0>();
    if (st == NSTEP - 1) break;
    mbar_arrive_z(bars + B_XA * 8, lane);
  }
  if (NSSTEPS) bar_arrive(NB_SM, 416);
  bar_arrive(NB_PV, NSSTEPS ? 384 : 416);
}

__device__ __forceinline__ void chain_mem(const uint32_t sb, const int w, const int lane_, const uint32_t rank, const int h,
                                          const bf16* __restrict__ mem0) {
  const int lane = pin(lane_);
  const int wave = rank == 2 ? 0 : rank + 1;
  const int c = w - 8, t = c * 32 + lane, b = wave * 32 + h;
  const uint32_t bars = sb + C_BAR;
  const int wi = (lane & 1) * 2 + (lane >> 4), cq = (lane >> 2) & 3;
  bar_sync(NB_ALL, 512);
#pragma unroll 1
  for (int i = c; i < 16; i += 4) {
    uint32_t r[4];
    ldsm4t(r, sb + C_OT + i * 512 + lane * 16);
    const uint32_t a = sb + C_M + (2 * i + (lane >> 4)) * 768 + (lane & 15) * 16;
    stsm4(a, r[0], r[1], r[2], r[3]); stsm4(a + 256, r[0], r[1], r[2], r[3]); stsm4(a + 512, r[0], r[1], r[2], r[3]);
  }
  fence_async_smem();
  mbar_expect_tx_z(bars + B_X * 8, 4096, t); mbar_expect_tx_z(bars + B_O * 8, 4096, t);
  bar_sync(NB_ALL, 512);
  cluster_sync();
  if (NSSTEPS) bar_arrive(NB_SM, 416);
  bar_arrive(NB_PV, NSSTEPS ? 384 : 416); bar_arrive(NB_W0, 416); bar_arrive(NB_M0, 384); bar_arrive(NB_M1, 384);
  sts32(sb + C_INFO + 16 + c * 32, 0);
  bar_arrive(NB_M2, 384); bar_arrive(NB_V, 384);
  bar_arrive(NB_RD, 384);

  {
    uint32_t* p = g_M + c * 16384 + (blockIdx.x & 7) * 32;
    const int vote = probe_home(p, lane);
    sts32(sb + C_POL + c * 4, home_flip(p) ? -vote : vote);
    bar_sync(NB_ALL, 128);
    const uint4 v = lds128(sb + C_POL);
    const uint32_t side = (int)(v.x + v.y + v.z + v.w) > 0;
    bar_sync(NB_ALL, 128);
    sts32(sb + C_POL + c * 4, side ^ home_flip(p));
    sts32(sb + C_INFO + 8, side ^ home_flip(g_P + b * 4096));
    st_rlx32(&g_fl.pol[b], (side ^ home_flip(g_P + b * 4096)) + 1);
  }
  uint32_t pgbits, polP;
  {
    const int tl = lane / 3, u = ((tl * 3 + rank) * 4 + c) * 3 + (lane - tl * 3);
    uint32_t pol;
    int it = 0;
    do { pol = ld_rlx32(&g_fl.pol[lane < 9 && u < 96 ? u : b]); give_up(it++, SPIN_LIMIT, 40); } while (__any_sync(~0u, pol == 0));
    pgbits = __reduce_or_sync(~0u, lane < 9 ? ppage(h >> 4, (pol - 1) & 1) << (2 * lane) : 0u);
    polP = __shfl_sync(~0u, pol - 1, 9);
  }
  const int mi = lane >> 3;
  const uint32_t l16 = pin(sb + lane * 16);
  const uint32_t r1 = rank == 2 ? 0 : rank + 1, r2 = rank == 0 ? 2 : rank - 1;
  const uint32_t oa = pin(sb + C_O + rank * 2048 + (lane >> 2) * 64 + (((lane & 3) ^ (lane >> 3)) << 4));
  const uint32_t a1 = mapa_u32(oa, r1), b1 = mapa_u32(bars + B_O * 8, r1), a2 = mapa_u32(oa, r2), b2 = mapa_u32(bars + B_O * 8, r2);
  const uint64_t dWo = mk_desc(sb + C_WO, 8192, 1024, 1), dO = mk_desc(sb + C_O, 16, 2048, 2);
  const uint64_t dK = mk_desc(sb + C_K, 128, 2048, 0);
  const uint64_t dV = mk_desc(sb + C_V, 2048, 128, 0), dVm = mk_desc(sb + C_V + 8192, 0, 128, 0);
  const uint32_t qa = pin(sb + C_Q + (c ? c + 1 : mi & 1) * 2048 + (mi >> 1) * 128 + (lane & 7) * 16);
  const uint32_t dg = ((lane >> 2) < 2 * (lane & 3) ? 1 : 0) | ((lane >> 2) < 2 * (lane & 3) + 1 ? 2 : 0);
  const uint32_t msk = pin(c == 0 ? dg | dg << 4 : c == 1 ? dg << 2 | 3 << 4 : c == 2 ? dg << 4 : 0);
  uint8_t* Pw = (uint8_t*)g_P + (rank * 4 + c) * 3 * 16384 + (h & 15) * 256 + ((lane * 4) ^ ((h & 3) << 5));
  const uint32_t pia = pin(sb + C_PI + ((lane >> 4) * 4 + (lane & 3)) * 256 + ((c * 64 + cq * 16) ^ ((lane & 3) << 5)));
  uint8_t* Mw = (uint8_t*)g_M + (b >> 5) * 16384 + ((lane & 2) ? 4096 : 12288) + (b & 31) * 256 + c * 64 + cq * 16 + wi * 4;
  uint32_t nretry = 0, nupd = 0;

  { const int st = 71; (void)st; STAT(0, lds32(sb + C_POL + c * 4)) STAT(1, polP) STAT(2, (uint32_t)(size_t)(g_M + c * 16384)) STAT(3, (uint32_t)(size_t)(g_P + b * 4096)) }
#pragma unroll 1
  for (int st = 0;; st++) {
    mbar_wait(bars + B_P1 * 8, st & 1, 38);
    mbar_wait(bars + B_T * 8, st & 1, 42);
    STAT(10, clk32())
    {
      float s[20];
      {
        uint32_t q[8][4];
        if (c == 3) mbar_wait(bars + B_X * 8, st & 1, 41);
#pragma unroll
        for (int i = 0; i < 8; i++) ldsm4t(q[i], qa + i * 256);
        if (c != 3) { mbar_wait(bars + B_X * 8, st & 1, 41); fence_async_smem(); }
        STAT(11, clk32())
        TR(0)
        wg_fence();
#pragma unroll
        for (int i = 0; i < 8; i++) { if (i == 0) wg_rs40<0>(s, q[i], dK); else wg_rs40<1>(s, q[i], dK + i * 16); }
        wg_commit();
        wg_wait<0>();
        if (NSSTEPS) bar_arrive(NB_SM, 416);
        acc_fence(s);
      }
      TR(1)
      const bool w0 = c == 0;
      float z[10] = {s[16], s[17], s[0], s[1], w0 ? s[18] : s[4], w0 ? s[19] : s[5], w0 ? s[2] : s[8], w0 ? s[3] : s[9], w0 ? s[6] : s[12], w0 ? s[7] : s[13]};
      if (msk & 1) z[2] = -INFINITY;
      if (msk & 2) z[3] = -INFINITY;
      if (msk & 4) z[6] = -INFINITY;
      if (msk & 8) z[7] = -INFINITY;
      if (msk & 16) z[8] = -INFINITY;
      if (msk & 32) z[9] = -INFINITY;
      float m0 = fmaxf(fmaxf(z[0], z[1]), fmaxf(z[2], z[3])), m1 = fmaxf(fmaxf(fmaxf(z[4], z[5]), fmaxf(z[6], z[7])), fmaxf(z[8], z[9]));
      m0 = fmaxf(m0, __shfl_xor_sync(~0u, m0, 1)); m1 = fmaxf(m1, __shfl_xor_sync(~0u, m1, 1));
      m0 = fmaxf(m0, __shfl_xor_sync(~0u, m0, 2)); m1 = fmaxf(m1, __shfl_xor_sync(~0u, m1, 2));
      if (!w0) m0 = m1 = fmaxf(m0, m1);
      m0 *= -SCALE_LOG2E; m1 *= -SCALE_LOG2E;
      uint32_t p[5];
#pragma unroll
      for (int k = 0; k < 5; k++) {
        z[2 * k] = ex2_fast(fmaf(z[2 * k], SCALE_LOG2E, k < 2 ? m0 : m1)); z[2 * k + 1] = ex2_fast(fmaf(z[2 * k + 1], SCALE_LOG2E, k < 2 ? m0 : m1));
        p[k] = pack_bf16(z[2 * k], z[2 * k + 1]);
      }
      const uint32_t p2 = w0 ? 0 : p[2], p3 = w0 ? 0 : p[3], p4 = w0 ? 0 : p[4];
      float oA[32], oB[32];
      wg_fence();
      wg_rs64<0>(oA, p[0], p[2], 0, 0, dVm); wg_rs64<1>(oA, p[1], p[3], p2, p[4], dV); wg_rs64<1>(oA, p3, 0, p4, 0, dV + 256);
      wg_commit();
      wg_rs64<0>(oB, p[0], p[2], 0, 0, dVm + 64); wg_rs64<1>(oB, p[1], p[3], p2, p[4], dV + 64); wg_rs64<1>(oB, p3, 0, p4, 0, dV + 320);
      wg_commit();
      float l0 = (z[0] + z[1]) + (z[2] + z[3]), l1 = ((z[4] + z[5]) + (z[6] + z[7])) + (z[8] + z[9]);
      if (!w0) l0 += l1;
      l0 += __shfl_xor_sync(~0u, l0, 1); l1 += __shfl_xor_sync(~0u, l1, 1);
      l0 += __shfl_xor_sync(~0u, l0, 2); l1 += __shfl_xor_sync(~0u, l1, 2);
      float i0, i1;
      asm volatile("rcp.approx.ftz.f32 %0, %2; rcp.approx.ftz.f32 %1, %3;" : "=f"(i0), "=f"(i1) : "f"(l0), "f"(l1));
      asm volatile("st.shared.v2.f32 [%0], {%1,%2};" ::"r"(sb + C_INFO + 24), "f"(i0), "f"(i1) : "memory");
      const uint32_t ta = l16 + C_OT + (st & 1) * 8192 + (c ? c + 1 : 0) * 2048;
      auto leave = [&](const float (&o)[32], auto hc) {
        constexpr int H = decltype(hc)::value;
        uint32_t e[8];
#pragma unroll
        for (int j = 0; j < 8; j++) e[j] = pack_bf16(o[4 * j] * i0, o[4 * j + 1] * i0);
        if (c == 3) {
          static_for2([&](auto bc) {
            constexpr int B = decltype(bc)::value;
            asm volatile("st.async.weak.shared::cluster.mbarrier::complete_tx::bytes.v4.b32 [%0 + %9], {%5,%6,%7,%8}, [%1];\n"
                         "st.async.weak.shared::cluster.mbarrier::complete_tx::bytes.v4.b32 [%2 + %9], {%5,%6,%7,%8}, [%3];\n"
                         "st.shared.v4.b32 [%4 + %9], {%5,%6,%7,%8};"
                         ::"r"(a1), "r"(b1), "r"(a2), "r"(b2), "r"(oa), "r"(e[4 * B]), "r"(e[4 * B + 1]), "r"(e[4 * B + 2]), "r"(e[4 * B + 3]),
                           "n"(H * 1024 + B * 512) : "memory");
          });
        } else {
          stsm4(ta + H * 1024, e[0], e[1], e[2], e[3]); stsm4(ta + H * 1024 + 512, e[4], e[5], e[6], e[7]);
          if (w0) {
#pragma unroll
            for (int j = 0; j < 8; j++) e[j] = pack_bf16(o[4 * j + 2] * i1, o[4 * j + 3] * i1);
            stsm4(ta + 2048 + H * 1024, e[0], e[1], e[2], e[3]); stsm4(ta + 2048 + H * 1024 + 512, e[4], e[5], e[6], e[7]);
          }
        }
      };
      wg_wait<1>();
      acc_fence(oA);
      leave(oA, IC<0>());
      wg_wait<0>();
      if (PVEARLY) bar_arrive(NB_PV, NSSTEPS ? 384 : 416);
      acc_fence(oB);
      leave(oB, IC<1>());
      if (!PVEARLY) bar_arrive(NB_PV, NSSTEPS ? 384 : 416);
      __syncwarp();
      mbar_arrive_z(bars + (c == 3 ? B_O : B_OT) * 8, lane);
      TR(2)
    }
    mbar_wait(bars + B_O * 8, st & 1, 43);
    if (st == NSTEP - 1) break;
    uint32_t info;
    {
      const uint32_t tag = (st & 1) ^ 1;
      float oc0[12], oc1[12], oc2[12];
      fence_async_smem();
      TR(3)
      wg_fence();
      out_tile(oc0, dWo, dO);
      wg_commit();
      out_tile(oc1, dWo + 1024, dO);
      wg_commit();
      asm volatile("" : "+r"(pgbits));
      auto put = [&](const float (&oc)[12], auto tlc) {
        constexpr int TL = decltype(tlc)::value;
        static_for3([&](auto jc) {
          constexpr int j = decltype(jc)::value;
          uint8_t* p = Pw + ((pgbits >> (2 * (TL * 3 + j))) & 3) * 4096;
          asm volatile("st.relaxed.gpu.global.u32 [%0 + %3], %1; st.relaxed.gpu.global.u32 [%0 + %3 + 128], %2;" ::"l"(p),
                       "r"((pack_bf16(oc[4 * j], oc[4 * j + 1]) & ~1u) | tag), "r"((pack_bf16(oc[4 * j + 2], oc[4 * j + 3]) & ~1u) | tag),
                       "n"((TL * 36 + j) * 16384) : "memory");
        });
      };
      wg_wait<1>();
      acc_fence(oc0);
      put(oc0, IC<0>());
      sts32(sb + C_INFO + 24, clk32());
      TR(4)
      out_tile(oc2, dWo + 2048, dO);
      wg_commit();
      wg_wait<1>();
      acc_fence(oc1);
      put(oc1, IC<1>());
      if (W0EARLY) bar_arrive(NB_W0, 416);
      bar_sync(NB_TA, 192);
      TR(5)
      wg_wait<0>();
      if (!W0EARLY) bar_arrive(NB_W0, 416);
      info = lds32(sb + C_INFO + ((st + 1) & 1) * 4);
      acc_fence(oc2);
      if (rank != 2) put(oc2, IC<2>());
      mbar_arrive_remote_z(((t & 1) ? b2 : b1) + (B_F - B_O) * 8, t >> 1);
      mbar_expect_tx_z(bars + ((t & 1) ? B_O : B_X) * 8, 4096, t >> 1);
      TR(6)
    }
    const int sn = (st + 1) & 3;
    uint8_t* mw = Mw + sn * 65536;
    asm volatile("" : "+l"(mw));
    if (__builtin_expect((st < DELTA && b % 3 != 0) || (info && b % 3 == 2), 0)) {
      bar_arrive(NB_RD, 384);
      const int col = b / 3 * 16 + c * 4 + ((lane >> 2) & 3), r0 = (lane & 1) * 4 + (lane >> 4) * 2;
      const bool upd = info && b % 3 == 2;
      if (upd) mbar_wait(bars + B_U * 8, nupd & 1, 39);
      uint32_t hv[2];
#pragma unroll
      for (int i = 0; i < 2; i++) {
        const int r = r0 + i, sg = st + 1 - DELTA;
        const void* p = !upd ? (const void*)(mem0 + r * DM + col) : r == (int)(info >> 4) ? (const void*)(g_x2p[sg][1] + col)
                      : (const void*)(g_xs[1] + sg * 32768 + (col >> 6) * 4096 + ((info & 3) * 8 + r) * 128 + ((((col >> 3) ^ r) & 7) << 4) + (col & 7) * 2);
        asm volatile("ld.relaxed.gpu.global.u16 %0, [%1];" : "=r"(hv[i]) : "l"(p) : "memory");
      }
      st_rlx32(mw, hv[0] | hv[1] << 16);
      STAT(1, 0) STAT(2, 0) STAT(4, 0)
    } else {
      const uint32_t flip = (st & 1) ? ~0u : 0u;
      const bool u16 = lane & 16;
      const uint32_t bs = (lane & 4) ? 0x3f800000u : 0x00003f80u, bs0 = (lane & 8) ? 0u : bs, bs1 = (lane & 8) ? bs : 0u;
      STATC(c_rdy)
      mbar_wait(bars + B_PI * 8, st & 1, 37);
      TR(7)
      uint4 q0 = lds128(pia), q1 = lds128(pia + 2048), q2 = lds128(pia + 4096), q3 = lds128(pia + 6144);
      int it = 0;
#pragma unroll 1
      while (true) {
        float d0[4] = {0.f, 0.f, 0.f, 0.f}, d1[4] = {0.f, 0.f, 0.f, 0.f};
        mma16816(d0, q0.x, q0.y, q0.z, q0.w, bs0, bs1);
        mma16816(d1, q1.x, q1.y, q1.z, q1.w, bs0, bs1);
        mma16816(d0, q2.x, q2.y, q2.z, q2.w, bs0, bs1);
        mma16816(d1, q3.x, q3.y, q3.z, q3.w, bs0, bs1);
        const bool all = __all_sync(~0u, (int)and3(and_x(q0.x, q1.x, flip), and_x(q2.x, q3.x, flip), 1u));
        const float a0 = d0[0] + d1[0], a1 = d0[1] + d1[1], a2 = d0[2] + d1[2], a3 = d0[3] + d1[3];
        asm volatile("{ .reg .pred p; setp.ne.u32 p, %0, 0; @p bar.arrive %1, 384; }" ::"r"((uint32_t)all), "n"((int)NB_RD) : "memory");
        const uint32_t mword = pack_bf16((u16 ? a2 : a0) + __shfl_xor_sync(~0u, u16 ? a0 : a2, 16), (u16 ? a3 : a1) + __shfl_xor_sync(~0u, u16 ? a1 : a3, 16));
        asm volatile("{ .reg .pred p; setp.ne.u32 p, %2, 0; @p st.relaxed.gpu.global.u32 [%0], %1; }" ::"l"(mw), "r"(mword), "r"((uint32_t)all) : "memory");
        if (__builtin_expect(all, 1)) break;
        give_up(++it, SPIN_LIMIT, 44);
        const uint8_t* Pr0 = (const uint8_t*)g_P + b * 16384 + (pia - sb - C_PI) + polP * 4096;
        const uint8_t* Pr1 = Pr0 + (3 - 2 * polP) * 4096;
        q0 = ld_rlx128(Pr0); q1 = ld_rlx128(Pr0 + 2048); q2 = ld_rlx128(Pr1); q3 = ld_rlx128(Pr1 + 2048);
      }
      STATC(c_mst)
      STAT(1, c_rdy - tref) STAT(2, c_mst - tref) STAT(4, it)
      TRV(14, it)
    }
    STAT(0, lds32(sb + C_INFO + 24) - tref) STAT(3, tref)
    nupd += info != 0;
    TR(9)
    {
      const uint32_t ma = l16 + C_M + c * 2048 + mi * 4;
      auto scan = [&](uint32_t m, uint32_t a) { return __vimax3_u32(__vimax3_u32(m, lds32(a), lds32(a + 512)), lds32(a + 1024), lds32(a + 1536)); };
      mbar_wait(bars + B_M0 * 8, (st + 1) & 1, 45);
      bar_arrive(NB_M0, 384);
      STATC(c_g0)
      TR(10)
      uint32_t m = scan(0, ma);
      mbar_wait(bars + B_M1 * 8, (st + 1) & 1, 46);
      bar_arrive(NB_M1, 384);
      STATC(c_g1)
      TR(11)
      m = scan(m, ma + 8192);
      mbar_wait(bars + B_M2 * 8, (st + 1) & 1, 47);
      STATC(c_g2)
      TR(12)
      int it = 0;
      bar_arrive(NB_M2, 384);
      const bool redo = __any_sync(~0u, scan(m, ma + 16384) == ~0u);
      sts32(sb + C_INFO + 16 + c * 32, redo);
      if (__builtin_expect(redo, 0)) {
#pragma unroll 1
        for (int g = 0; g < 3;) {
          if (!__any_sync(~0u, scan(0, ma + g * 8192) == ~0u)) { g++; continue; }
          give_up(++it, SPIN_LIMIT, 48);
          if (lane == 0) {
            mbar_expect_tx(bars + (B_R + c) * 8, 2048);
            bulk_g2s(sb + C_M + g * 8192 + c * 2048, (const uint8_t*)g_M + sn * 65536 + (lds32(sb + C_POL + sn * 4) ? 4096 : 12288) + g * 16384 + c * 2048,
                     2048, bars + (B_R + c) * 8);
          }
          __syncwarp();
          mbar_wait(bars + (B_R + c) * 8, nretry++ & 1, 49);
        }
      }
      bar_arrive(NB_V, 384);
      STAT(5, c_g0 - tref) STAT(7, c_g1 - tref) STAT(8, c_g2 - tref)
      STAT(9, clk32() - tref) STAT(6, it + redo * 256)
      TR(13)
      TRV(15, it)
      st_rlx32(Mw + (st & 3) * 65536, ~0u);
    }
  }
}

__device__ __forceinline__ void chain_dma(const uint32_t sb, const int w, const int lane, const uint32_t rank, const int h) {
  const uint32_t bars = sb + C_BAR;
  bar_sync(NB_ALL, 512);
  if (w == 12) { HD(3) }
  bar_sync(NB_ALL, 512);
  if (w == 12) { HD(4) }
  cluster_sync();
  if (w == 12) { HD(5) }
  const int expf_ = EXPF;
  if (w == 12) {
    u64 best = 0;
    uint32_t nx = 0;
    auto load = [&](uint32_t dst, const uint8_t* src, uint32_t bytes) {
      mbar_expect_tx_z(bars + B_XL * 8, bytes, lane >> 1);
      if (lane < 2 && bytes) {
        fence_async_glb();
        bulk_g2s(sb + dst, src, bytes, bars + B_XL * 8);
      }
      __syncwarp();
      mbar_wait(bars + B_XL * 8, nx++ & 1, 52);
    };
    load(C_X + lane * 16384, g_xs[0] + lane * 16384, 16384);
    HD(6)
    bar_arrive(NB_X1, 288); bar_arrive(NSSTEPS ? NB_SM : NB_PV, 416);
#pragma unroll 1
    for (int st = 0; st < NSTEP; st++) {
      const int sg = st - DELTA;
      const bool more = st + 1 < NSEG && !(expf_ & 4);
      uint32_t info = 0;
      if (sg >= 0) {
        const u64 k = wait_keys(g_fl.key[0][sg], lane, 50);
        if (k > best) { best = k; info = 4 | ((key_token(k) >> 3) & 3) | (key_token(k) & 7) << 4; }
      }
      TR(0)
      mbar_wait(bars + B_XA * 8, st & 1, 58);
      sts32(sb + C_INFO + (st & 1) * 4, info);
      if (st > 0) bar_arrive(NB_TA, 192);
      TR(1)
      load(lane ? C_X : C_X + 32768, lane ? g_xs[0] + (st + 1) * 32768 : g_xs[1] + sg * 32768, lane ? (more ? KA * 1024 : 0) : (sg >= 0 && !(expf_ & 8) ? 32768 : 0));
      bar_arrive(NB_W0, 416);
      TR(2)
      if (__builtin_expect(info, 0)) {
        int it = 0;
        while (ld_rlx32(g_fl.patch[sg]) == 0) { give_up(++it, SPIN_LIMIT, 56); warp_sleep(250); }
        mbar_arrive_z(bars + B_U * 8, lane);
      }
      mbar_wait(bars + B_XF * 8, st & 1, 53);
      mbar_wait(bars + (B_M0 + BGATE) * 8, st & 1, 54);
      load(C_X + KA * 1024, g_xs[0] + (st + 1) * 32768 + KA * 1024, more && lane == 0 ? 32768 - KA * 1024 : 0);
      TR(3)
      bar_arrive(NSSTEPS ? NB_SM : NB_PV, 416);
    }
  } else if (w == 13) {
    constexpr uint32_t NP = 8192 / SHIP;
    const uint32_t o = (lane >> 1) * SHIP, own = sb + C_Q + rank * 10240, bt = bars + B_T * 8;
    const uint32_t d2 = 1 + (lane & 1);
    const uint32_t src2 = (rank == 0 ? sb + C_SA : rank == 1 ? own : sb + C_SB) + o;
    const uint32_t skip = (lane & 1) ? 4 | (o >> 11) : 8;
#pragma unroll 1
    for (int st = 0; st < NSTEP; st++) {
      mbar_wait(bars + B_P1 * 8, st & 1, 61);
      fence_async_smem();
      if (st > 0) { mbar_wait(bars + B_F * 8, (st - 1) & 1, 60); mbar_wait(bars + (S1GATE ? B_PI : B_J) * 8, (st - 1) & 1, 65); }
      const uint32_t info = lds32(sb + C_INFO + (st & 1) * 4);
      TR(2)
      if (st < NSEG && rank != 0 && lane < 2 * NP && d2 == 1 && !(expf_ & 1)) bulk_s2r(mapa_u32(own + o, 0), sb + C_SA + o, SHIP, mapa_u32(bt, 0));
      __syncwarp();
      TR(3)
      mbar_wait(bars + B_P2 * 8, st & 1, 62);
      fence_async_smem();
      if (st > 0 && (SHIPLATE >> rank & 1)) mbar_wait(bars + B_I * 8, (st - 1) & 1, 64);
      TR(0)
      if (st >= DELTA && lane < 2 * NP && d2 != rank && (info & 7) != skip && !(expf_ & 2)) bulk_s2r(mapa_u32(own + o, d2), src2, SHIP, mapa_u32(bt, d2));
      __syncwarp();
      TR(1)
    }
  } else if (w == 14) {
    const int s0 = rank == 0 ? 0 : DELTA;
    const uint32_t tbytes = (expf_ & (rank ? 2 : 1)) ? 0 : 16384;
    mbar_expect_tx_z(bars + B_T * 8, s0 == 0 ? tbytes : 0, lane);
#pragma unroll 1
    for (int st = 0; st < NSTEP; st++) {
      const int sg = st - s0;
      const bool act = (unsigned)sg < (unsigned)NSEG;
      mbar_wait(bars + B_OT * 8, st & 1, 70);
      mbar_expect_tx_z(bars + B_T * 8, (unsigned)(sg + 1) < (unsigned)NSEG ? tbytes : 0, lane);
      fence_async_smem();
      const int s1 = rank && st < NSEG - 1 ? st + 1 : st;
      if (s1 != st) mbar_wait(bars + B_X * 8, s1 & 1, 71);
      TR(0)
      if (act && lane == 0 && !(expf_ & (rank ? 32 : 16))) {
        bulk_s2g(g_O[st & (OSLOTS - 1)][rank] + h * 8192, sb + C_OT + (st & 1) * 8192, 8192);
        asm volatile("cp.async.bulk.commit_group;" ::: "memory");
        asm volatile("cp.async.bulk.wait_group 0;" ::: "memory");
        asm volatile("fence.acq_rel.gpu;" ::: "memory");
      }
      __syncwarp();
      if (WLAG && s1 < NSTEP - 1) mbar_wait(bars + (FGATE ? B_M0 + FGATE - 1 : B_I) * 8, (s1 + (FGATE > 0)) & 1, 72);
      if (act && lane == 0) asm volatile("red.relaxed.gpu.global.add.u32 [%0], 1;" ::"l"(&g_fl.oflag[rank][sg][h >> 2]) : "memory");
      __syncwarp();
      TR(1)
    }
  } else {
    mbar_arrive_z(bars + B_M0 * 8, lane); mbar_arrive_z(bars + B_M1 * 8, lane); mbar_arrive_z(bars + B_M2 * 8, lane);
    const uint32_t wave = rank == 2 ? 0 : rank + 1, gate_p = GATE_P + wave * GATE_W, gate_g = GATE_G, gate_m = GATE_M;
    uint32_t nupd = 0, late = 0;
#pragma unroll 1
    for (int st = 0; st < NSTEP - 1; st++) {
      mbar_wait(bars + B_X * 8, st & 1, 75);
      if (st < 4) { HD(8 + st) }
      if (st == NSTEP - 2) { HD(12) }
      mbar_wait(bars + B_T * 8, st & 1, 77);
      const uint32_t now = gtime() & ~31u, tag = (st + 1) & 31;
      if (lane == 0) st_rlx32(&g_fl.stamp[blockIdx.x], (now + late) | tag);
      late = 0;
      __syncwarp();
      wait_clock(clk32() + 550);
      uint32_t s0, s1, s2;
      int it = 0;
#pragma unroll 1
      do {
        s0 = ld_rlx32(&g_fl.stamp[lane]) ^ tag; s1 = ld_rlx32(&g_fl.stamp[32 + lane]) ^ tag; s2 = ld_rlx32(&g_fl.stamp[64 + lane]) ^ tag;
        give_up(it++, SPIN_LIMIT, 76);
      } while (__any_sync(~0u, ((s0 | s1 | s2) & 31) != 0));
      const uint32_t tref = now + __reduce_max_sync(~0u, __vimax3_s32((int)(s0 - now), (int)(s1 - now), (int)(s2 - now)));
      const uint32_t g0 = gtime();
      uint32_t g1, c1;
      it = 0;
      do { g1 = gtime(); c1 = clk32(); } while (g1 == g0 && ++it < 64);
      c1 -= (g1 - tref) * 7 / 4;
      sts32(sb + C_INFO + 12, c1);
      TR(0)
      bar_sync(NB_TA, 192);
      const int sn = (st + 1) & 3;
      const uint8_t* src = (const uint8_t*)g_M + sn * 65536 + (lds32(sb + C_POL + sn * 4) ? 4096 : 12288);
      {
        const uint32_t pol = lds32(sb + C_INFO + 8);
        const uint8_t* ps = (const uint8_t*)g_P + (wave * 32 + h) * 16384;
        if (lane == 0) {
          mbar_expect_tx(bars + B_PI * 8, 8192);
          wait_clock(c1 + gate_p);
          bulk_g2s(sb + C_PI, ps + pol * 4096, 4096, bars + B_PI * 8);
          bulk_g2s(sb + C_PI + 4096, ps + (3 - pol) * 4096, 4096, bars + B_PI * 8);
          mbar_arrive_z(bars + B_J * 8, 0);
        }
        __syncwarp();
      }
      c1 += gate_m;
      if (__builtin_expect(lds32(sb + C_INFO + ((st + 1) & 1) * 4), 0)) {
        late = rank == 2 ? 160 : 0;
        mbar_wait(bars + B_U * 8, nupd++ & 1, 78);
        const uint32_t c2 = clk32() + 1300;
        if ((int)(c2 - c1) > 0) c1 = c2;
      }
      mbar_expect_tx_z(bars + (B_M0 + lane) * 8, 8192, lane / 3);
      if (lane == 0) {
#pragma unroll
        for (int g = 0; g < 3; g++) {
          wait_clock(c1 + g * gate_g);
          bulk_g2s(sb + C_M + g * 8192, src + g * 16384, 8192, bars + (B_M0 + g) * 8);
          if (g == IGRP) mbar_arrive_z(bars + B_I * 8, 0);
        }
      }
      __syncwarp();
      TR(3)
    }
  }
}

__global__ void __cluster_dims__(3, 1, 1) __launch_bounds__(512, 1)
chain_kernel(const bf16* __restrict__ Wq, const bf16* __restrict__ Wk, const bf16* __restrict__ Wv,
             const bf16* __restrict__ Wo, const bf16* __restrict__ mem0) {
  extern __shared__ __align__(1024) uint8_t smem_raw[];
  const uint32_t sb = (smem_u32(smem_raw) + 1023) & ~1023u;
  const int tid = threadIdx.x, lane = tid & 31;
  const int w = __shfl_sync(~0u, tid >> 5, 0);
  uint32_t rank;
  asm volatile("mov.u32 %0, %%cluster_ctarank;" : "=r"(rank));
  const int h = blockIdx.x / 3;
  asm volatile("griddepcontrol.launch_dependents;" ::: "memory");
  TG(0)
  if (tid == 0) {
    const uint32_t bars = sb + C_BAR;
    mbar_init(bars + B_M0 * 8, 1); mbar_init(bars + B_M1 * 8, 1); mbar_init(bars + B_M2 * 8, 1);
    for (int i = 0; i < 4; i++) mbar_init(bars + (B_R + i) * 8, 1);
    mbar_init(bars + B_X * 8, 9); mbar_init(bars + B_O * 8, 2); mbar_init(bars + B_T * 8, 1); mbar_init(bars + B_F * 8, 2);
    mbar_init(bars + B_XL * 8, 2); mbar_init(bars + B_U * 8, 1);
    mbar_init(bars + B_P1 * 8, 8); mbar_init(bars + B_P2 * 8, 8); mbar_init(bars + B_OT * 8, 3); mbar_init(bars + B_XF * 8, 8); mbar_init(bars + B_XA * 8, 8); mbar_init(bars + B_I * 8, 1); mbar_init(bars + B_PI * 8, 1); mbar_init(bars + B_J * 8, 1);
    asm volatile("fence.mbarrier_init.release.cluster;" ::: "memory");
  }
  {
    cp16(sb + C_OT + tid * 16, mem0 + (tid & 7) * DM + (tid >> 3) * 8);
    const bf16* W1 = (rank == 0 ? Wq : rank == 1 ? Wk : Wv) + h * 128;
#pragma unroll 4
    for (int cidx = tid; cidx < 512 * 16; cidx += 512) {
      const int d = cidx >> 4, q = cidx & 15;
      cp16(sb + C_X + d * W_STRIDE + q * 16, W1 + (size_t)d * HD + q * 8);
    }
    const int nt = rank == 2 ? 2 : 3;
    for (int cidx = tid; cidx < nt * 1024; cidx += 512) {
      const int tl = cidx >> 10, e = (cidx >> 3) & 127, q = cidx & 7;
      const int es = (e & ~30) | ((e & 6) << 2) | ((e >> 2) & 6);
      cp16(sb + C_WO + tl * 16384 + e * 128 + ((q ^ (e & 7)) << 4), Wo + (size_t)(h * 128 + es) * DM + (tl * 3 + rank) * 64 + q * 8);
    }
    asm volatile("cp.async.commit_group;" ::: "memory");
    if (w == 0) { HD(0) }
    if (w == 0) { HD(1) }
    asm volatile("cp.async.wait_group 0;" ::: "memory");
    fence_async_smem();
    __syncthreads();
    if (w == 0) { HD(2) }
  }
  if (w < 8) {
    reg_inc<184>();
    chain_proj(sb, w, lane, rank);
    TG(1)
    TRDUMP
    cluster_sync();
  } else if (w < 12) {
    reg_dec<120>();
    chain_mem(sb, w, lane, rank, h, mem0);
    STATDUMP
    TRDUMP
    cluster_sync();
  } else {
    reg_dec<24>();
    chain_dma(sb, w, lane, rank, h);
    TRDUMP
    cluster_sync();
  }
}
#undef TRC
#undef TRS

constexpr int K_BAR = 0, K_LN = 128, K_FH = 320, K_FS = 512, K_FY = 1536;
constexpr int K_W = 3072;
constexpr int K_O = K_W + 3 * 49152;
constexpr int K_ST = K_O + 65536;
constexpr int K_SMEM = K_ST + 16384;
static_assert(K_SMEM <= 232448 && 512 * W_STRIDE <= 3 * 49152, "shared memory");
enum { KB_FULL = 0, KB_EMPTY = 2, KB_OK = 4, KB_GO = 7, KB_ST = 10, KB_REL = 12 };
enum { KN_ST = 1, KN_ST1, KN_REL, KN_FFN, KN_INIT, KN_RES, KN_RES1, KN_CAND, KN_TAKEN, KN_FF2 };
#define GATE_R 850
struct WorkerParams {
  const bf16 *x0, *Wo, *w_r, *w_gate, *w_up, *w_down;
  bf16* out;
};
#define TRC (96 + blockIdx.x)
#define FT(e)
#define QUIET 4900
__device__ __forceinline__ void quiet_until(uint32_t t) {
  int d;
  while ((d = (int)(t - clk32())) > 0) warp_sleep(min(d / 3 + 20, 1000));
}
#define FOR_UNITS _Pragma("unroll 1") for (int st = 0, n = 0; st < WSTEP; st++) \
                  _Pragma("unroll 1") for (int v = st < NSEG ? 0 : st < WSTEP - 1 ? 1 : 2, sg = v ? st - WD : st; v < (st >= WD ? 3 : 1); v++, n++, sg = st - WD)

template <int ACC>
__device__ __forceinline__ void wg_ss8(float (&d)[4], uint64_t da, uint64_t db) {
  asm volatile("wgmma.mma_async.sync.aligned.m64n8k16.f32.bf16.bf16 {%0,%1,%2,%3}, %4, %5, %6, 1, 1, 1, 0;" : O4(d, 0) : "l"(da), "l"(db), "n"(ACC));
}
template <int NU>
__device__ __forceinline__ void ffn_slice(uint32_t sb, int t, const bf16* yrow, int ev) {
  const int lane = t & 31, c = t >> 5;
  FT(1)
  {
    const uint2 r = ld_rlx64(yrow + t * 4);
    asm volatile("st.shared.v2.b32 [%0], {%1,%2};" ::"r"(sb + K_FY + ((t >> 1) & 31) * 32 + (t >> 6) * 16 + (t & 1) * 8), "r"(r.x), "r"(r.y) : "memory");
  }
  fence_async_smem();
  bar_sync(KN_FFN, 128);
  FT(2)
  {
    float g[NU][4];
    const uint64_t da = mk_desc(sb + K_W, 16384, 512, 2), db = mk_desc(sb + K_FY, 32, 0, 0);
    wg_fence();
#pragma unroll
    for (int i = 0; i < 16; i++)
#pragma unroll
      for (int u = 0; u < NU; u++) { if (i == 0) wg_ss8<0>(g[u], da + u * 3072, db); else wg_ss8<1>(g[u], da + u * 3072 + i * 64, db + i * 4); }
    wg_commit();
    wg_wait<0>();
#pragma unroll
    for (int u = 0; u < NU; u++) {
      acc_fence(g[u]);
      if ((lane & 3) == 0) {
        const uint32_t a = sb + K_FS + u * 256 + c * 64 + lane;
        sts32(a, __float_as_uint(c < 2 ? g[u][0] : g[u][1])); sts32(a + 32, __float_as_uint(c < 2 ? g[u][2] : g[u][3]));
      }
    }
  }
  FT(3)
  bar_sync(KN_FFN, 128);
  {
    const uint32_t pa = sb + K_FS + c * 256 + lane * 4;
    const float gt = round_bf16(__uint_as_float(lds32(pa)) + __uint_as_float(lds32(pa + 128)));
    const float up = __shfl_xor_sync(~0u, gt, 16);
    const uint32_t hv = pack_bf16(round_bf16(__fdividef(gt, 1.f + __expf(-gt))) * up, 0.f);
    if (lane < 16) asm volatile("st.shared.b16 [%0], %1;" ::"r"(sb + K_FH + (c * 16 + lane) * 2), "h"((unsigned short)hv) : "memory");
  }
  fence_async_smem();
  bar_sync(KN_FFN, 128);
  FT(4)
#pragma unroll 1
  for (int hf = 0; hf < 2; hf++) {
    float o[4][4];
    const uint64_t da = mk_desc(sb + K_W + 32768 + hf * 8192, 16, 1024, 1), db = mk_desc(sb + K_FH, 16, 0, 0);
    wg_fence();
#pragma unroll
    for (int u = 0; u < NU; u++)
#pragma unroll
      for (int j = 0; j < 4; j++) { if (u == 0) wg_ss8<0>(o[j], da + j * 128, db); else wg_ss8<1>(o[j], da + u * 3072 + j * 128, db + u * 2); }
    wg_commit();
    wg_wait<0>();
    float lo = 0.f, hi = 0.f;
#pragma unroll
    for (int j = 0; j < 4; j++) {
      acc_fence(o[j]);
      const float a = __shfl_sync(~0u, o[j][0], lane & 28), b = __shfl_sync(~0u, o[j][2], lane & 28);
      if ((lane & 3) == j) { lo = a; hi = b; }
    }
    float* p = &g_fl.upd[ev][hf * 256 + (lane & 3) * 64 + c * 16 + (lane >> 2)];
    asm volatile("red.relaxed.gpu.global.add.f32 [%0], %1; red.relaxed.gpu.global.add.f32 [%0 + 32], %2;" ::"l"(p), "f"(lo), "f"(hi) : "memory");
  }
  FT(5)
  bar_sync(KN_FFN, 128);
  if (t == 96) red_release(g_fl.ffncnt[ev]);
  __syncwarp();
}
__device__ __forceinline__ uint4 pair_ln(uint4 r, float& e, uint32_t sl, int bar, int t) {
  const float x[8] = {bf_lo(r.x), bf_hi(r.x), bf_lo(r.y), bf_hi(r.y), bf_lo(r.z), bf_hi(r.z), bf_lo(r.w), bf_hi(r.w)};
  const float s = ((x[0] + x[1]) + (x[2] + x[3])) + ((x[4] + x[5]) + (x[6] + x[7]));
  const float q = (fmaf(x[0], x[0], x[1] * x[1]) + fmaf(x[2], x[2], x[3] * x[3])) + (fmaf(x[4], x[4], x[5] * x[5]) + fmaf(x[6], x[6], x[7] * x[7]));
  const bool u16 = t & 16, u8 = t & 8;
  const float a = (u16 ? q : s) + __shfl_xor_sync(~0u, u16 ? s : q, 16), b = e + __shfl_xor_sync(~0u, e, 16);
  float v = (u8 ? b : a) + __shfl_xor_sync(~0u, u8 ? a : b, 8);
  v += __shfl_xor_sync(~0u, v, 4); v += __shfl_xor_sync(~0u, v, 2); v += __shfl_xor_sync(~0u, v, 1);
  sts32(sl + (t >> 3) * 4, __float_as_uint(v));
  bar_sync(bar, 64);
  const uint4 s0 = lds128(sl), s1 = lds128(sl + 16);
  const float m = (__uint_as_float(s0.x) + __uint_as_float(s1.x)) * (1.f / DM), m2 = (__uint_as_float(s0.z) + __uint_as_float(s1.z)) * (1.f / DM);
  e = __uint_as_float(s0.y) + __uint_as_float(s1.y);
  float rs;
  asm("rsqrt.approx.ftz.f32 %0, %1;" : "=f"(rs) : "f"(fmaxf(fmaf(-m, m, m2), 0.f) + 1e-5f));
  return make_uint4(pack_bf16((x[0] - m) * rs, (x[1] - m) * rs), pack_bf16((x[2] - m) * rs, (x[3] - m) * rs),
                    pack_bf16((x[4] - m) * rs, (x[5] - m) * rs), pack_bf16((x[6] - m) * rs, (x[7] - m) * rs));
}
__device__ __forceinline__ uint32_t score_bits(float r) {
  const uint32_t b = pack_bf16(0.f, r);
  return (b & 0x80000000u) ? ~b : (b | 0x80000000u);
}

__global__ void __launch_bounds__(640, 1) worker_kernel(const __grid_constant__ WorkerParams prm) {
  extern __shared__ __align__(1024) uint8_t smem_raw[];
  const uint32_t sb = smem_u32(smem_raw);
  if (sb & 1023) __trap();
  const int tid = threadIdx.x, lane = tid & 31;
  const int w = __shfl_sync(~0u, tid >> 5, 0);
  const int me = blockIdx.x, kb = me >> 2, cb = me & 3;
  const bool full = me < 32;
  const uint32_t bars = sb + K_BAR;
  TG(0)
  if (tid == 0) {
    for (int i = 0; i < 2; i++) { mbar_init(bars + (KB_FULL + i) * 8, 1); mbar_init(bars + (KB_EMPTY + i) * 8, 1); }
    for (int i = 0; i < 9; i++) mbar_init(bars + (KB_OK + i) * 8, i < 3 ? 2 : 1);
    sts32(sb + K_LN + 144, 0);
    asm volatile("fence.mbarrier_init.release.cluster;" ::: "memory");
  }
  if (full) {
    const bf16* W1 = prm.Wo + (size_t)kb * 512 * DM + cb * 128;
#pragma unroll 4
    for (int cidx = tid; cidx < 512 * 16; cidx += 640) {
      const int d = cidx >> 4, q = cidx & 15;
      cp16(sb + K_W + d * W_STRIDE + q * 16, W1 + (size_t)d * DM + q * 8);
    }
    asm volatile("cp.async.commit_group;" ::: "memory");
    asm volatile("cp.async.wait_group 0;" ::: "memory");
  }
  fence_async_smem();
  __syncthreads();
  if (w < 8) {
    reg_inc<176>();
    if (full) {
      uint32_t wA[32][4];
      load_wfrags(wA, sb + K_W, w, lane);
      bar_arrive(KN_INIT, 384);
      const uint32_t sp = pin(sb + K_ST + ((lane >> 4) * 8 + (lane & 7)) * 256 + (((2 * w + ((lane >> 3) & 1)) ^ (lane & 7)) << 4));
      const uint32_t tm = pin(lane < 4 ? 0x00010001u : 0u);
      FOR_UNITS {
        float d[16];
        mbar_wait(bars + (KB_FULL + (n & 1)) * 8, (n >> 1) & 1, 81);
        TR(4 * v)
        const uint64_t db = mk_desc(sb + K_O + (n & 1) * 32768, 128, 2048, 0);
        wg_fence();
#pragma unroll
        for (int ks = 0; ks < 32; ks++) {
          if (ks == 0) wg_rs32<0, 0>(d, wA[ks], db);
          else wg_rs32<0, 1>(d, wA[ks], db + (ks >> 3) * 512 + (ks & 7) * 16);
        }
        wg_commit();
        mbar_wait(bars + (KB_ST + (n & 1)) * 8, ((n >> 1) & 1) ^ 1, 82);
        wg_wait<0>();
        acc_fence(d);
        TR(4 * v + 1)
        const uint32_t tag = (sg & 2) ? 0u : tm;
        uint32_t pk[8];
#pragma unroll
        for (int i = 0; i < 8; i++) pk[i] = (pack_bf16(d[2 * i], d[2 * i + 1]) & ~tm) | tag;
        stsm4t(sp + (n & 1) * 8192, pk[0], pk[1], pk[2], pk[3]);
        stsm4t(sp + (n & 1) * 8192 + 4096, pk[4], pk[5], pk[6], pk[7]);
        bar_arrive(KN_ST + (n & 1), 288);
        TR(4 * v + 2)
      }
    }
  } else if (w < 12) {
    reg_dec<56>();
    if (full) {
      const int ly = (w >> 1) & 1, t = pin(tid & 63);
      const uint32_t so = pin((t >> 4) * 8192 + me * 256 + (((t & 15) ^ (me & 7)) << 4));
      int sstar = -1;
      uint32_t sl = sb + K_LN + ly * 64;
      float rr = 0.f;
      int kprev = -1;
      auto records = [&](int sg, uint32_t off) {
        int it = 0;
        while (__any_sync(~0u, (int)lds32(sb + K_LN + 144) <= sg)) { give_up(++it, SPIN_LIMIT, 86); warp_sleep(50); }
        return lds32(sb + K_LN + off);
      };
#pragma unroll 1
      for (int n = ly ? 2 * WD : 0; n < 2 * WSTEP; n++) {
        const int st = n >> 1, v = (n & 1) ? 2 : ly, sg = v ? st - WD : st, tok = sg * 32 + me;
        if (n == 2 * NSEG) bar_sync(KN_INIT, 128);
        if (n == 2 * NSEG + 2) sstar = records(NSEG - 1, 156);
        if (v == 2 ? sg < 0 || (st < NSEG ? st & 1 : 0) != ly : sg >= NSEG - v) continue;
        const bf16* xin = v ? g_rows[tok][0][2] : prm.x0 + tok * DM;
        if (v == 2 && ((records(sg, 148 + (sg >> 5) * 4) >> (sg & 31)) & 1)) xin = g_x2p[sg][0];
        const uint8_t* src = g_part[v] + (sg & 1) * (32 * 8192) + so;
        const uint32_t flip = (sg & 2) ? ~0u : 0u;
        mbar_wait(bars + (KB_GO + v) * 8, sg & 1, 87);
        TR(4 * v)
        uint4 p[8], x;
        int it = 0;
#pragma unroll 1
        do {
#pragma unroll
          for (int k = 0; k < 8; k++) p[k] = ld_rlx128(src + k * 32768);
          x = ld_rlx128(((WEXP & 2) ? prm.x0 : xin) + t * 8);
          give_up(it++, SPIN_LIMIT, 85);
        } while (__builtin_expect(!__all_sync(~0u, (int)and3(and3(and_x(p[0].x, p[1].x, flip), and_x(p[2].x, p[3].x, flip), 1u),
                                                             and_x(p[4].x, p[5].x, flip), and_x(p[6].x, p[7].x, flip))), 0));
        mbar_arrive_z(bars + (KB_OK + v) * 8, t & 31);
#define P8(h, f) (((h(p[0].f) + h(p[1].f)) + (h(p[2].f) + h(p[3].f))) + ((h(p[4].f) + h(p[5].f)) + (h(p[6].f) + h(p[7].f))))
#define X8(f) x.f = add_bf16x2(x.f, pack_bf16(P8(bf_lo, f), P8(bf_hi, f)));
        X8(x) X8(y) X8(z) X8(w)
#undef X8
#undef P8
        TRV(12 + v, it - 1)
        TR(4 * v + 1)
        bf16* dst = g_rows[tok][v][0] + t * 8;
        *(uint4*)dst = x;
        const uint4 wr = ld_rlx128(prm.w_r + t * 8);
        sl ^= 32;
        uint4 y = pair_ln(x, rr, sl, KN_RES + ly, t);
        *(uint4*)(dst + DM) = y;
        x = make_uint4(add_bf16x2(x.x, y.x), add_bf16x2(x.y, y.y), add_bf16x2(x.z, y.z), add_bf16x2(x.w, y.w));
        *(uint4*)(v == (sg < sstar ? 1 : 2) ? prm.out + tok * DM + t * 8 : dst + 2 * DM) = x;
        asm volatile("{ .reg .pred p; setp.eq.u32 p, %2, 0; @p st.relaxed.gpu.global.u64 [%0], %1; }" ::"l"(&g_fl.key[0][0][0] + max(kprev, 0)),
                     "l"((u64)score_bits(rr) << 32 | (uint32_t)~(kprev & (NTOK - 1))), "r"(t | (kprev < 0)) : "memory");
        kprev = v * NTOK + tok;
        rr = (fmaf(bf_lo(y.x), bf_lo(wr.x), bf_hi(y.x) * bf_hi(wr.x)) + fmaf(bf_lo(y.y), bf_lo(wr.y), bf_hi(y.y) * bf_hi(wr.y))) +
             (fmaf(bf_lo(y.z), bf_lo(wr.z), bf_hi(y.z) * bf_hi(wr.z)) + fmaf(bf_lo(y.w), bf_lo(wr.w), bf_hi(y.w) * bf_hi(wr.w)));
        if (v == 0 || st >= NSEG) {
          sl ^= 32;
          y = pair_ln(x, rr, sl, KN_RES + ly, t);
          if (v == 0) *(uint4*)(g_xs[1] + sg * 32768 + (t >> 3) * 4096 + me * 128 + (((t ^ me) & 7) << 4)) = y;
          sts32(sb + K_LN + 128 + ly * 4, score_bits(rr));
          bar_arrive(KN_REL, v == 0 || st == WSTEP - 1 ? 96 : 160);
          kprev = -1;
        }
        TR(4 * v + 2)
      }
    }
  } else if (w < 16) {
    reg_dec<48>();
    const int t = tid - 384, nu = full ? 3 : 4;
    if (full) bar_sync(KN_INIT, 384);
    {
      const int j0 = (full ? me * 3 : 96 + (me - 32) * 4) * 16;
#pragma unroll 1
      for (int i = t; i < nu * 3072; i += 128) {
        const int u = i / 3072, r = i - u * 3072;
        const int q = (r ^ (r >> 3)) & 3, r2 = r - 2048;
        const bf16* src = r < 2048 ? ((q & 2) ? prm.w_up : prm.w_gate) + (size_t)(r >> 2) * FF + j0 + u * 16 + (q & 1) * 8
                                   : prm.w_down + (size_t)(j0 + u * 16 + ((r2 >> 3) & 15)) * DM + (r2 >> 7) * 64 + ((r2 ^ (r2 >> 3)) & 7) * 8;
        cp16(sb + K_W + i * 16, src);
      }
      asm volatile("cp.async.wait_all;" ::: "memory");
    }
    bar_arrive(KN_TAKEN, 160);
#pragma unroll 1
    while (true) {
      bar_sync(KN_CAND, 160);
      const uint4 cand = lds128(sb + K_LN + 160);
      const u64 k = (u64)cand.y << 32 | cand.x;
      const int ev = cand.z, ver = cand.w & 3, tok = key_token(k);
      const bool last = cand.w & 4;
      if (!last) {
        bar_arrive(KN_TAKEN, 160);
        FT(0)
        if (full) ffn_slice<3>(sb, t, g_rows[tok][ver][1], ev); else ffn_slice<4>(sb, t, g_rows[tok][ver][1], ev);
      }
      if ((tok & 31) == me && (ver == 0 || last)) {
        if (t < 64) {
          FT(6)
          uint4 x = ld_rlx128(g_rows[tok][ver][0] + t * 8);
          const uint4 y = ld_rlx128(g_rows[tok][ver][1] + t * 8);
          const float sig = round_bf16(__fdividef(1.f, 1.f + __expf(-key_score(k))));
          int it = 0;
          while (ld_rlx32(g_fl.ffncnt[ev]) < NWORK) { give_up(++it, SPIN_LIMIT, 80); warp_sleep(40); }
          const uint4 u0 = ld_rlx128(&g_fl.upd[ev][t * 8]), u1 = ld_rlx128(&g_fl.upd[ev][t * 8 + 4]);
          auto upd = [&](uint32_t xw, uint32_t yw, uint32_t a, uint32_t b) {
            const uint32_t r = pack_bf16(__uint_as_float(a), __uint_as_float(b));
            return add_bf16x2(xw, add_bf16x2(yw, pack_bf16(bf_lo(r) * sig, bf_hi(r) * sig)));
          };
          x = make_uint4(upd(x.x, y.x, u0.x, u0.y), upd(x.y, y.y, u0.z, u0.w), upd(x.z, y.z, u1.x, u1.y), upd(x.w, y.w, u1.z, u1.w));
          FT(7)
          *(uint4*)((ver ? prm.out + tok * DM : g_x2p[ev][0]) + t * 8) = x;
          if (ver == 0) {
            float e = 0.f;
            *(uint4*)(g_x2p[ev][1] + t * 8) = pair_ln(x, e, sb + K_FS, KN_FF2, t);
            bar_sync(KN_FF2, 64);
            if (t == 0) st_release32(g_fl.patch[ev], 1);
            __syncwarp();
          }
        }
      }
      if (ev == NSEG && !last && full) {
        const int nc = min((int)lds32(sb + K_LN + 156), NSEG + 1 - WD);
#pragma unroll 1
        for (int s0 = (t >> 6) * 4; s0 < nc; s0 += 8) {
          uint4 q[4];
#pragma unroll
          for (int i = 0; i < 4; i++) q[i] = ld_rlx128(g_rows[min(s0 + i, nc - 1) * 32 + me][1][2] + (t & 63) * 8);
#pragma unroll
          for (int i = 0; i < 4; i++) *(uint4*)(prm.out + (min(s0 + i, nc - 1) * 32 + me) * DM + (t & 63) * 8) = q[i];
        }
      }
      FT(8)
      if (last) break;
    }
  } else {
    reg_dec<24>();
    if (w == 16) {
      u64 best = 0, mask = 0;
      int sstar = 0;
      uint32_t ver = 0, ev = 0;
      auto post = [&](uint32_t cmd) {
        bar_sync(KN_TAKEN, 160);
        sts128(sb + K_LN + 160, make_uint4((uint32_t)best, (uint32_t)(best >> 32), ev, ver | cmd));
        bar_arrive(KN_CAND, 160);
      };
      u64 accn = 0, acca = 0;
      uint32_t recs = 0;
      int j = 0;
      uint32_t tq = clk32();
#pragma unroll 1
      for (int st = 0; st < WSTEP; st++) {
        const u64* keys = st < NSEG ? g_fl.key[0][st] : g_fl.key[2][st - WD];
        const bool early = __any_sync(~0u, ld_rlx32(keys + lane) == 0);
        if (early && st < NSEG) quiet_until(tq);
        u64 k = wait_keys(keys, lane, 91);
        if (early) tq = clk32() + QUIET;
        if (st < NSEG) {
          const bool rec = k > best;
          recs &= ~(1u << (st & 31));
          if (rec) {
            best = k; ev = sstar = st;
            recs |= 1u << (st & 31);
            if ((key_token(k) & 31) == me) mask |= 1ull << st;
          }
          if (lane == 0) sts128(sb + K_LN + 144, make_uint4(st + 1, (uint32_t)mask, (uint32_t)(mask >> 32), sstar));
          __syncwarp();
          if (rec) post(0);
        }
#pragma unroll 1
        for (; j <= st - WD - (st < NSEG ? 2 : 0); j++) {
          u64 kn = 1, kc;
          int it = 0;
          do {
            if (j < NSEG - 1) asm volatile("ld.relaxed.gpu.global.u64 %0, [%1];" : "=l"(kn) : "l"(&g_fl.key[1][j][lane]) : "memory");
            asm volatile("ld.relaxed.gpu.global.u64 %0, [%1];" : "=l"(kc) : "l"(&g_fl.key[2][j][lane]) : "memory");
            give_up(it++, SPIN_LIMIT, 92);
          } while (__any_sync(~0u, kn == 0 || kc == 0));
          if ((recs >> (j & 31)) & 1) acca = accn;
          if (kc > acca) acca = kc;
          if (kn > accn) accn = kn;
        }
        if (st >= NSEG) {
          const u64 m = j <= sstar ? accn : acca;
          const uint32_t hi = __reduce_max_sync(~0u, (uint32_t)(m >> 32));
          k = (u64)hi << 32 | __reduce_max_sync(~0u, (uint32_t)(m >> 32) == hi ? (uint32_t)m : 0u);
          if (st == NSEG || k != best) {
            best = k; ev = st;
            ver = (key_token(k) >> 5) < sstar ? 1 : 2;
            post(0);
          }
        }
      }
      HD(6)
      post(4);
    } else if (!full) {
    } else if (w == 17) {
      uint32_t tq = clk32();
      FOR_UNITS {
        if (ld_rlx32(&g_fl.oflag[v][sg][kb]) < 4) {
          if (v == (st < NSEG ? 0 : 1) && st < WSTEP - 3) quiet_until(tq);
          wait_count(&g_fl.oflag[v][sg][kb], 4, 84);
          if (v == (st < NSEG ? 0 : 1)) tq = clk32() + QUIET;
        }
        mbar_wait(bars + (KB_EMPTY + (n & 1)) * 8, ((n >> 1) & 1) ^ 1, 83);
        TR(v)
        if (st == WSTEP - 1) { HD(v) }
        if (lane == 0) {
          fence_async_glb();
          mbar_expect_tx(bars + (KB_FULL + (n & 1)) * 8, (WEXP & 4) ? 4096 : 32768);
          bulk_g2s(sb + K_O + (n & 1) * 32768, g_O[(v ? sg + DELTA : sg) & (OSLOTS - 1)][v] + kb * 32768, (WEXP & 4) ? 4096 : 32768, bars + (KB_FULL + (n & 1)) * 8);
        }
        __syncwarp();
      }
    } else if (w == 18) {
      FOR_UNITS {
        if (sg > 0) mbar_wait(bars + (KB_OK + v) * 8, (sg - 1) & 1, 90);
        bar_sync(KN_ST + (n & 1), 288);
        fence_async_smem();
        const uint32_t tg = clk32() + GATE_R;
        if (lane == 0) {
          bulk_s2g(g_part[v] + ((sg & 1) * 32 + me) * 8192, sb + K_ST + (n & 1) * 8192, 8192);
          asm volatile("cp.async.bulk.commit_group;" ::: "memory");
          mbar_arrive_z(bars + (KB_EMPTY + (n & 1)) * 8, 0);
          asm volatile("cp.async.bulk.wait_group.read 0;" ::: "memory");
        }
        __syncwarp();
        mbar_arrive_z(bars + (KB_ST + (n & 1)) * 8, lane);
        TR(v)
        if (v == (st < NSEG ? 0 : st < WSTEP - 1 ? 1 : 2) && st > 0) mbar_wait(bars + KB_REL * 8, (st - 1) & 1, 93);
        wait_clock(tg);
        if (st == WSTEP - 1) { HD(2 + v) }
        mbar_arrive_z(bars + (KB_GO + v) * 8, lane);
      }
    } else {
#pragma unroll 1
      for (int st = 0; st < WSTEP; st++) {
        const int sg = st < NSEG ? st : st - WD;
        const bool both = st >= NSEG && st < WSTEP - 1;
        bar_sync(KN_REL, both ? 160 : 96);
        const uint32_t ob = __shfl_sync(~0u, lds32(sb + K_LN + 128), 0), obn = __shfl_sync(~0u, lds32(sb + K_LN + 132), 0);
        mbar_arrive_z(bars + KB_REL * 8, lane);
        if (st == WSTEP - 1) { HD(5) }
        if (lane == 0) {
          if (both) asm volatile("st.relaxed.gpu.global.u64 [%0], %1;" ::"l"(&g_fl.key[1][sg][me]), "l"((u64)obn << 32 | (uint32_t)~(sg * 32 + me)) : "memory");
          st_release_u64(&g_fl.key[st < NSEG ? 0 : 2][sg][me], (u64)ob << 32 | (uint32_t)~(sg * 32 + me));
        }
        __syncwarp();
        TR(0)
      }
    }
  }
}
#undef TRC

bool g_ready;

}

extern "C" void kernel_launch(void* const* d_in, const int* in_sizes, int n_in, void* d_out, int out_size) {
  (void)in_sizes; (void)n_in; (void)out_size;
  const bf16* x0 = (const bf16*)d_in[0];
  const bf16* mem0 = (const bf16*)d_in[1];
  const bf16* Wq = (const bf16*)d_in[2];
  const bf16* Wk = (const bf16*)d_in[3];
  const bf16* Wv = (const bf16*)d_in[4];
  const bf16* Wo = (const bf16*)d_in[5];
  if (!g_ready) {
    cudaFuncSetAttribute(worker_kernel, cudaFuncAttributeMaxDynamicSharedMemorySize, K_SMEM);
    cudaFuncSetAttribute(chain_kernel, cudaFuncAttributeMaxDynamicSharedMemorySize, C_SMEM);
    g_ready = true;
  }
  cudaStream_t st = cudaStreamPerThread;
  prep_kernel<<<NTOK / 8, 256, 0, st>>>(x0, Wq, Wk, Wv, Wo);
  chain_kernel<<<96, 512, C_SMEM, st>>>(Wq, Wk, Wv, Wo, mem0);
  cudaLaunchAttribute pdl[1];
  pdl[0].id = cudaLaunchAttributeProgrammaticStreamSerialization;
  pdl[0].val.programmaticStreamSerializationAllowed = 1;
  WorkerParams wp;
  wp.x0 = x0; wp.Wo = Wo; wp.w_r = (const bf16*)d_in[8]; wp.w_gate = (const bf16*)d_in[9]; wp.w_up = (const bf16*)d_in[10];
  wp.w_down = (const bf16*)d_in[11]; wp.out = (bf16*)d_out;
  cudaLaunchConfig_t cfg = {};
  cfg.gridDim = dim3(NWORK); cfg.blockDim = dim3(640); cfg.dynamicSmemBytes = K_SMEM; cfg.stream = st;
  cfg.attrs = pdl; cfg.numAttrs = 1;
  cudaLaunchKernelEx(&cfg, worker_kernel, wp);
}
```

```cpp
#include <cuda_runtime.h>
#include <cuda_bf16.h>
#include <cuda.h>
#include <stdint.h>

namespace {

typedef __nv_bfloat16 bf16;
typedef unsigned long long u64;

constexpr int NTOK = 2048, DM = 512, HD = 4096, NSEG = 64, FF = 1792;
#define DELTA 5
constexpr int NSTEP = NSEG + DELTA;
#define WLAG 1
constexpr int WD = DELTA + WLAG, WSTEP = NSEG + WD;
constexpr int SPIN_LIMIT = 40000;
constexpr int MBAR_LIMIT = 20000;
constexpr int NWORK = 36;
constexpr int OSLOTS = 8;
#define SLP_C 100
#define SLP_K 200
#define WEXP 0

__device__ __align__(1024) uint8_t g_xs[2][NSEG * 32768];
__device__ __align__(1024) uint8_t g_O[OSLOTS][3][32 * 8192];
__device__ __align__(1024) uint8_t g_part[3][2 * 32 * 8192];
__device__ __align__(1024) bf16 g_rows[NTOK][3][3][DM];
__device__ __align__(1024) bf16 g_x2p[NSEG][2][DM];
struct Flags {
  uint32_t pol[96];
  uint32_t stamp[96];
  uint32_t oflag[3][NSEG][8];
  uint32_t ffncnt[WSTEP][8];
  uint32_t patch[NSEG][8];
  u64 key[3][NSEG][32];
  float upd[WSTEP][DM];
};
struct Exchange { uint32_t M[4 * 16384], P[96 * 4096]; Flags fl; uint32_t ready[32]; };
__device__ __align__(65536) Exchange g_ex;
#define g_M g_ex.M
#define g_P g_ex.P
#define g_fl g_ex.fl
#define TR(e)
#define TRV(e, v)
#define TG(i)
#define HD(e)
#define TRDUMP
#define TREXTRA 0

#define STAT(e, v)
#define STATC(n)
#define STATDUMP
__device__ __forceinline__ uint32_t smem_u32(const void* p) { return (uint32_t)__cvta_generic_to_shared(p); }
__device__ __forceinline__ uint32_t pack_bf16(float lo, float hi) {
  uint32_t r;
  asm("cvt.rn.bf16x2.f32 %0, %1, %2;" : "=r"(r) : "f"(hi), "f"(lo));
  return r;
}
__device__ __forceinline__ float bf_lo(uint32_t v) { return __uint_as_float(v << 16); }
__device__ __forceinline__ float bf_hi(uint32_t v) { return __uint_as_float(v & 0xffff0000u); }
__device__ __forceinline__ float ex2_fast(float x) { float y; asm("ex2.approx.ftz.f32 %0, %1;" : "=f"(y) : "f"(x)); return y; }
__device__ __forceinline__ float round_bf16(float x) { return __bfloat162float(__float2bfloat16_rn(x)); }
__device__ __forceinline__ uint32_t clk32() { uint32_t t; asm volatile("mov.u32 %0, %%clock;" : "=r"(t) :: "memory"); return t; }

__device__ __forceinline__ void mma16816(float (&d)[4], uint32_t a0, uint32_t a1, uint32_t a2, uint32_t a3,
                                         uint32_t b0, uint32_t b1) {
  asm("mma.sync.aligned.m16n8k16.row.col.f32.bf16.bf16.f32 {%0,%1,%2,%3}, {%4,%5,%6,%7}, {%8,%9}, {%0,%1,%2,%3};"
      : "+f"(d[0]), "+f"(d[1]), "+f"(d[2]), "+f"(d[3])
      : "r"(a0), "r"(a1), "r"(a2), "r"(a3), "r"(b0), "r"(b1));
}
__device__ __forceinline__ void ldsm4t(uint32_t (&r)[4], uint32_t addr) {
  asm volatile("ldmatrix.sync.aligned.m8n8.x4.trans.shared.b16 {%0,%1,%2,%3}, [%4];"
               : "=r"(r[0]), "=r"(r[1]), "=r"(r[2]), "=r"(r[3]) : "r"(addr) : "memory");
}
__device__ __forceinline__ void stsm4(uint32_t addr, uint32_t a, uint32_t b, uint32_t c, uint32_t d) {
  asm volatile("stmatrix.sync.aligned.m8n8.x4.shared.b16 [%0], {%1,%2,%3,%4};" ::"r"(addr), "r"(a), "r"(b), "r"(c), "r"(d) : "memory");
}
__device__ __forceinline__ void stsm4t(uint32_t addr, uint32_t a, uint32_t b, uint32_t c, uint32_t d) {
  asm volatile("stmatrix.sync.aligned.m8n8.x4.trans.shared.b16 [%0], {%1,%2,%3,%4};" ::"r"(addr), "r"(a), "r"(b), "r"(c), "r"(d) : "memory");
}
__device__ __forceinline__ uint4 lds128(uint32_t a) {
  uint4 v; asm volatile("ld.shared.v4.b32 {%0,%1,%2,%3}, [%4];" : "=r"(v.x), "=r"(v.y), "=r"(v.z), "=r"(v.w) : "r"(a) : "memory"); return v;
}
__device__ __forceinline__ uint32_t lds32(uint32_t a) { uint32_t v; asm volatile("ld.shared.b32 %0, [%1];" : "=r"(v) : "r"(a) : "memory"); return v; }
__device__ __forceinline__ void sts32(uint32_t a, uint32_t x) { asm volatile("st.shared.b32 [%0], %1;" ::"r"(a), "r"(x) : "memory"); }
__device__ __forceinline__ void sts128(uint32_t a, uint4 v) {
  asm volatile("st.shared.v4.b32 [%0], {%1,%2,%3,%4};" ::"r"(a), "r"(v.x), "r"(v.y), "r"(v.z), "r"(v.w) : "memory");
}
__device__ __forceinline__ void cp16(uint32_t dst, const void* src) {
  asm volatile("cp.async.cg.shared.global [%0], [%1], 16;" ::"r"(dst), "l"(src) : "memory");
}
__device__ __forceinline__ void mbar_init(uint32_t mbar, uint32_t cnt) {
  asm volatile("mbarrier.init.shared.b64 [%0], %1;" ::"r"(mbar), "r"(cnt) : "memory");
}
__device__ __forceinline__ void mbar_expect_tx(uint32_t mbar, uint32_t bytes) {
  asm volatile("mbarrier.arrive.expect_tx.shared.b64 _, [%0], %1;" ::"r"(mbar), "r"(bytes) : "memory");
}
__device__ __forceinline__ void mbar_arrive_z(uint32_t mbar, uint32_t z) {
  asm volatile("{ .reg .pred p; setp.eq.u32 p, %1, 0; @p mbarrier.arrive.shared.b64 _, [%0]; }" ::"r"(mbar), "r"(z) : "memory");
}
__device__ __forceinline__ void mbar_expect_tx_z(uint32_t mbar, uint32_t bytes, uint32_t z) {
  asm volatile("{ .reg .pred p; setp.eq.u32 p, %2, 0; @p mbarrier.arrive.expect_tx.shared.b64 _, [%0], %1; }" ::"r"(mbar), "r"(bytes), "r"(z) : "memory");
}
__device__ __forceinline__ void mbar_arrive_remote_z(uint32_t mbar, uint32_t z) {
  asm volatile("{ .reg .pred p; setp.eq.u32 p, %1, 0; @p mbarrier.arrive.shared::cluster.b64 _, [%0]; }" ::"r"(mbar), "r"(z) : "memory");
}
__device__ __forceinline__ void warp_sleep(uint32_t ns) { __nanosleep(ns); __syncwarp(); }
__device__ __forceinline__ void fail(int) { __trap(); }
__device__ __forceinline__ void give_up(int it, int limit, int code) { if (it > limit) fail(code); }
__device__ __forceinline__ void mbar_wait(uint32_t mbar, uint32_t par, int code) {
  asm volatile("{ .reg .pred p; .reg .b32 n; mov.b32 n, %2;\n"
               "W: mbarrier.try_wait.parity.shared::cta.b64 p, [%0], %1; @p bra D;\n"
               "add.s32 n, n, -1; setp.eq.s32 p, n, 0; @p trap; bra W;\n"
               "D: }" ::"r"(mbar), "r"(par), "n"(MBAR_LIMIT) : "memory");
}
__device__ __forceinline__ void bulk_g2s(uint32_t dst, const void* src, uint32_t bytes, uint32_t mbar) {
  asm volatile("cp.async.bulk.shared::cluster.global.mbarrier::complete_tx::bytes [%0], [%1], %2, [%3];"
               ::"r"(dst), "l"(src), "r"(bytes), "r"(mbar) : "memory");
}
__device__ __forceinline__ void bulk_s2r(uint32_t dst, uint32_t src, uint32_t bytes, uint32_t mbar) {
  asm volatile("cp.async.bulk.shared::cluster.shared::cta.mbarrier::complete_tx::bytes [%0], [%1], %2, [%3];"
               ::"r"(dst), "r"(src), "r"(bytes), "r"(mbar) : "memory");
}
__device__ __forceinline__ void bulk_s2g(void* dst, uint32_t src, uint32_t bytes) {
  asm volatile("cp.async.bulk.global.shared::cta.bulk_group [%0], [%1], %2;" ::"l"(dst), "r"(src), "r"(bytes) : "memory");
}
__device__ __forceinline__ void fence_async_smem() { asm volatile("fence.proxy.async.shared::cta;" ::: "memory"); }
__device__ __forceinline__ void fence_async_glb() { asm volatile("fence.proxy.async.global;" ::: "memory"); }
__device__ __forceinline__ void bar_sync(int id, int n) { asm volatile("bar.sync %0, %1;" ::"r"(id), "r"(n) : "memory"); }
__device__ __forceinline__ void bar_arrive(int id, int n) { asm volatile("bar.arrive %0, %1;" ::"r"(id), "r"(n) : "memory"); }
__device__ __forceinline__ void cluster_sync() { asm volatile("barrier.cluster.arrive.release; barrier.cluster.wait.acquire;" ::: "memory"); }
__device__ __forceinline__ uint32_t mapa_u32(uint32_t a, uint32_t r) {
  uint32_t o;
  asm("mapa.shared::cluster.u32 %0, %1, %2;" : "=r"(o) : "r"(a), "r"(r));
  return o;
}
template <int OFF>
__device__ __forceinline__ void st_async32(uint32_t a, uint32_t x, uint32_t mbar) {
  asm volatile("st.async.weak.shared::cluster.mbarrier::complete_tx::bytes.b32 [%0 + %3], %1, [%2];" ::"r"(a), "r"(x), "r"(mbar), "n"(OFF) : "memory");
}
__device__ __forceinline__ uint4 ld_rlx128(const void* p) {
  uint4 v;
  asm volatile("ld.relaxed.gpu.global.v4.u32 {%0,%1,%2,%3}, [%4];" : "=r"(v.x), "=r"(v.y), "=r"(v.z), "=r"(v.w) : "l"(p) : "memory");
  return v;
}
__device__ __forceinline__ uint2 ld_rlx64(const void* p) {
  uint2 v; asm volatile("ld.relaxed.gpu.global.v2.u32 {%0,%1}, [%2];" : "=r"(v.x), "=r"(v.y) : "l"(p) : "memory"); return v;
}
__device__ __forceinline__ uint32_t ld_rlx32(const void* p) {
  uint32_t v; asm volatile("ld.relaxed.gpu.global.u32 %0, [%1];" : "=r"(v) : "l"(p) : "memory"); return v;
}
__device__ __forceinline__ void st_rlx32(void* p, uint32_t a) { asm volatile("st.relaxed.gpu.global.u32 [%0], %1;" ::"l"(p), "r"(a) : "memory"); }
__device__ __forceinline__ void red_release(uint32_t* p) { asm volatile("red.release.gpu.global.add.u32 [%0], 1;" ::"l"(p) : "memory"); }
__device__ __forceinline__ void st_release32(void* p, uint32_t a) { asm volatile("st.release.gpu.global.u32 [%0], %1;" ::"l"(p), "r"(a) : "memory"); }
__device__ __forceinline__ void st_release_u64(void* p, u64 a) { asm volatile("st.release.gpu.global.u64 [%0], %1;" ::"l"(p), "l"(a) : "memory"); }
__device__ __forceinline__ void wait_count(const uint32_t* p, uint32_t val, int code) {
  int it = 0;
  while (ld_rlx32(p) < val) {
    give_up(++it, SPIN_LIMIT, code);
    warp_sleep(SLP_C);
  }
}
__device__ __forceinline__ u64 wait_keys(const u64* keys, int lane, int code) {
  u64 k;
  int it = 0;
  while (true) {
    asm volatile("ld.relaxed.gpu.global.u64 %0, [%1];" : "=l"(k) : "l"(keys + lane) : "memory");
    if (__all_sync(~0u, k != 0)) break;
    give_up(++it, SPIN_LIMIT, code);
    warp_sleep(SLP_K);
  }
  const uint32_t hi = __reduce_max_sync(~0u, (uint32_t)(k >> 32));
  const uint32_t lo = __reduce_max_sync(~0u, (uint32_t)(k >> 32) == hi ? (uint32_t)k : 0u);
  return (u64)hi << 32 | lo;
}
__device__ __forceinline__ int key_token(u64 k) { return (int)(~(uint32_t)k) & (NTOK - 1); }
__device__ __forceinline__ float key_score(u64 k) {
  const uint32_t ob = (uint32_t)(k >> 32);
  return __uint_as_float((ob & 0x80000000u) ? (ob & 0x7fffffffu) : ~ob);
}

__device__ __forceinline__ uint64_t mk_desc(uint32_t saddr, uint32_t lbo, uint32_t sbo, uint32_t sw) {
  return (uint64_t)((saddr & 0x3FFFF) >> 4) | (uint64_t)(lbo >> 4) << 16 | (uint64_t)(sbo >> 4) << 32 | (uint64_t)sw << 62;
}
template <int N> __device__ __forceinline__ void reg_inc() { asm volatile("setmaxnreg.inc.sync.aligned.u32 %0;" ::"n"(N)); }
template <int N> __device__ __forceinline__ void reg_dec() { asm volatile("setmaxnreg.dec.sync.aligned.u32 %0;" ::"n"(N)); }
__device__ __forceinline__ void wg_fence() { asm volatile("wgmma.fence.sync.aligned;" ::: "memory"); }
__device__ __forceinline__ void wg_commit() { asm volatile("wgmma.commit_group.sync.aligned;" ::: "memory"); }
template <int N> __device__ __forceinline__ void wg_wait() { asm volatile("wgmma.wait_group.sync.aligned %0;" ::"n"(N) : "memory"); }
template <int N> __device__ __forceinline__ void acc_fence(float (&d)[N]) {
#pragma unroll
  for (int i = 0; i < N; i++) asm volatile("" : "+f"(d[i]) :: "memory");
}
#define O4(d, i) "+f"(d[i]), "+f"(d[i + 1]), "+f"(d[i + 2]), "+f"(d[i + 3])
template <int TB, int ACC>
__device__ __forceinline__ void wg_rs24(float (&d)[12], const uint32_t (&a)[4], uint64_t db) {
  asm volatile("wgmma.mma_async.sync.aligned.m64n24k16.f32.bf16.bf16 {%0,%1,%2,%3,%4,%5,%6,%7,%8,%9,%10,%11}, {%12,%13,%14,%15}, %16, %17, 1, 1, %18;"
               : O4(d, 0), O4(d, 4), O4(d, 8) : "r"(a[0]), "r"(a[1]), "r"(a[2]), "r"(a[3]), "l"(db), "n"(ACC), "n"(TB));
}
template <int TB, int ACC>
__device__ __forceinline__ void wg_rs32(float (&d)[16], const uint32_t (&a)[4], uint64_t db) {
  asm volatile("wgmma.mma_async.sync.aligned.m64n32k16.f32.bf16.bf16 {%0,%1,%2,%3,%4,%5,%6,%7,%8,%9,%10,%11,%12,%13,%14,%15}, {%16,%17,%18,%19}, %20, %21, 1, 1, %22;"
               : O4(d, 0), O4(d, 4), O4(d, 8), O4(d, 12) : "r"(a[0]), "r"(a[1]), "r"(a[2]), "r"(a[3]), "l"(db), "n"(ACC), "n"(TB));
}
template <int ACC>
__device__ __forceinline__ void wg_rs64(float (&d)[32], uint32_t a0, uint32_t a1, uint32_t a2, uint32_t a3, uint64_t db) {
  asm volatile("wgmma.mma_async.sync.aligned.m64n64k16.f32.bf16.bf16 {%0,%1,%2,%3,%4,%5,%6,%7,%8,%9,%10,%11,%12,%13,%14,%15,"
               "%16,%17,%18,%19,%20,%21,%22,%23,%24,%25,%26,%27,%28,%29,%30,%31}, {%32,%33,%34,%35}, %36, %37, 1, 1, 0;"
               : O4(d, 0), O4(d, 4), O4(d, 8), O4(d, 12), O4(d, 16), O4(d, 20), O4(d, 24), O4(d, 28)
               : "r"(a0), "r"(a1), "r"(a2), "r"(a3), "l"(db), "n"(ACC));
}
template <int ACC>
__device__ __forceinline__ void wg_ss24(float (&d)[12], uint64_t da, uint64_t db) {
  asm volatile("wgmma.mma_async.sync.aligned.m64n24k16.f32.bf16.bf16 {%0,%1,%2,%3,%4,%5,%6,%7,%8,%9,%10,%11}, %12, %13, %14, 1, 1, 1, 0;"
               : O4(d, 0), O4(d, 4), O4(d, 8) : "l"(da), "l"(db), "n"(ACC));
}
template <int ACC>
__device__ __forceinline__ void wg_rs40(float (&d)[20], const uint32_t (&a)[4], uint64_t db) {
  asm volatile("wgmma.mma_async.sync.aligned.m64n40k16.f32.bf16.bf16 {%0,%1,%2,%3,%4,%5,%6,%7,%8,%9,%10,%11,%12,%13,%14,%15,%16,%17,%18,%19}, {%20,%21,%22,%23}, %24, %25, 1, 1, 1;"
               : O4(d, 0), O4(d, 4), O4(d, 8), O4(d, 12), O4(d, 16) : "r"(a[0]), "r"(a[1]), "r"(a[2]), "r"(a[3]), "l"(db), "n"(ACC));
}

struct Row { uint32_t w[8]; };
__device__ __forceinline__ uint32_t add_bf16x2(uint32_t a, uint32_t b) {
  uint32_t d; asm("add.rn.bf16x2 %0, %1, %2;" : "=r"(d) : "r"(a), "r"(b)); return d;
}
__device__ __forceinline__ Row warp_ln(const Row& r, float& extra) {
  float x[16];
#pragma unroll
  for (int i = 0; i < 8; i++) { x[2 * i] = bf_lo(r.w[i]); x[2 * i + 1] = bf_hi(r.w[i]); }
  float m = (((x[0] + x[1]) + (x[2] + x[3])) + ((x[4] + x[5]) + (x[6] + x[7]))) + (((x[8] + x[9]) + (x[10] + x[11])) + ((x[12] + x[13]) + (x[14] + x[15])));
  m *= (1.f / 16);
  float v0 = 0.f, v1 = 0.f;
#pragma unroll
  for (int i = 0; i < 16; i += 2) { const float d0 = x[i] - m, d1 = x[i + 1] - m; v0 = fmaf(d0, d0, v0); v1 = fmaf(d1, d1, v1); }
  float v = v0 + v1;
#pragma unroll
  for (int o = 1; o <= 16; o <<= 1) {
    const float mo = __shfl_xor_sync(~0u, m, o), vo = __shfl_xor_sync(~0u, v, o);
    extra += __shfl_xor_sync(~0u, extra, o);
    const float d = mo - m;
    v = fmaf(d * d, 8.f * o, v + vo);
    m = 0.5f * (m + mo);
  }
  const float var = fmaf(v, 1.f / DM, 1e-5f);
  float rs = rsqrtf(var);
  rs = rs * fmaf(-0.5f * var * rs, rs, 1.5f);
  Row y;
#pragma unroll
  for (int i = 0; i < 8; i++) y.w[i] = pack_bf16((x[2 * i] - m) * rs, (x[2 * i + 1] - m) * rs);
  return y;
}
__device__ __forceinline__ Row warp_ln(const Row& r) { float e = 0.f; return warp_ln(r, e); }
__device__ __forceinline__ Row load_row(const bf16* p, int lane) {
  Row r;
#pragma unroll
  for (int q = 0; q < 4; q++) { const uint2 v = ld_rlx64(p + lane * 4 + q * 128); r.w[2 * q] = v.x; r.w[2 * q + 1] = v.y; }
  return r;
}
__device__ __forceinline__ void store_row_img(uint8_t* img, int rr, int lane, const Row& r) {
  uint8_t* p = img + (lane >> 4) * 4096 + rr * 128 + ((((lane & 15) >> 1) ^ (rr & 7)) << 4) + (lane & 1) * 8;
#pragma unroll
  for (int q = 0; q < 4; q++) *(uint2*)(p + q * 8192) = make_uint2(r.w[2 * q], r.w[2 * q + 1]);
}

constexpr int C_WO = 0;
constexpr int C_X = 49152;
constexpr int C_M = C_X + 65536;
constexpr int C_Q = C_M + 24576;
constexpr int C_K = C_Q + 10240, C_V = C_K + 10240;
constexpr int C_SA = C_V + 10240, C_SB = C_SA + 8192;
constexpr int C_O = C_SB + 8192;
constexpr int C_OT = C_O + 6144;
constexpr int C_PI = C_OT + 16384;
constexpr int C_BAR = C_PI + 8192;
constexpr int C_SMEM = C_BAR + 384 + 1024 + TREXTRA;
constexpr int C_STG = C_X + 32768;
static_assert(C_STG + 131072 <= C_BAR, "staging");
enum { B_M0 = 0, B_M1, B_M2, B_R, B_X = B_R + 4, B_O, B_T, B_F, B_XL, B_U, B_P1, B_P2, B_OT, B_XF, B_XA, B_I, B_PI, B_J, B_W, B_WO, B_NUM };
static_assert(B_NUM <= 24, "barriers");
constexpr int C_POL = C_BAR + 192, C_INFO = C_BAR + 208;
enum { NB_ALL = 0, NB_M0, NB_PV, NB_W0, NB_TA, NB_X1, NB_M1, NB_M2, NB_RD, NB_V, NB_SM, NB_C };
constexpr float SCALE_LOG2E = 0.08838834764831845f * 1.4426950408889634f;
#define N0STEPS 9
#define N2STEPS 12
#define FGATE 1
#define NSSTEPS 0
constexpr int KA = 32 - NSSTEPS - N2STEPS, K3 = KA - N0STEPS;
static_assert(KA % 4 == 0, "the rows of layer 1 are refilled in two parts");
#define BGATE 0
#define W0EARLY 0
#define PVEARLY 1
#define S1GATE 0
#define IGRP 0
#define SHIPLATE 7
#define SHIP 1024
#define GATE_P 2250
#define GATE_W 170
#define EXPF 0
#define GATE_G 200
#define GATE_M 3230
#define HOLE0 22
#define HOLE1 28
#define HOLE2 32
__device__ __forceinline__ uint32_t gtime() { uint32_t t; asm volatile("mov.u32 %0, %%globaltimer_lo;" : "=r"(t) :: "memory"); return t; }
__device__ __forceinline__ void wait_clock(uint32_t t) {
  asm volatile("{ .reg .pred p; .reg .b32 c; .reg .b64 cc;\nL: mov.u64 cc, %%clock64; cvt.u32.u64 c, cc; sub.u32 c, c, %0; setp.lt.s32 p, c, 0; @p bra L; }" ::"r"(t) : "memory");
}
__device__ __forceinline__ void bar_sync_z(int id, int n, uint32_t z) {
  asm volatile("{ .reg .pred p; setp.eq.u32 p, %2, 0; @p bar.sync %0, %1; }" ::"r"(id), "r"(n), "r"(z) : "memory");
}

__device__ __forceinline__ int probe_home(uint32_t* p, int lane) {
  uint32_t best[2] = {~0u, ~0u};
#pragma unroll 1
  for (int rep = 0; rep < 5; rep++) {
#pragma unroll
    for (int pg = 0; pg < 2; pg++) {
      uint32_t t0, t1, v = 0;
      asm volatile("mov.u32 %0, %%clock;" : "=r"(t0) :: "memory");
      asm volatile("{ .reg .pred p; setp.eq.u32 p, %2, 0; @p atom.relaxed.gpu.global.exch.b32 %0, [%1], %3; }" : "+r"(v) : "l"(p + pg * 1024), "r"(lane), "r"(rep) : "memory");
      asm volatile("{ .reg .pred p; setp.ne.u32 p, %1, 0x13572468; mov.u32 %0, 0; @p mov.u32 %0, %%clock; }" : "=r"(t1) : "r"(v) : "memory");
      best[pg] = min(best[pg], t1 - t0);
    }
  }
  return __shfl_sync(~0u, max(-150, min(150, (int)(best[1] - best[0]))), 0);
}
__device__ __forceinline__ uint32_t home_flip(const void* p) { const uint32_t a = (uint32_t)(size_t)p; return ((a >> 16) ^ (a >> 17) ^ (a >> 19)) & 1; }
__device__ __forceinline__ uint32_t ppage(uint32_t lp, uint32_t pol) { return lp ? 3 - pol : pol; }
__device__ __forceinline__ uint32_t and_x(uint32_t a, uint32_t b, uint32_t m) {
  uint32_t d; asm("lop3.b32 %0, %1, %2, %3, 0x42;" : "=r"(d) : "r"(a), "r"(b), "r"(m)); return d;
}
__device__ __forceinline__ uint32_t and3(uint32_t a, uint32_t b, uint32_t c) {
  uint32_t d; asm("lop3.b32 %0, %1, %2, %3, 0x80;" : "=r"(d) : "r"(a), "r"(b), "r"(c)); return d;
}

template <int N> struct IC { static constexpr int value = N; };
template <class F> __device__ __forceinline__ void static_for2(F f) { f(IC<0>()); f(IC<1>()); }
template <class F> __device__ __forceinline__ void static_for3(F f) { f(IC<0>()); f(IC<1>()); f(IC<2>()); }
__device__ __forceinline__ void stage_weights(uint32_t stage, const CUtensorMap* map, int col, int row, uint32_t mbar) {
  mbar_expect_tx(mbar, 131072);
#pragma unroll 1
  for (int i = 0; i < 4; i++)
    asm volatile("cp.async.bulk.tensor.2d.shared::cluster.global.mbarrier::complete_tx::bytes [%0], [%1, {%3, %4}], [%2];"
                 ::"r"(stage + (i & 1) * 65536 + (i >> 1) * 32768), "l"(map), "r"(mbar), "r"(col + (i & 1) * 64), "r"(row + (i >> 1) * 256) : "memory");
}
__device__ __forceinline__ void load_wfrags(uint32_t (&wA)[32][4], uint32_t stage, int w, int lane) {
  const int mi = lane >> 3, r = lane & 7;
  const uint32_t a = stage + (w >> 2) * 65536 + ((mi >> 1) * 8 + r) * 128 + ((((w & 3) * 2 + (mi & 1)) ^ r) << 4);
#pragma unroll
  for (int ks = 0; ks < 32; ks++) ldsm4t(wA[ks], a + ks * 2048);
}
template <int K0, int K1>
__device__ __forceinline__ void tok_seq(float (&d)[16], const uint32_t (&wA)[32][4], uint64_t desc, uint32_t wave) {
#pragma unroll
  for (int k = K0; k < K1; k++) {
    const int ks = k & 31;
    constexpr int HM0 = 1, HM1 = 2, HM2 = 4;
    const int hm = (k == HOLE0 ? HM0 : 0) | (k == HOLE1 ? HM1 : 0) | (k == HOLE2 ? HM2 : 0);
    if (hm) bar_sync_z(NB_RD, 384, ((hm >> wave) & 1) ^ 1);
    if (ks == 0) wg_rs32<0, 0>(d, wA[ks], desc);
    else wg_rs32<0, 1>(d, wA[ks], desc + (ks >> 2) * 256 + (ks & 3) * 2);
  }
}
template <int K0, int K1>
__device__ __forceinline__ void mem_part(float (&d)[12], const uint32_t (&wA)[32][4], uint64_t desc) {
#pragma unroll
  for (int ks = K0; ks < K1; ks++) {
    if (ks == 0) wg_rs24<1, 0>(d, wA[ks], desc);
    else wg_rs24<1, 1>(d, wA[ks], desc + ks * 48);
  }
}
__device__ __forceinline__ void out_tile(float (&d)[12], uint64_t da, uint64_t db) {
#pragma unroll
  for (int i = 0; i < 8; i++) { if (i == 0) wg_ss24<0>(d, da, db); else wg_ss24<1>(d, da + i * 128, db + (i >> 1) * 32 + (i & 1) * 2); }
}
__device__ __forceinline__ void tok_pack(uint32_t (&p)[8], const float (&d)[16]) {
#pragma unroll
  for (int i = 0; i < 8; i++) p[i] = pack_bf16(d[2 * i], d[2 * i + 1]);
}
__device__ __forceinline__ void tok_store(uint32_t dst, const uint32_t (&p)[8]) {
  stsm4(dst, p[0], p[1], p[2], p[3]);
  stsm4(dst + 4096, p[4], p[5], p[6], p[7]);
}
template <class T> __device__ __forceinline__ T keep(T v) { asm volatile("" : "+r"(v)); return v; }
__device__ __forceinline__ uint32_t pin(uint32_t v) { return __shfl_sync(~0u, v, threadIdx.x & 31); }

#define TRC blockIdx.x
#define TRS (C_BAR + 384)
__device__ __forceinline__ void chain_proj(const uint32_t sb, const int w, const int lane_, const uint32_t rank) {
  uint32_t wA[32][4];
  mbar_wait(sb + C_BAR + B_W * 8, 0, 30);
  if (w == 0) { HD(2) }
  load_wfrags(wA, sb + C_STG, w, lane_);
  bar_arrive(NB_ALL, 384);
  const int lane = pin(lane_);
  const uint32_t bars = sb + C_BAR;
  const uint32_t quad = pin(sb + (lane_ >> 4) * 2048 + (lane_ & 15) * 16);
  const uint32_t own = C_Q + rank * 10240;
  const uint64_t dX1 = mk_desc(sb + C_X, 16, 1024, 1), dX2 = dX1 + 2048;
  const uint64_t dM = mk_desc(sb + C_M, 128, 256, 0);
  const uint32_t r1 = rank == 0 ? 1 : 0, r2 = rank == 2 ? 1 : 2;
  const uint32_t xa = pin(sb + own + 8192 + w * 256 + lane_ * 4);
  const uint32_t a1x = pin(mapa_u32(xa, r1)), a2x = pin(mapa_u32(xa, r2));
  const uint32_t b1x = pin(mapa_u32(bars + B_X * 8, r1)), b2x = pin(mapa_u32(bars + B_X * 8, r2));
  const uint32_t wave = rank == 2 ? 0 : rank + 1;
  float a[16];
  bar_sync(NB_X1, 288);
  wg_fence();
  tok_seq<32, 32 + KA>(a, wA, mk_desc(__shfl_sync(~0u, sb, 0) + C_X, 16, 1024, 1), 3);
  wg_commit();
  wg_wait<0>();
  mbar_arrive_z(bars + B_XA * 8, lane);
#pragma unroll 1
  for (int st = 0;; st++) {
    uint32_t pk[8];
    wg_fence();
    if (NSSTEPS) bar_sync(NB_SM, 416);
    tok_seq<32 + KA, 32 + KA + NSSTEPS>(a, wA, dX1, 3);
    bar_sync(NB_PV, NSSTEPS ? 384 : 416);
    tok_seq<32 + KA + NSSTEPS, 64>(a, wA, dX1, 3);
    wg_commit();
    wg_wait<0>();
    acc_fence(a);
    mbar_arrive_z(bars + B_XF * 8, lane);
    tok_pack(pk, a);
    TR(1)
    bar_sync(NB_W0, 416);
    tok_store(quad + w * 256 + (rank == 0 ? own : C_SA), pk);
    __syncwarp();
    mbar_arrive_z(bars + B_P1 * 8, lane);
    wg_fence();
    tok_seq<0, 32>(a, wA, dX2, wave);
    wg_commit();
    const uint32_t info = lds32(sb + C_INFO + (st & 1) * 4);
    TR(2)
    wg_wait<0>();
    acc_fence(a);
    TR(3)
    tok_pack(pk, a);
    tok_store(quad + w * 256 + (rank == 0 ? C_SA : own), pk);
    if (rank == 2) tok_store(quad + w * 256 + C_SB, pk);
    __syncwarp();
    mbar_arrive_z(bars + B_P2 * 8, lane);
    TR(4)
    wg_fence();
    tok_seq<32, 32 + K3>(a, wA, dX1, wave);
    TR(6)
    {
      float am[12];
      bar_sync(NB_M0, 384);
      mem_part<0, 10>(am, wA, dM);
      TR(7)
      bar_sync(NB_M1, 384);
      mem_part<10, 21>(am, wA, dM);
      bar_sync(NB_M2, 384);
      mem_part<21, 32>(am, wA, dM);
      wg_commit();
      bar_sync(NB_V, 384);
      const bool redo = __any_sync(~0u, lds32(sb + C_INFO + 16 + (lane & 3) * 32) != 0);
      if (__builtin_expect(redo, 0)) {
        wg_wait<0>();
        wg_fence();
        mem_part<0, 32>(am, wA, dM);
        wg_commit();
      }
      wg_wait<0>();
      acc_fence(am);
      TR(8)
      const uint32_t x00 = pack_bf16(am[0], am[1]), x01 = pack_bf16(am[2], am[3]), x10 = pack_bf16(am[4], am[5]), x11 = pack_bf16(am[6], am[7]);
      const uint32_t y0 = pack_bf16(am[8], am[9]), y1 = pack_bf16(am[10], am[11]), x20 = info ? x10 : y0, x21 = info ? x11 : y1;
      st_async32<0>(a1x, rank == 0 ? x10 : x00, b1x); st_async32<0>(a2x, rank == 2 ? x10 : x20, b2x);
      st_async32<128>(a1x, rank == 0 ? x11 : x01, b1x); st_async32<128>(a2x, rank == 2 ? x11 : x21, b2x);
      sts32(xa, rank == 0 ? x00 : rank == 2 ? x20 : x10); sts32(xa + 128, rank == 0 ? x01 : rank == 2 ? x21 : x11);
      if (__builtin_expect(info, 0)) {
        const uint32_t o = (info & 3) * 2048 - 8192;
        if (rank == 2) { sts32(xa + o, y0); sts32(xa + o + 128, y1); }
        else { st_async32<0>(a2x + o, y0, b2x + (B_T - B_X) * 8); st_async32<128>(a2x + o, y1, b2x + (B_T - B_X) * 8); }
      }
      __syncwarp();
      mbar_arrive_z(bars + B_X * 8, lane);
    }
    TR(9)
    wg_fence();
    tok_seq<32 + K3, 32 + KA>(a, wA, dX1, 3);
    wg_commit();
    TR(0)
    wg_wait<0>();
    if (st == NSTEP - 1) break;
    mbar_arrive_z(bars + B_XA * 8, lane);
  }
  if (NSSTEPS) bar_arrive(NB_SM, 416);
  bar_arrive(NB_PV, NSSTEPS ? 384 : 416);
}

__device__ __forceinline__ void chain_mem(const uint32_t sb, const int w, const int lane_, const uint32_t rank, const int h,
                                          const bf16* __restrict__ mem0) {
  const int lane = pin(lane_);
  const int wave = rank == 2 ? 0 : rank + 1;
  const int c = w - 8, t = c * 32 + lane, b = wave * 32 + h;
  const uint32_t bars = sb + C_BAR;
  const int wi = (lane & 1) * 2 + (lane >> 4), cq = (lane >> 2) & 3;
  mbar_expect_tx_z(bars + B_X * 8, 4096, t); mbar_expect_tx_z(bars + B_O * 8, 4096, t);
  if (NSSTEPS) bar_arrive(NB_SM, 416);
  bar_arrive(NB_PV, NSSTEPS ? 384 : 416); bar_arrive(NB_W0, 416); bar_arrive(NB_RD, 384);
  uint32_t m0[16];
#pragma unroll
  for (int i = 0; i < 16; i++) m0[i] = *(const uint32_t*)(mem0 + (lane >> 2) * DM + (c * 16 + i) * 8 + (lane & 3) * 2);
  {
    uint32_t* p = g_M + c * 16384 + 14 * 1024 + (blockIdx.x & 31) * 32;
    const int vote = probe_home(p, lane);
    sts32(sb + C_POL + c * 4, home_flip(p) ? -vote : vote);
    bar_sync(NB_C, 128);
    const uint4 v = lds128(sb + C_POL);
    const uint32_t side = (int)(v.x + v.y + v.z + v.w) > 0;
    bar_sync(NB_C, 128);
    sts32(sb + C_POL + c * 4, side ^ home_flip(p));
    sts32(sb + C_INFO + 8, side ^ home_flip(g_P + b * 4096));
    if (c == 0) { HD(0) }
    wait_count(g_ex.ready, NWORK, 35);
    if (c == 0) { HD(1) }
    st_rlx32(&g_fl.pol[b], (side ^ home_flip(g_P + b * 4096)) + 1);
  }
  bar_sync(NB_ALL, 384);
  if (c == 0) { HD(3) }
  mbar_arrive_remote_z(mapa_u32(bars + B_F * 8, (rank + 1 + (t & 1)) % 3), t >> 1);
#pragma unroll
  for (int i = 0; i < 16; i += 4) {
    const uint32_t a = sb + C_M + (c * 8 + i / 2 + (lane >> 4)) * 768 + (lane & 15) * 16;
    stsm4t(a, m0[i], m0[i + 1], m0[i + 2], m0[i + 3]); stsm4t(a + 256, m0[i], m0[i + 1], m0[i + 2], m0[i + 3]); stsm4t(a + 512, m0[i], m0[i + 1], m0[i + 2], m0[i + 3]);
  }
  sts32(sb + C_INFO + 16 + c * 32, 0);
  fence_async_smem();
  bar_arrive(NB_M0, 384); bar_arrive(NB_M1, 384); bar_arrive(NB_M2, 384);
  mbar_wait(bars + B_F * 8, 0, 34);
  bar_arrive(NB_V, 384);
  mbar_wait(bars + B_WO * 8, 0, 33);
  uint32_t pgbits, polP;
  {
    const int tl = lane / 3, u = ((tl * 3 + rank) * 4 + c) * 3 + (lane - tl * 3);
    uint32_t pol;
    int it = 0;
    do { pol = ld_rlx32(&g_fl.pol[lane < 9 && u < 96 ? u : b]); give_up(it++, SPIN_LIMIT, 40); } while (__any_sync(~0u, pol == 0));
    pgbits = __reduce_or_sync(~0u, lane < 9 ? ppage(h >> 4, (pol - 1) & 1) << (2 * lane) : 0u);
    polP = __shfl_sync(~0u, pol - 1, 9);
  }
  const int mi = lane >> 3;
  const uint32_t l16 = pin(sb + lane * 16);
  const uint32_t r1 = rank == 2 ? 0 : rank + 1, r2 = rank == 0 ? 2 : rank - 1;
  const uint32_t oa = pin(sb + C_O + rank * 2048 + (lane >> 2) * 64 + (((lane & 3) ^ (lane >> 3)) << 4));
  const uint32_t a1 = mapa_u32(oa, r1), b1 = mapa_u32(bars + B_O * 8, r1), a2 = mapa_u32(oa, r2), b2 = mapa_u32(bars + B_O * 8, r2);
  const uint64_t dWo = mk_desc(sb + C_WO, 8192, 1024, 1), dO = mk_desc(sb + C_O, 16, 2048, 2);
  const uint64_t dK = mk_desc(sb + C_K, 128, 2048, 0);
  const uint64_t dV = mk_desc(sb + C_V, 2048, 128, 0), dVm = mk_desc(sb + C_V + 8192, 0, 128, 0);
  const uint32_t qa = pin(sb + C_Q + (c ? c + 1 : mi & 1) * 2048 + (mi >> 1) * 128 + (lane & 7) * 16);
  const uint32_t dg = ((lane >> 2) < 2 * (lane & 3) ? 1 : 0) | ((lane >> 2) < 2 * (lane & 3) + 1 ? 2 : 0);
  const uint32_t msk = pin(c == 0 ? dg | dg << 4 : c == 1 ? dg << 2 | 3 << 4 : c == 2 ? dg << 4 : 0);
  uint8_t* Pw = (uint8_t*)g_P + (rank * 4 + c) * 3 * 16384 + (h & 15) * 256 + ((lane * 4) ^ ((h & 3) << 5));
  const uint32_t pia = pin(sb + C_PI + ((lane >> 4) * 4 + (lane & 3)) * 256 + ((c * 64 + cq * 16) ^ ((lane & 3) << 5)));
  uint8_t* Mw = (uint8_t*)g_M + (b >> 5) * 16384 + ((lane & 2) ? 4096 : 12288) + (b & 31) * 256 + c * 64 + cq * 16 + wi * 4;
  uint32_t nretry = 0, nupd = 0;

  { const int st = 71; (void)st; STAT(0, lds32(sb + C_POL + c * 4)) STAT(1, polP) STAT(2, (uint32_t)(size_t)(g_M + c * 16384)) STAT(3, (uint32_t)(size_t)(g_P + b * 4096)) }
#pragma unroll 1
  for (int st = 0;; st++) {
    mbar_wait(bars + B_P1 * 8, st & 1, 38);
    mbar_wait(bars + B_T * 8, st & 1, 42);
    STAT(10, clk32())
    {
      float s[20];
      {
        uint32_t q[8][4];
        if (c == 3) mbar_wait(bars + B_X * 8, st & 1, 41);
#pragma unroll
        for (int i = 0; i < 8; i++) ldsm4t(q[i], qa + i * 256);
        if (c != 3) { mbar_wait(bars + B_X * 8, st & 1, 41); fence_async_smem(); }
        STAT(11, clk32())
        TR(0)
        wg_fence();
#pragma unroll
        for (int i = 0; i < 8; i++) { if (i == 0) wg_rs40<0>(s, q[i], dK); else wg_rs40<1>(s, q[i], dK + i * 16); }
        wg_commit();
        wg_wait<0>();
        if (NSSTEPS) bar_arrive(NB_SM, 416);
        acc_fence(s);
      }
      TR(1)
      const bool w0 = c == 0;
      float z[10] = {s[16], s[17], s[0], s[1], w0 ? s[18] : s[4], w0 ? s[19] : s[5], w0 ? s[2] : s[8], w0 ? s[3] : s[9], w0 ? s[6] : s[12], w0 ? s[7] : s[13]};
      if (msk & 1) z[2] = -INFINITY;
      if (msk & 2) z[3] = -INFINITY;
      if (msk & 4) z[6] = -INFINITY;
      if (msk & 8) z[7] = -INFINITY;
      if (msk & 16) z[8] = -INFINITY;
      if (msk & 32) z[9] = -INFINITY;
      float m0 = fmaxf(fmaxf(z[0], z[1]), fmaxf(z[2], z[3])), m1 = fmaxf(fmaxf(fmaxf(z[4], z[5]), fmaxf(z[6], z[7])), fmaxf(z[8], z[9]));
      m0 = fmaxf(m0, __shfl_xor_sync(~0u, m0, 1)); m1 = fmaxf(m1, __shfl_xor_sync(~0u, m1, 1));
      m0 = fmaxf(m0, __shfl_xor_sync(~0u, m0, 2)); m1 = fmaxf(m1, __shfl_xor_sync(~0u, m1, 2));
      if (!w0) m0 = m1 = fmaxf(m0, m1);
      m0 *= -SCALE_LOG2E; m1 *= -SCALE_LOG2E;
      uint32_t p[5];
#pragma unroll
      for (int k = 0; k < 5; k++) {
        z[2 * k] = ex2_fast(fmaf(z[2 * k], SCALE_LOG2E, k < 2 ? m0 : m1)); z[2 * k + 1] = ex2_fast(fmaf(z[2 * k + 1], SCALE_LOG2E, k < 2 ? m0 : m1));
        p[k] = pack_bf16(z[2 * k], z[2 * k + 1]);
      }
      const uint32_t p2 = w0 ? 0 : p[2], p3 = w0 ? 0 : p[3], p4 = w0 ? 0 : p[4];
      float oA[32], oB[32];
      wg_fence();
      wg_rs64<0>(oA, p[0], p[2], 0, 0, dVm); wg_rs64<1>(oA, p[1], p[3], p2, p[4], dV); wg_rs64<1>(oA, p3, 0, p4, 0, dV + 256);
      wg_commit();
      wg_rs64<0>(oB, p[0], p[2], 0, 0, dVm + 64); wg_rs64<1>(oB, p[1], p[3], p2, p[4], dV + 64); wg_rs64<1>(oB, p3, 0, p4, 0, dV + 320);
      wg_commit();
      float l0 = (z[0] + z[1]) + (z[2] + z[3]), l1 = ((z[4] + z[5]) + (z[6] + z[7])) + (z[8] + z[9]);
      if (!w0) l0 += l1;
      l0 += __shfl_xor_sync(~0u, l0, 1); l1 += __shfl_xor_sync(~0u, l1, 1);
      l0 += __shfl_xor_sync(~0u, l0, 2); l1 += __shfl_xor_sync(~0u, l1, 2);
      float i0, i1;
      asm volatile("rcp.approx.ftz.f32 %0, %2; rcp.approx.ftz.f32 %1, %3;" : "=f"(i0), "=f"(i1) : "f"(l0), "f"(l1));
      asm volatile("st.shared.v2.f32 [%0], {%1,%2};" ::"r"(sb + C_INFO + 24), "f"(i0), "f"(i1) : "memory");
      const uint32_t ta = l16 + C_OT + (st & 1) * 8192 + (c ? c + 1 : 0) * 2048;
      auto leave = [&](const float (&o)[32], auto hc) {
        constexpr int H = decltype(hc)::value;
        uint32_t e[8];
#pragma unroll
        for (int j = 0; j < 8; j++) e[j] = pack_bf16(o[4 * j] * i0, o[4 * j + 1] * i0);
        if (c == 3) {
          static_for2([&](auto bc) {
            constexpr int B = decltype(bc)::value;
            asm volatile("st.async.weak.shared::cluster.mbarrier::complete_tx::bytes.v4.b32 [%0 + %9], {%5,%6,%7,%8}, [%1];\n"
                         "st.async.weak.shared::cluster.mbarrier::complete_tx::bytes.v4.b32 [%2 + %9], {%5,%6,%7,%8}, [%3];\n"
                         "st.shared.v4.b32 [%4 + %9], {%5,%6,%7,%8};"
                         ::"r"(a1), "r"(b1), "r"(a2), "r"(b2), "r"(oa), "r"(e[4 * B]), "r"(e[4 * B + 1]), "r"(e[4 * B + 2]), "r"(e[4 * B + 3]),
                           "n"(H * 1024 + B * 512) : "memory");
          });
        } else {
          stsm4(ta + H * 1024, e[0], e[1], e[2], e[3]); stsm4(ta + H * 1024 + 512, e[4], e[5], e[6], e[7]);
          if (w0) {
#pragma unroll
            for (int j = 0; j < 8; j++) e[j] = pack_bf16(o[4 * j + 2] * i1, o[4 * j + 3] * i1);
            stsm4(ta + 2048 + H * 1024, e[0], e[1], e[2], e[3]); stsm4(ta + 2048 + H * 1024 + 512, e[4], e[5], e[6], e[7]);
          }
        }
      };
      wg_wait<1>();
      acc_fence(oA);
      leave(oA, IC<0>());
      wg_wait<0>();
      if (PVEARLY) bar_arrive(NB_PV, NSSTEPS ? 384 : 416);
      acc_fence(oB);
      leave(oB, IC<1>());
      if (!PVEARLY) bar_arrive(NB_PV, NSSTEPS ? 384 : 416);
      __syncwarp();
      mbar_arrive_z(bars + (c == 3 ? B_O : B_OT) * 8, lane);
      TR(2)
    }
    mbar_wait(bars + B_O * 8, st & 1, 43);
    if (st == NSTEP - 1) break;
    uint32_t info;
    {
      const uint32_t tag = (st & 1) ^ 1;
      float oc0[12], oc1[12], oc2[12];
      fence_async_smem();
      TR(3)
      wg_fence();
      out_tile(oc0, dWo, dO);
      wg_commit();
      out_tile(oc1, dWo + 1024, dO);
      wg_commit();
      asm volatile("" : "+r"(pgbits));
      auto put = [&](const float (&oc)[12], auto tlc) {
        constexpr int TL = decltype(tlc)::value;
        static_for3([&](auto jc) {
          constexpr int j = decltype(jc)::value;
          uint8_t* p = Pw + ((pgbits >> (2 * (TL * 3 + j))) & 3) * 4096;
          asm volatile("st.relaxed.gpu.global.u32 [%0 + %3], %1; st.relaxed.gpu.global.u32 [%0 + %3 + 128], %2;" ::"l"(p),
                       "r"((pack_bf16(oc[4 * j], oc[4 * j + 1]) & ~1u) | tag), "r"((pack_bf16(oc[4 * j + 2], oc[4 * j + 3]) & ~1u) | tag),
                       "n"((TL * 36 + j) * 16384) : "memory");
        });
      };
      wg_wait<1>();
      acc_fence(oc0);
      put(oc0, IC<0>());
      sts32(sb + C_INFO + 24, clk32());
      TR(4)
      out_tile(oc2, dWo + 2048, dO);
      wg_commit();
      wg_wait<1>();
      acc_fence(oc1);
      put(oc1, IC<1>());
      if (W0EARLY) bar_arrive(NB_W0, 416);
      bar_sync(NB_TA, 192);
      TR(5)
      wg_wait<0>();
      if (!W0EARLY) bar_arrive(NB_W0, 416);
      info = lds32(sb + C_INFO + ((st + 1) & 1) * 4);
      acc_fence(oc2);
      if (rank != 2) put(oc2, IC<2>());
      mbar_arrive_remote_z(((t & 1) ? b2 : b1) + (B_F - B_O) * 8, t >> 1);
      mbar_expect_tx_z(bars + ((t & 1) ? B_O : B_X) * 8, 4096, t >> 1);
      TR(6)
    }
    const int sn = (st + 1) & 3;
    uint8_t* mw = Mw + sn * 65536;
    asm volatile("" : "+l"(mw));
    if (__builtin_expect((st < DELTA && b % 3 != 0) || (info && b % 3 == 2), 0)) {
      bar_arrive(NB_RD, 384);
      const int col = b / 3 * 16 + c * 4 + ((lane >> 2) & 3), r0 = (lane & 1) * 4 + (lane >> 4) * 2;
      const bool upd = info && b % 3 == 2;
      if (upd) mbar_wait(bars + B_U * 8, nupd & 1, 39);
      uint32_t hv[2];
#pragma unroll
      for (int i = 0; i < 2; i++) {
        const int r = r0 + i, sg = st + 1 - DELTA;
        const void* p = !upd ? (const void*)(mem0 + r * DM + col) : r == (int)(info >> 4) ? (const void*)(g_x2p[sg][1] + col)
                      : (const void*)(g_xs[1] + sg * 32768 + (col >> 6) * 4096 + ((info & 3) * 8 + r) * 128 + ((((col >> 3) ^ r) & 7) << 4) + (col & 7) * 2);
        asm volatile("ld.relaxed.gpu.global.u16 %0, [%1];" : "=r"(hv[i]) : "l"(p) : "memory");
      }
      st_rlx32(mw, hv[0] | hv[1] << 16);
      STAT(1, 0) STAT(2, 0) STAT(4, 0)
    } else {
      const uint32_t flip = (st & 1) ? ~0u : 0u;
      const bool u16 = lane & 16;
      const uint32_t bs = (lane & 4) ? 0x3f800000u : 0x00003f80u, bs0 = (lane & 8) ? 0u : bs, bs1 = (lane & 8) ? bs : 0u;
      STATC(c_rdy)
      mbar_wait(bars + B_PI * 8, st & 1, 37);
      TR(7)
      uint4 q0 = lds128(pia), q1 = lds128(pia + 2048), q2 = lds128(pia + 4096), q3 = lds128(pia + 6144);
      int it = 0;
#pragma unroll 1
      while (true) {
        float d0[4] = {0.f, 0.f, 0.f, 0.f}, d1[4] = {0.f, 0.f, 0.f, 0.f};
        mma16816(d0, q0.x, q0.y, q0.z, q0.w, bs0, bs1);
        mma16816(d1, q1.x, q1.y, q1.z, q1.w, bs0, bs1);
        mma16816(d0, q2.x, q2.y, q2.z, q2.w, bs0, bs1);
        mma16816(d1, q3.x, q3.y, q3.z, q3.w, bs0, bs1);
        const bool all = __all_sync(~0u, (int)and3(and_x(q0.x, q1.x, flip), and_x(q2.x, q3.x, flip), 1u));
        const float a0 = d0[0] + d1[0], a1 = d0[1] + d1[1], a2 = d0[2] + d1[2], a3 = d0[3] + d1[3];
        asm volatile("{ .reg .pred p; setp.ne.u32 p, %0, 0; @p bar.arrive %1, 384; }" ::"r"((uint32_t)all), "n"((int)NB_RD) : "memory");
        const uint32_t mword = pack_bf16((u16 ? a2 : a0) + __shfl_xor_sync(~0u, u16 ? a0 : a2, 16), (u16 ? a3 : a1) + __shfl_xor_sync(~0u, u16 ? a1 : a3, 16));
        asm volatile("{ .reg .pred p; setp.ne.u32 p, %2, 0; @p st.relaxed.gpu.global.u32 [%0], %1; }" ::"l"(mw), "r"(mword), "r"((uint32_t)all) : "memory");
        if (__builtin_expect(all, 1)) break;
        give_up(++it, SPIN_LIMIT, 44);
        const uint8_t* Pr0 = (const uint8_t*)g_P + b * 16384 + (pia - sb - C_PI) + polP * 4096;
        const uint8_t* Pr1 = Pr0 + (3 - 2 * polP) * 4096;
        q0 = ld_rlx128(Pr0); q1 = ld_rlx128(Pr0 + 2048); q2 = ld_rlx128(Pr1); q3 = ld_rlx128(Pr1 + 2048);
      }
      STATC(c_mst)
      STAT(1, c_rdy - tref) STAT(2, c_mst - tref) STAT(4, it)
      TRV(14, it)
    }
    STAT(0, lds32(sb + C_INFO + 24) - tref) STAT(3, tref)
    nupd += info != 0;
    TR(9)
    {
      const uint32_t ma = l16 + C_M + c * 2048 + mi * 4;
      auto scan = [&](uint32_t m, uint32_t a) { return __vimax3_u32(__vimax3_u32(m, lds32(a), lds32(a + 512)), lds32(a + 1024), lds32(a + 1536)); };
      mbar_wait(bars + B_M0 * 8, (st + 1) & 1, 45);
      bar_arrive(NB_M0, 384);
      STATC(c_g0)
      TR(10)
      uint32_t m = scan(0, ma);
      mbar_wait(bars + B_M1 * 8, (st + 1) & 1, 46);
      bar_arrive(NB_M1, 384);
      STATC(c_g1)
      TR(11)
      m = scan(m, ma + 8192);
      mbar_wait(bars + B_M2 * 8, (st + 1) & 1, 47);
      STATC(c_g2)
      TR(12)
      int it = 0;
      bar_arrive(NB_M2, 384);
      const bool redo = __any_sync(~0u, scan(m, ma + 16384) == ~0u);
      sts32(sb + C_INFO + 16 + c * 32, redo);
      if (__builtin_expect(redo, 0)) {
#pragma unroll 1
        for (int g = 0; g < 3;) {
          if (!__any_sync(~0u, scan(0, ma + g * 8192) == ~0u)) { g++; continue; }
          give_up(++it, SPIN_LIMIT, 48);
          if (lane == 0) {
            mbar_expect_tx(bars + (B_R + c) * 8, 2048);
            bulk_g2s(sb + C_M + g * 8192 + c * 2048, (const uint8_t*)g_M + sn * 65536 + (lds32(sb + C_POL + sn * 4) ? 4096 : 12288) + g * 16384 + c * 2048,
                     2048, bars + (B_R + c) * 8);
          }
          __syncwarp();
          mbar_wait(bars + (B_R + c) * 8, nretry++ & 1, 49);
        }
      }
      bar_arrive(NB_V, 384);
      STAT(5, c_g0 - tref) STAT(7, c_g1 - tref) STAT(8, c_g2 - tref)
      STAT(9, clk32() - tref) STAT(6, it + redo * 256)
      TR(13)
      TRV(15, it)
      st_rlx32(Mw + (st & 3) * 65536, ~0u);
    }
  }
}

__device__ __forceinline__ void chain_dma(const uint32_t sb, const int w, const int lane, const uint32_t rank, const int h) {
  const uint32_t bars = sb + C_BAR;
  const int expf_ = EXPF;
  if (w == 12) {
    u64 best = 0;
    uint32_t nx = 0;
    auto load = [&](uint32_t dst, const uint8_t* src, uint32_t bytes) {
      mbar_expect_tx_z(bars + B_XL * 8, bytes, lane >> 1);
      if (lane < 2 && bytes) {
        fence_async_glb();
        bulk_g2s(sb + dst, src, bytes, bars + B_XL * 8);
      }
      __syncwarp();
      mbar_wait(bars + B_XL * 8, nx++ & 1, 52);
    };
    wait_count(g_ex.ready, NWORK, 59);
    load(C_X + lane * 16384, g_xs[0] + lane * 16384, 16384);
    HD(6)
    bar_arrive(NB_X1, 288); bar_arrive(NSSTEPS ? NB_SM : NB_PV, 416);
#pragma unroll 1
    for (int st = 0; st < NSTEP; st++) {
      const int sg = st - DELTA;
      const bool more = st + 1 < NSEG && !(expf_ & 4);
      uint32_t info = 0;
      if (sg >= 0) {
        const u64 k = wait_keys(g_fl.key[0][sg], lane, 50);
        if (k > best) { best = k; info = 4 | ((key_token(k) >> 3) & 3) | (key_token(k) & 7) << 4; }
      }
      TR(0)
      mbar_wait(bars + B_XA * 8, st & 1, 58);
      sts32(sb + C_INFO + (st & 1) * 4, info);
      if (st > 0) bar_arrive(NB_TA, 192);
      TR(1)
      load(lane ? C_X : C_X + 32768, lane ? g_xs[0] + (st + 1) * 32768 : g_xs[1] + sg * 32768, lane ? (more ? KA * 1024 : 0) : (sg >= 0 && !(expf_ & 8) ? 32768 : 0));
      bar_arrive(NB_W0, 416);
      TR(2)
      if (__builtin_expect(info, 0)) {
        int it = 0;
        while (ld_rlx32(g_fl.patch[sg]) == 0) { give_up(++it, SPIN_LIMIT, 56); warp_sleep(250); }
        mbar_arrive_z(bars + B_U * 8, lane);
      }
      mbar_wait(bars + B_XF * 8, st & 1, 53);
      mbar_wait(bars + (B_M0 + BGATE) * 8, st & 1, 54);
      load(C_X + KA * 1024, g_xs[0] + (st + 1) * 32768 + KA * 1024, more && lane == 0 ? 32768 - KA * 1024 : 0);
      TR(3)
      bar_arrive(NSSTEPS ? NB_SM : NB_PV, 416);
    }
  } else if (w == 13) {
    constexpr uint32_t NP = 8192 / SHIP;
    const uint32_t o = (lane >> 1) * SHIP, own = sb + C_Q + rank * 10240, bt = bars + B_T * 8;
    const uint32_t d2 = 1 + (lane & 1);
    const uint32_t src2 = (rank == 0 ? sb + C_SA : rank == 1 ? own : sb + C_SB) + o;
    const uint32_t skip = (lane & 1) ? 4 | (o >> 11) : 8;
#pragma unroll 1
    for (int st = 0; st < NSTEP; st++) {
      mbar_wait(bars + B_P1 * 8, st & 1, 61);
      fence_async_smem();
      mbar_wait(bars + B_F * 8, st & 1, 60);
      if (st > 0) mbar_wait(bars + (S1GATE ? B_PI : B_J) * 8, (st - 1) & 1, 65);
      const uint32_t info = lds32(sb + C_INFO + (st & 1) * 4);
      TR(2)
      if (st < NSEG && rank != 0 && lane < 2 * NP && d2 == 1 && !(expf_ & 1)) bulk_s2r(mapa_u32(own + o, 0), sb + C_SA + o, SHIP, mapa_u32(bt, 0));
      __syncwarp();
      TR(3)
      mbar_wait(bars + B_P2 * 8, st & 1, 62);
      fence_async_smem();
      if (st > 0 && (SHIPLATE >> rank & 1)) mbar_wait(bars + B_I * 8, (st - 1) & 1, 64);
      TR(0)
      if (st >= DELTA && lane < 2 * NP && d2 != rank && (info & 7) != skip && !(expf_ & 2)) bulk_s2r(mapa_u32(own + o, d2), src2, SHIP, mapa_u32(bt, d2));
      __syncwarp();
      TR(1)
    }
  } else if (w == 14) {
    const int s0 = rank == 0 ? 0 : DELTA;
    const uint32_t tbytes = (expf_ & (rank ? 2 : 1)) ? 0 : 16384;
    mbar_expect_tx_z(bars + B_T * 8, s0 == 0 ? tbytes : 0, lane);
#pragma unroll 1
    for (int st = 0; st < NSTEP; st++) {
      const int sg = st - s0;
      const bool act = (unsigned)sg < (unsigned)NSEG;
      mbar_wait(bars + B_OT * 8, st & 1, 70);
      mbar_expect_tx_z(bars + B_T * 8, (unsigned)(sg + 1) < (unsigned)NSEG ? tbytes : 0, lane);
      fence_async_smem();
      const int s1 = rank && st < NSEG - 1 ? st + 1 : st;
      if (s1 != st) mbar_wait(bars + B_X * 8, s1 & 1, 71);
      TR(0)
      if (act && lane == 0 && !(expf_ & (rank ? 32 : 16))) {
        bulk_s2g(g_O[st & (OSLOTS - 1)][rank] + h * 8192, sb + C_OT + (st & 1) * 8192, 8192);
        asm volatile("cp.async.bulk.commit_group;" ::: "memory");
        asm volatile("cp.async.bulk.wait_group 0;" ::: "memory");
        asm volatile("fence.acq_rel.gpu;" ::: "memory");
      }
      __syncwarp();
      if (WLAG && s1 < NSTEP - 1) mbar_wait(bars + (FGATE ? B_M0 + FGATE - 1 : B_I) * 8, (s1 + (FGATE > 0)) & 1, 72);
      if (act && lane == 0) asm volatile("red.relaxed.gpu.global.add.u32 [%0], 1;" ::"l"(&g_fl.oflag[rank][sg][h >> 2]) : "memory");
      __syncwarp();
      TR(1)
    }
  } else {
    mbar_arrive_z(bars + B_M0 * 8, lane); mbar_arrive_z(bars + B_M1 * 8, lane); mbar_arrive_z(bars + B_M2 * 8, lane);
    const uint32_t wave = rank == 2 ? 0 : rank + 1, gate_p = GATE_P + wave * GATE_W, gate_g = GATE_G, gate_m = GATE_M;
    uint32_t nupd = 0, late = 0;
#pragma unroll 1
    for (int st = 0; st < NSTEP - 1; st++) {
      mbar_wait(bars + B_X * 8, st & 1, 75);
      if (st < 4) { HD(8 + st) }
      if (st == NSTEP - 2) { HD(12) }
      mbar_wait(bars + B_T * 8, st & 1, 77);
      const uint32_t now = gtime() & ~31u, tag = (st + 1) & 31;
      if (lane == 0) st_rlx32(&g_fl.stamp[blockIdx.x], (now + late) | tag);
      late = 0;
      __syncwarp();
      wait_clock(clk32() + 550);
      uint32_t s0, s1, s2;
      int it = 0;
#pragma unroll 1
      do {
        s0 = ld_rlx32(&g_fl.stamp[lane]) ^ tag; s1 = ld_rlx32(&g_fl.stamp[32 + lane]) ^ tag; s2 = ld_rlx32(&g_fl.stamp[64 + lane]) ^ tag;
        give_up(it++, SPIN_LIMIT, 76);
      } while (__any_sync(~0u, ((s0 | s1 | s2) & 31) != 0));
      const uint32_t tref = now + __reduce_max_sync(~0u, __vimax3_s32((int)(s0 - now), (int)(s1 - now), (int)(s2 - now)));
      const uint32_t g0 = gtime();
      uint32_t g1, c1;
      it = 0;
      do { g1 = gtime(); c1 = clk32(); } while (g1 == g0 && ++it < 64);
      c1 -= (g1 - tref) * 7 / 4;
      sts32(sb + C_INFO + 12, c1);
      TR(0)
      bar_sync(NB_TA, 192);
      const int sn = (st + 1) & 3;
      const uint8_t* src = (const uint8_t*)g_M + sn * 65536 + (lds32(sb + C_POL + sn * 4) ? 4096 : 12288);
      {
        const uint32_t pol = lds32(sb + C_INFO + 8);
        const uint8_t* ps = (const uint8_t*)g_P + (wave * 32 + h) * 16384;
        if (lane == 0) {
          mbar_expect_tx(bars + B_PI * 8, 8192);
          wait_clock(c1 + gate_p);
          bulk_g2s(sb + C_PI, ps + pol * 4096, 4096, bars + B_PI * 8);
          bulk_g2s(sb + C_PI + 4096, ps + (3 - pol) * 4096, 4096, bars + B_PI * 8);
          mbar_arrive_z(bars + B_J * 8, 0);
        }
        __syncwarp();
      }
      c1 += gate_m;
      if (__builtin_expect(lds32(sb + C_INFO + ((st + 1) & 1) * 4), 0)) {
        late = rank == 2 ? 160 : 0;
        mbar_wait(bars + B_U * 8, nupd++ & 1, 78);
        const uint32_t c2 = clk32() + 1300;
        if ((int)(c2 - c1) > 0) c1 = c2;
      }
      mbar_expect_tx_z(bars + (B_M0 + lane) * 8, 8192, lane / 3);
      if (lane == 0) {
#pragma unroll
        for (int g = 0; g < 3; g++) {
          wait_clock(c1 + g * gate_g);
          bulk_g2s(sb + C_M + g * 8192, src + g * 16384, 8192, bars + (B_M0 + g) * 8);
          if (g == IGRP) mbar_arrive_z(bars + B_I * 8, 0);
        }
      }
      __syncwarp();
      TR(3)
    }
  }
}

struct ChainMaps { CUtensorMap w[3], wo; };
__global__ void __cluster_dims__(3, 1, 1) __launch_bounds__(512, 1)
chain_kernel(const __grid_constant__ ChainMaps maps, const bf16* __restrict__ mem0) {
  extern __shared__ __align__(1024) uint8_t smem_raw[];
  const uint32_t sb = (smem_u32(smem_raw) + 1023) & ~1023u;
  const int tid = threadIdx.x, lane = tid & 31;
  const int w = __shfl_sync(~0u, tid >> 5, 0);
  uint32_t rank;
  asm volatile("mov.u32 %0, %%cluster_ctarank;" : "=r"(rank));
  const int h = blockIdx.x / 3;
  asm volatile("griddepcontrol.launch_dependents;" ::: "memory");
  TG(0)
  if (tid == 0) {
    const uint32_t bars = sb + C_BAR;
    mbar_init(bars + B_M0 * 8, 1); mbar_init(bars + B_M1 * 8, 1); mbar_init(bars + B_M2 * 8, 1);
    for (int i = 0; i < 4; i++) mbar_init(bars + (B_R + i) * 8, 1);
    mbar_init(bars + B_X * 8, 9); mbar_init(bars + B_O * 8, 2); mbar_init(bars + B_T * 8, 1); mbar_init(bars + B_F * 8, 2);
    mbar_init(bars + B_XL * 8, 2); mbar_init(bars + B_U * 8, 1);
    mbar_init(bars + B_P1 * 8, 8); mbar_init(bars + B_P2 * 8, 8); mbar_init(bars + B_OT * 8, 3); mbar_init(bars + B_XF * 8, 8); mbar_init(bars + B_XA * 8, 8); mbar_init(bars + B_I * 8, 1); mbar_init(bars + B_PI * 8, 1); mbar_init(bars + B_J * 8, 1);
    mbar_init(bars + B_W * 8, 1); mbar_init(bars + B_WO * 8, 1);
    asm volatile("fence.mbarrier_init.release.cluster;" ::: "memory");
    fence_async_smem();
    stage_weights(sb + C_STG, &maps.w[rank], h * 128, 0, bars + B_W * 8);
    const int nt = rank == 2 ? 2 : 3;
    mbar_expect_tx(bars + B_WO * 8, nt * 16384);
    for (int tl = 0; tl < nt; tl++)
      asm volatile("cp.async.bulk.tensor.5d.shared::cluster.global.mbarrier::complete_tx::bytes [%0], [%1, {%3, 0, 0, 0, %4}], [%2];"
                   ::"r"(sb + C_WO + tl * 16384), "l"(&maps.wo), "r"(bars + B_WO * 8), "r"((tl * 3 + rank) * 64), "r"(h * 4) : "memory");
  }
  __syncthreads();
  cluster_sync();
  if (w < 8) {
    reg_inc<184>();
    chain_proj(sb, w, lane, rank);
    TG(1)
    TRDUMP
    cluster_sync();
  } else if (w < 12) {
    reg_dec<120>();
    chain_mem(sb, w, lane, rank, h, mem0);
    STATDUMP
    TRDUMP
    cluster_sync();
  } else {
    reg_dec<24>();
    chain_dma(sb, w, lane, rank, h);
    TRDUMP
    cluster_sync();
  }
}
#undef TRC
#undef TRS

constexpr int K_BAR = 0, K_LN = 128, K_FH = 320, K_FS = 512, K_FY = 1536;
constexpr int K_W = 3072;
constexpr int K_O = K_W + 3 * 49152;
constexpr int K_ST = K_O + 65536;
constexpr int K_SMEM = K_ST + 16384;
static_assert(K_SMEM <= 232448, "shared memory");
enum { KB_FULL = 0, KB_EMPTY = 2, KB_OK = 4, KB_GO = 7, KB_ST = 10, KB_REL = 12, KB_W = 13 };
enum { KN_ST = 1, KN_ST1, KN_REL, KN_FFN, KN_INIT, KN_RES, KN_RES1, KN_CAND, KN_TAKEN, KN_FF2 };
#define GATE_R 850
struct WorkerParams {
  CUtensorMap wo;
  const bf16 *x0, *w_r, *w_gate, *w_up, *w_down;
  bf16* out;
};
#define TRC (96 + blockIdx.x)
#define FT(e)
#define QUIET 4900
__device__ __forceinline__ void quiet_until(uint32_t t) {
  int d;
  while ((d = (int)(t - clk32())) > 0) warp_sleep(min(d / 3 + 20, 1000));
}
#define FOR_UNITS _Pragma("unroll 1") for (int st = 0, n = 0; st < WSTEP; st++) \
                  _Pragma("unroll 1") for (int v = st < NSEG ? 0 : st < WSTEP - 1 ? 1 : 2, sg = v ? st - WD : st; v < (st >= WD ? 3 : 1); v++, n++, sg = st - WD)

template <int ACC>
__device__ __forceinline__ void wg_ss8(float (&d)[4], uint64_t da, uint64_t db) {
  asm volatile("wgmma.mma_async.sync.aligned.m64n8k16.f32.bf16.bf16 {%0,%1,%2,%3}, %4, %5, %6, 1, 1, 1, 0;" : O4(d, 0) : "l"(da), "l"(db), "n"(ACC));
}
template <int NU>
__device__ __forceinline__ void ffn_slice(uint32_t sb, int t, const bf16* yrow, int ev) {
  const int lane = t & 31, c = t >> 5;
  FT(1)
  {
    const uint2 r = ld_rlx64(yrow + t * 4);
    asm volatile("st.shared.v2.b32 [%0], {%1,%2};" ::"r"(sb + K_FY + ((t >> 1) & 31) * 32 + (t >> 6) * 16 + (t & 1) * 8), "r"(r.x), "r"(r.y) : "memory");
  }
  fence_async_smem();
  bar_sync(KN_FFN, 128);
  FT(2)
  {
    float g[NU][4];
    const uint64_t da = mk_desc(sb + K_W, 16384, 512, 2), db = mk_desc(sb + K_FY, 32, 0, 0);
    wg_fence();
#pragma unroll
    for (int i = 0; i < 16; i++)
#pragma unroll
      for (int u = 0; u < NU; u++) { if (i == 0) wg_ss8<0>(g[u], da + u * 3072, db); else wg_ss8<1>(g[u], da + u * 3072 + i * 64, db + i * 4); }
    wg_commit();
    wg_wait<0>();
#pragma unroll
    for (int u = 0; u < NU; u++) {
      acc_fence(g[u]);
      if ((lane & 3) == 0) {
        const uint32_t a = sb + K_FS + u * 256 + c * 64 + lane;
        sts32(a, __float_as_uint(c < 2 ? g[u][0] : g[u][1])); sts32(a + 32, __float_as_uint(c < 2 ? g[u][2] : g[u][3]));
      }
    }
  }
  FT(3)
  bar_sync(KN_FFN, 128);
  {
    const uint32_t pa = sb + K_FS + c * 256 + lane * 4;
    const float gt = round_bf16(__uint_as_float(lds32(pa)) + __uint_as_float(lds32(pa + 128)));
    const float up = __shfl_xor_sync(~0u, gt, 16);
    const uint32_t hv = pack_bf16(round_bf16(__fdividef(gt, 1.f + __expf(-gt))) * up, 0.f);
    if (lane < 16) asm volatile("st.shared.b16 [%0], %1;" ::"r"(sb + K_FH + (c * 16 + lane) * 2), "h"((unsigned short)hv) : "memory");
  }
  fence_async_smem();
  bar_sync(KN_FFN, 128);
  FT(4)
#pragma unroll 1
  for (int hf = 0; hf < 2; hf++) {
    float o[4][4];
    const uint64_t da = mk_desc(sb + K_W + 32768 + hf * 8192, 16, 1024, 1), db = mk_desc(sb + K_FH, 16, 0, 0);
    wg_fence();
#pragma unroll
    for (int u = 0; u < NU; u++)
#pragma unroll
      for (int j = 0; j < 4; j++) { if (u == 0) wg_ss8<0>(o[j], da + j * 128, db); else wg_ss8<1>(o[j], da + u * 3072 + j * 128, db + u * 2); }
    wg_commit();
    wg_wait<0>();
    float lo = 0.f, hi = 0.f;
#pragma unroll
    for (int j = 0; j < 4; j++) {
      acc_fence(o[j]);
      const float a = __shfl_sync(~0u, o[j][0], lane & 28), b = __shfl_sync(~0u, o[j][2], lane & 28);
      if ((lane & 3) == j) { lo = a; hi = b; }
    }
    float* p = &g_fl.upd[ev][hf * 256 + (lane & 3) * 64 + c * 16 + (lane >> 2)];
    asm volatile("red.relaxed.gpu.global.add.f32 [%0], %1; red.relaxed.gpu.global.add.f32 [%0 + 32], %2;" ::"l"(p), "f"(lo), "f"(hi) : "memory");
  }
  FT(5)
  bar_sync(KN_FFN, 128);
  if (t == 96) red_release(g_fl.ffncnt[ev]);
  __syncwarp();
}
__device__ __forceinline__ uint4 pair_ln(uint4 r, float& e, uint32_t sl, int bar, int t) {
  const float x[8] = {bf_lo(r.x), bf_hi(r.x), bf_lo(r.y), bf_hi(r.y), bf_lo(r.z), bf_hi(r.z), bf_lo(r.w), bf_hi(r.w)};
  const float s = ((x[0] + x[1]) + (x[2] + x[3])) + ((x[4] + x[5]) + (x[6] + x[7]));
  const float q = (fmaf(x[0], x[0], x[1] * x[1]) + fmaf(x[2], x[2], x[3] * x[3])) + (fmaf(x[4], x[4], x[5] * x[5]) + fmaf(x[6], x[6], x[7] * x[7]));
  const bool u16 = t & 16, u8 = t & 8;
  const float a = (u16 ? q : s) + __shfl_xor_sync(~0u, u16 ? s : q, 16), b = e + __shfl_xor_sync(~0u, e, 16);
  float v = (u8 ? b : a) + __shfl_xor_sync(~0u, u8 ? a : b, 8);
  v += __shfl_xor_sync(~0u, v, 4); v += __shfl_xor_sync(~0u, v, 2); v += __shfl_xor_sync(~0u, v, 1);
  sts32(sl + (t >> 3) * 4, __float_as_uint(v));
  bar_sync(bar, 64);
  const uint4 s0 = lds128(sl), s1 = lds128(sl + 16);
  const float m = (__uint_as_float(s0.x) + __uint_as_float(s1.x)) * (1.f / DM), m2 = (__uint_as_float(s0.z) + __uint_as_float(s1.z)) * (1.f / DM);
  e = __uint_as_float(s0.y) + __uint_as_float(s1.y);
  float rs;
  asm("rsqrt.approx.ftz.f32 %0, %1;" : "=f"(rs) : "f"(fmaxf(fmaf(-m, m, m2), 0.f) + 1e-5f));
  return make_uint4(pack_bf16((x[0] - m) * rs, (x[1] - m) * rs), pack_bf16((x[2] - m) * rs, (x[3] - m) * rs),
                    pack_bf16((x[4] - m) * rs, (x[5] - m) * rs), pack_bf16((x[6] - m) * rs, (x[7] - m) * rs));
}
__device__ __forceinline__ uint32_t score_bits(float r) {
  const uint32_t b = pack_bf16(0.f, r);
  return (b & 0x80000000u) ? ~b : (b | 0x80000000u);
}

__global__ void __launch_bounds__(640, 1) worker_kernel(const __grid_constant__ WorkerParams prm) {
  extern __shared__ __align__(1024) uint8_t smem_raw[];
  const uint32_t sb = smem_u32(smem_raw);
  if (sb & 1023) __trap();
  const int tid = threadIdx.x, lane = tid & 31;
  const int w = __shfl_sync(~0u, tid >> 5, 0);
  const int me = blockIdx.x, kb = me >> 2, cb = me & 3;
  const bool full = me < 32;
  const uint32_t bars = sb + K_BAR;
  TG(0)
  if (tid == 0) {
    for (int i = 0; i < 2; i++) { mbar_init(bars + (KB_FULL + i) * 8, 1); mbar_init(bars + (KB_EMPTY + i) * 8, 1); }
    for (int i = 0; i < 10; i++) mbar_init(bars + (KB_OK + i) * 8, i < 3 ? 2 : 1);
    sts32(sb + K_LN + 144, 0);
    asm volatile("fence.mbarrier_init.release.cluster;" ::: "memory");
    fence_async_smem();
  }
  {
    Row r[3];
#pragma unroll
    for (int i = 0; i < 3; i++) r[i] = load_row(prm.x0 + (size_t)min(me * 20 + w + i * NWORK * 20, NTOK - 1) * DM, lane);
    if (tid == 0 && full) stage_weights(sb + K_W, &prm.wo, cb * 128, kb * 512, bars + KB_W * 8);
    const int gt = me * 640 + tid, nt = NWORK * 640;
    if (gt < 4 * 3072) ((uint4*)g_M)[gt / 3072 * 4096 + 256 + gt % 3072] = make_uint4(~0u, ~0u, ~0u, ~0u);
    if (gt < 16384) ((uint4*)(g_part[1] + 32 * 8192))[gt] = make_uint4(0, 0, 0, 0);
    if (gt < (int)(sizeof(Flags) / 16)) ((uint4*)&g_fl)[gt] = make_uint4(0, 0, 0, 0);
    static_assert(sizeof(Flags) / 16 <= NWORK * 640, "reset");
    if ((NSTEP - 1) & 1)
      for (int i = gt; i < 96 * 1024; i += nt) ((uint4*)g_P)[i] = make_uint4(0, 0, 0, 0);
#pragma unroll
    for (int i = 0; i < 3; i++) {
      const int row = min(me * 20 + w + i * NWORK * 20, NTOK - 1);
      store_row_img(g_xs[0] + (size_t)(row >> 5) * 32768, row & 31, lane, warp_ln(r[i]));
    }
  }
  __syncthreads();
  if (tid == 608) red_release(g_ex.ready);
  __syncwarp();
  if (w < 8) {
    reg_inc<176>();
    if (full) {
      uint32_t wA[32][4];
      mbar_wait(bars + KB_W * 8, 0, 79);
      load_wfrags(wA, sb + K_W, w, lane);
      bar_arrive(KN_INIT, 384);
      const uint32_t sp = pin(sb + K_ST + ((lane >> 4) * 8 + (lane & 7)) * 256 + (((2 * w + ((lane >> 3) & 1)) ^ (lane & 7)) << 4));
      const uint32_t tm = pin(lane < 4 ? 0x00010001u : 0u);
      FOR_UNITS {
        float d[16];
        mbar_wait(bars + (KB_FULL + (n & 1)) * 8, (n >> 1) & 1, 81);
        TR(4 * v)
        const uint64_t db = mk_desc(sb + K_O + (n & 1) * 32768, 128, 2048, 0);
        wg_fence();
#pragma unroll
        for (int ks = 0; ks < 32; ks++) {
          if (ks == 0) wg_rs32<0, 0>(d, wA[ks], db);
          else wg_rs32<0, 1>(d, wA[ks], db + (ks >> 3) * 512 + (ks & 7) * 16);
        }
        wg_commit();
        mbar_wait(bars + (KB_ST + (n & 1)) * 8, ((n >> 1) & 1) ^ 1, 82);
        wg_wait<0>();
        acc_fence(d);
        TR(4 * v + 1)
        const uint32_t tag = (sg & 2) ? 0u : tm;
        uint32_t pk[8];
#pragma unroll
        for (int i = 0; i < 8; i++) pk[i] = (pack_bf16(d[2 * i], d[2 * i + 1]) & ~tm) | tag;
        stsm4t(sp + (n & 1) * 8192, pk[0], pk[1], pk[2], pk[3]);
        stsm4t(sp + (n & 1) * 8192 + 4096, pk[4], pk[5], pk[6], pk[7]);
        bar_arrive(KN_ST + (n & 1), 288);
        TR(4 * v + 2)
      }
    }
  } else if (w < 12) {
    reg_dec<56>();
    if (full) {
      const int ly = (w >> 1) & 1, t = pin(tid & 63);
      const uint32_t so = pin((t >> 4) * 8192 + me * 256 + (((t & 15) ^ (me & 7)) << 4));
      int sstar = -1;
      uint32_t sl = sb + K_LN + ly * 64;
      float rr = 0.f;
      int kprev = -1;
      auto records = [&](int sg, uint32_t off) {
        int it = 0;
        while (__any_sync(~0u, (int)lds32(sb + K_LN + 144) <= sg)) { give_up(++it, SPIN_LIMIT, 86); warp_sleep(50); }
        return lds32(sb + K_LN + off);
      };
#pragma unroll 1
      for (int n = ly ? 2 * WD : 0; n < 2 * WSTEP; n++) {
        const int st = n >> 1, v = (n & 1) ? 2 : ly, sg = v ? st - WD : st, tok = sg * 32 + me;
        if (n == 2 * NSEG) bar_sync(KN_INIT, 128);
        if (n == 2 * NSEG + 2) sstar = records(NSEG - 1, 156);
        if (v == 2 ? sg < 0 || (st < NSEG ? st & 1 : 0) != ly : sg >= NSEG - v) continue;
        const bf16* xin = v ? g_rows[tok][0][2] : prm.x0 + tok * DM;
        if (v == 2 && ((records(sg, 148 + (sg >> 5) * 4) >> (sg & 31)) & 1)) xin = g_x2p[sg][0];
        const uint8_t* src = g_part[v] + (sg & 1) * (32 * 8192) + so;
        const uint32_t flip = (sg & 2) ? ~0u : 0u;
        mbar_wait(bars + (KB_GO + v) * 8, sg & 1, 87);
        TR(4 * v)
        uint4 p[8], x;
        int it = 0;
#pragma unroll 1
        do {
#pragma unroll
          for (int k = 0; k < 8; k++) p[k] = ld_rlx128(src + k * 32768);
          x = ld_rlx128(((WEXP & 2) ? prm.x0 : xin) + t * 8);
          give_up(it++, SPIN_LIMIT, 85);
        } while (__builtin_expect(!__all_sync(~0u, (int)and3(and3(and_x(p[0].x, p[1].x, flip), and_x(p[2].x, p[3].x, flip), 1u),
                                                             and_x(p[4].x, p[5].x, flip), and_x(p[6].x, p[7].x, flip))), 0));
        mbar_arrive_z(bars + (KB_OK + v) * 8, t & 31);
#define P8(h, f) (((h(p[0].f) + h(p[1].f)) + (h(p[2].f) + h(p[3].f))) + ((h(p[4].f) + h(p[5].f)) + (h(p[6].f) + h(p[7].f))))
#define X8(f) x.f = add_bf16x2(x.f, pack_bf16(P8(bf_lo, f), P8(bf_hi, f)));
        X8(x) X8(y) X8(z) X8(w)
#undef X8
#undef P8
        TRV(12 + v, it - 1)
        TR(4 * v + 1)
        bf16* dst = g_rows[tok][v][0] + t * 8;
        *(uint4*)dst = x;
        const uint4 wr = ld_rlx128(prm.w_r + t * 8);
        sl ^= 32;
        uint4 y = pair_ln(x, rr, sl, KN_RES + ly, t);
        *(uint4*)(dst + DM) = y;
        x = make_uint4(add_bf16x2(x.x, y.x), add_bf16x2(x.y, y.y), add_bf16x2(x.z, y.z), add_bf16x2(x.w, y.w));
        *(uint4*)(v == (sg < sstar ? 1 : 2) ? prm.out + tok * DM + t * 8 : dst + 2 * DM) = x;
        asm volatile("{ .reg .pred p; setp.eq.u32 p, %2, 0; @p st.relaxed.gpu.global.u64 [%0], %1; }" ::"l"(&g_fl.key[0][0][0] + max(kprev, 0)),
                     "l"((u64)score_bits(rr) << 32 | (uint32_t)~(kprev & (NTOK - 1))), "r"(t | (kprev < 0)) : "memory");
        kprev = v * NTOK + tok;
        rr = (fmaf(bf_lo(y.x), bf_lo(wr.x), bf_hi(y.x) * bf_hi(wr.x)) + fmaf(bf_lo(y.y), bf_lo(wr.y), bf_hi(y.y) * bf_hi(wr.y))) +
             (fmaf(bf_lo(y.z), bf_lo(wr.z), bf_hi(y.z) * bf_hi(wr.z)) + fmaf(bf_lo(y.w), bf_lo(wr.w), bf_hi(y.w) * bf_hi(wr.w)));
        if (v == 0 || st >= NSEG) {
          sl ^= 32;
          y = pair_ln(x, rr, sl, KN_RES + ly, t);
          if (v == 0) *(uint4*)(g_xs[1] + sg * 32768 + (t >> 3) * 4096 + me * 128 + (((t ^ me) & 7) << 4)) = y;
          sts32(sb + K_LN + 128 + ly * 4, score_bits(rr));
          bar_arrive(KN_REL, v == 0 || st == WSTEP - 1 ? 96 : 160);
          kprev = -1;
        }
        TR(4 * v + 2)
      }
    }
  } else if (w < 16) {
    reg_dec<48>();
    const int t = tid - 384, nu = full ? 3 : 4;
    if (full) bar_sync(KN_INIT, 384);
    {
      const int j0 = (full ? me * 3 : 96 + (me - 32) * 4) * 16;
#pragma unroll 1
      for (int i = t; i < nu * 3072; i += 128) {
        const int u = i / 3072, r = i - u * 3072;
        const int q = (r ^ (r >> 3)) & 3, r2 = r - 2048;
        const bf16* src = r < 2048 ? ((q & 2) ? prm.w_up : prm.w_gate) + (size_t)(r >> 2) * FF + j0 + u * 16 + (q & 1) * 8
                                   : prm.w_down + (size_t)(j0 + u * 16 + ((r2 >> 3) & 15)) * DM + (r2 >> 7) * 64 + ((r2 ^ (r2 >> 3)) & 7) * 8;
        cp16(sb + K_W + i * 16, src);
      }
      asm volatile("cp.async.wait_all;" ::: "memory");
    }
    bar_arrive(KN_TAKEN, 160);
#pragma unroll 1
    while (true) {
      bar_sync(KN_CAND, 160);
      const uint4 cand = lds128(sb + K_LN + 160);
      const u64 k = (u64)cand.y << 32 | cand.x;
      const int ev = cand.z, ver = cand.w & 3, tok = key_token(k);
      const bool last = cand.w & 4;
      if (!last) {
        bar_arrive(KN_TAKEN, 160);
        FT(0)
        if (full) ffn_slice<3>(sb, t, g_rows[tok][ver][1], ev); else ffn_slice<4>(sb, t, g_rows[tok][ver][1], ev);
      }
      if ((tok & 31) == me && (ver == 0 || last)) {
        if (t < 64) {
          FT(6)
          uint4 x = ld_rlx128(g_rows[tok][ver][0] + t * 8);
          const uint4 y = ld_rlx128(g_rows[tok][ver][1] + t * 8);
          const float sig = round_bf16(__fdividef(1.f, 1.f + __expf(-key_score(k))));
          int it = 0;
          while (ld_rlx32(g_fl.ffncnt[ev]) < NWORK) { give_up(++it, SPIN_LIMIT, 80); warp_sleep(40); }
          const uint4 u0 = ld_rlx128(&g_fl.upd[ev][t * 8]), u1 = ld_rlx128(&g_fl.upd[ev][t * 8 + 4]);
          auto upd = [&](uint32_t xw, uint32_t yw, uint32_t a, uint32_t b) {
            const uint32_t r = pack_bf16(__uint_as_float(a), __uint_as_float(b));
            return add_bf16x2(xw, add_bf16x2(yw, pack_bf16(bf_lo(r) * sig, bf_hi(r) * sig)));
          };
          x = make_uint4(upd(x.x, y.x, u0.x, u0.y), upd(x.y, y.y, u0.z, u0.w), upd(x.z, y.z, u1.x, u1.y), upd(x.w, y.w, u1.z, u1.w));
          FT(7)
          *(uint4*)((ver ? prm.out + tok * DM : g_x2p[ev][0]) + t * 8) = x;
          if (ver == 0) {
            float e = 0.f;
            *(uint4*)(g_x2p[ev][1] + t * 8) = pair_ln(x, e, sb + K_FS, KN_FF2, t);
            bar_sync(KN_FF2, 64);
            if (t == 0) st_release32(g_fl.patch[ev], 1);
            __syncwarp();
          }
        }
      }
      if (ev == NSEG && !last && full) {
        const int nc = min((int)lds32(sb + K_LN + 156), NSEG + 1 - WD);
#pragma unroll 1
        for (int s0 = (t >> 6) * 4; s0 < nc; s0 += 8) {
          uint4 q[4];
#pragma unroll
          for (int i = 0; i < 4; i++) q[i] = ld_rlx128(g_rows[min(s0 + i, nc - 1) * 32 + me][1][2] + (t & 63) * 8);
#pragma unroll
          for (int i = 0; i < 4; i++) *(uint4*)(prm.out + (min(s0 + i, nc - 1) * 32 + me) * DM + (t & 63) * 8) = q[i];
        }
      }
      FT(8)
      if (last) break;
    }
  } else {
    reg_dec<24>();
    if (w < 18) wait_count(g_ex.ready, NWORK, 94);
    if (w == 16) {
      u64 best = 0, mask = 0;
      int sstar = 0;
      uint32_t ver = 0, ev = 0;
      auto post = [&](uint32_t cmd) {
        bar_sync(KN_TAKEN, 160);
        sts128(sb + K_LN + 160, make_uint4((uint32_t)best, (uint32_t)(best >> 32), ev, ver | cmd));
        bar_arrive(KN_CAND, 160);
      };
      u64 accn = 0, acca = 0;
      uint32_t recs = 0;
      int j = 0;
      uint32_t tq = clk32();
#pragma unroll 1
      for (int st = 0; st < WSTEP; st++) {
        const u64* keys = st < NSEG ? g_fl.key[0][st] : g_fl.key[2][st - WD];
        const bool early = __any_sync(~0u, ld_rlx32(keys + lane) == 0);
        if (early && st < NSEG) quiet_until(tq);
        u64 k = wait_keys(keys, lane, 91);
        if (early) tq = clk32() + QUIET;
        if (st < NSEG) {
          const bool rec = k > best;
          recs &= ~(1u << (st & 31));
          if (rec) {
            best = k; ev = sstar = st;
            recs |= 1u << (st & 31);
            if ((key_token(k) & 31) == me) mask |= 1ull << st;
          }
          if (lane == 0) sts128(sb + K_LN + 144, make_uint4(st + 1, (uint32_t)mask, (uint32_t)(mask >> 32), sstar));
          __syncwarp();
          if (rec) post(0);
        }
#pragma unroll 1
        for (; j <= st - WD - (st < NSEG ? 2 : 0); j++) {
          u64 kn = 1, kc;
          int it = 0;
          do {
            if (j < NSEG - 1) asm volatile("ld.relaxed.gpu.global.u64 %0, [%1];" : "=l"(kn) : "l"(&g_fl.key[1][j][lane]) : "memory");
            asm volatile("ld.relaxed.gpu.global.u64 %0, [%1];" : "=l"(kc) : "l"(&g_fl.key[2][j][lane]) : "memory");
            give_up(it++, SPIN_LIMIT, 92);
          } while (__any_sync(~0u, kn == 0 || kc == 0));
          if ((recs >> (j & 31)) & 1) acca = accn;
          if (kc > acca) acca = kc;
          if (kn > accn) accn = kn;
        }
        if (st >= NSEG) {
          const u64 m = j <= sstar ? accn : acca;
          const uint32_t hi = __reduce_max_sync(~0u, (uint32_t)(m >> 32));
          k = (u64)hi << 32 | __reduce_max_sync(~0u, (uint32_t)(m >> 32) == hi ? (uint32_t)m : 0u);
          if (st == NSEG || k != best) {
            best = k; ev = st;
            ver = (key_token(k) >> 5) < sstar ? 1 : 2;
            post(0);
          }
        }
      }
      HD(6)
      post(4);
      if (me == 0 && lane == 0) st_rlx32(g_ex.ready, 0);
    } else if (!full) {
    } else if (w == 17) {
      uint32_t tq = clk32();
      FOR_UNITS {
        if (ld_rlx32(&g_fl.oflag[v][sg][kb]) < 4) {
          if (v == (st < NSEG ? 0 : 1) && st < WSTEP - 3) quiet_until(tq);
          wait_count(&g_fl.oflag[v][sg][kb], 4, 84);
          if (v == (st < NSEG ? 0 : 1)) tq = clk32() + QUIET;
        }
        mbar_wait(bars + (KB_EMPTY + (n & 1)) * 8, ((n >> 1) & 1) ^ 1, 83);
        TR(v)
        if (st == WSTEP - 1) { HD(v) }
        if (lane == 0) {
          fence_async_glb();
          mbar_expect_tx(bars + (KB_FULL + (n & 1)) * 8, (WEXP & 4) ? 4096 : 32768);
          bulk_g2s(sb + K_O + (n & 1) * 32768, g_O[(v ? sg + DELTA : sg) & (OSLOTS - 1)][v] + kb * 32768, (WEXP & 4) ? 4096 : 32768, bars + (KB_FULL + (n & 1)) * 8);
        }
        __syncwarp();
      }
    } else if (w == 18) {
      FOR_UNITS {
        if (sg > 0) mbar_wait(bars + (KB_OK + v) * 8, (sg - 1) & 1, 90);
        bar_sync(KN_ST + (n & 1), 288);
        fence_async_smem();
        const uint32_t tg = clk32() + GATE_R;
        if (lane == 0) {
          bulk_s2g(g_part[v] + ((sg & 1) * 32 + me) * 8192, sb + K_ST + (n & 1) * 8192, 8192);
          asm volatile("cp.async.bulk.commit_group;" ::: "memory");
          mbar_arrive_z(bars + (KB_EMPTY + (n & 1)) * 8, 0);
          asm volatile("cp.async.bulk.wait_group.read 0;" ::: "memory");
        }
        __syncwarp();
        mbar_arrive_z(bars + (KB_ST + (n & 1)) * 8, lane);
        TR(v)
        if (v == (st < NSEG ? 0 : st < WSTEP - 1 ? 1 : 2) && st > 0) mbar_wait(bars + KB_REL * 8, (st - 1) & 1, 93);
        wait_clock(tg);
        if (st == WSTEP - 1) { HD(2 + v) }
        mbar_arrive_z(bars + (KB_GO + v) * 8, lane);
      }
    } else {
#pragma unroll 1
      for (int st = 0; st < WSTEP; st++) {
        const int sg = st < NSEG ? st : st - WD;
        const bool both = st >= NSEG && st < WSTEP - 1;
        bar_sync(KN_REL, both ? 160 : 96);
        const uint32_t ob = __shfl_sync(~0u, lds32(sb + K_LN + 128), 0), obn = __shfl_sync(~0u, lds32(sb + K_LN + 132), 0);
        mbar_arrive_z(bars + KB_REL * 8, lane);
        if (st == WSTEP - 1) { HD(5) }
        if (lane == 0) {
          if (both) asm volatile("st.relaxed.gpu.global.u64 [%0], %1;" ::"l"(&g_fl.key[1][sg][me]), "l"((u64)obn << 32 | (uint32_t)~(sg * 32 + me)) : "memory");
          st_release_u64(&g_fl.key[st < NSEG ? 0 : 2][sg][me], (u64)ob << 32 | (uint32_t)~(sg * 32 + me));
        }
        __syncwarp();
        TR(0)
      }
    }
  }
}
#undef TRC

typedef CUresult (*EncodeFn)(CUtensorMap*, CUtensorMapDataType, cuuint32_t, void*, const cuuint64_t*, const cuuint64_t*,
                             const cuuint32_t*, const cuuint32_t*, CUtensorMapInterleave, CUtensorMapSwizzle,
                             CUtensorMapL2promotion, CUtensorMapFloatOOBfill);
void make_map(EncodeFn fn, CUtensorMap* m, const void* ptr, int rank, const cuuint64_t* dims, const cuuint64_t* strides, const cuuint32_t* box) {
  const cuuint32_t es[5] = {1, 1, 1, 1, 1};
  fn(m, CU_TENSOR_MAP_DATA_TYPE_BFLOAT16, rank, (void*)ptr, dims, strides, box, es, CU_TENSOR_MAP_INTERLEAVE_NONE,
     CU_TENSOR_MAP_SWIZZLE_128B, CU_TENSOR_MAP_L2_PROMOTION_L2_256B, CU_TENSOR_MAP_FLOAT_OOB_FILL_NONE);
}
struct HostState {
  const void* key[4];
  ChainMaps cm;
  CUtensorMap wo;
};
HostState g_hs;

}

extern "C" void kernel_launch(void* const* d_in, const int* in_sizes, int n_in, void* d_out, int out_size) {
  (void)in_sizes; (void)n_in; (void)out_size;
  HostState& hs = g_hs;
  if (hs.key[0] != d_in[2] || hs.key[1] != d_in[3] || hs.key[2] != d_in[4] || hs.key[3] != d_in[5]) {
    void* fnp = nullptr;
    cudaDriverEntryPointQueryResult qr;
    cudaGetDriverEntryPoint("cuTensorMapEncodeTiled", &fnp, cudaEnableDefault, &qr);
    const cuuint32_t box[2] = {64, 256}, box5[5] = {64, 2, 4, 4, 4};
    const cuuint64_t dw[2] = {HD, DM}, sw[1] = {HD * 2}, dwo[2] = {DM, HD}, swo[1] = {DM * 2};
    const cuuint64_t d5[5] = {DM, 2, 4, 4, HD / 32}, s5[4] = {DM * 2, 8 * DM * 2, 2 * DM * 2, 32 * DM * 2};
    for (int i = 0; i < 3; i++) make_map((EncodeFn)fnp, &hs.cm.w[i], d_in[2 + i], 2, dw, sw, box);
    make_map((EncodeFn)fnp, &hs.cm.wo, d_in[5], 5, d5, s5, box5);
    make_map((EncodeFn)fnp, &hs.wo, d_in[5], 2, dwo, swo, box);
    cudaFuncSetAttribute(worker_kernel, cudaFuncAttributeMaxDynamicSharedMemorySize, K_SMEM);
    cudaFuncSetAttribute(chain_kernel, cudaFuncAttributeMaxDynamicSharedMemorySize, C_SMEM);
    for (int i = 0; i < 4; i++) hs.key[i] = d_in[2 + i];
  }
  cudaStream_t st = cudaStreamPerThread;
  WorkerParams wp;
  wp.wo = hs.wo; wp.x0 = (const bf16*)d_in[0]; wp.w_r = (const bf16*)d_in[8]; wp.w_gate = (const bf16*)d_in[9];
  wp.w_up = (const bf16*)d_in[10]; wp.w_down = (const bf16*)d_in[11]; wp.out = (bf16*)d_out;
  chain_kernel<<<96, 512, C_SMEM, st>>>(hs.cm, (const bf16*)d_in[1]);
  cudaLaunchAttribute pdl[1];
  pdl[0].id = cudaLaunchAttributeProgrammaticStreamSerialization;
  pdl[0].val.programmaticStreamSerializationAllowed = 1;
  cudaLaunchConfig_t cfg = {};
  cfg.gridDim = dim3(NWORK); cfg.blockDim = dim3(640); cfg.dynamicSmemBytes = K_SMEM; cfg.stream = st;
  cfg.attrs = pdl; cfg.numAttrs = 1;
  cudaLaunchKernelEx(&cfg, worker_kernel, wp);
}
```

```cpp
#include <cuda_runtime.h>
#include <cuda_bf16.h>
#include <cuda.h>
#include <stdint.h>

namespace {

typedef __nv_bfloat16 bf16;
typedef unsigned long long u64;

constexpr int NTOK = 2048, DM = 512, HD = 4096, NSEG = 64, FF = 1792;
#define DELTA 5
constexpr int NSTEP = NSEG + DELTA;
#define WLAG 1
constexpr int WD = DELTA + WLAG, WSTEP = NSEG + WD;
constexpr int SPIN_LIMIT = 40000;
constexpr int MBAR_LIMIT = 20000;
constexpr int NWORK = 36;
constexpr int OSLOTS = 8;
#define SLP_C 100
#define SLP_K 200
#define WEXP 0

__device__ __align__(1024) uint8_t g_xs[2][NSEG * 32768];
__device__ __align__(1024) uint8_t g_O[OSLOTS][3][32 * 8192];
__device__ __align__(1024) uint8_t g_part[3][2 * 32 * 8192];
__device__ __align__(1024) bf16 g_rows[NTOK][3][3][DM];
__device__ __align__(1024) bf16 g_x2p[NSEG][2][DM];
struct Flags {
  uint32_t pol[96];
  uint32_t stamp[96];
  uint32_t oflag[3][NSEG][8];
  uint32_t ffncnt[WSTEP][8];
  uint32_t patch[NSEG][8];
  u64 key[3][NSEG][32];
  float upd[WSTEP][DM];
};
struct Exchange { uint32_t M[4 * 16384], P[96 * 4096]; Flags fl; uint32_t ready[32]; };
__device__ __align__(65536) Exchange g_ex;
#define g_M g_ex.M
#define g_P g_ex.P
#define g_fl g_ex.fl
#define TR(e)
#define TRV(e, v)
#define TG(i)
#define HD(e)
#define TRDUMP
#define TREXTRA 0

#define STAT(e, v)
#define STATC(n)
#define STATDUMP
__device__ __forceinline__ uint32_t smem_u32(const void* p) { return (uint32_t)__cvta_generic_to_shared(p); }
__device__ __forceinline__ uint32_t pack_bf16(float lo, float hi) {
  uint32_t r;
  asm("cvt.rn.bf16x2.f32 %0, %1, %2;" : "=r"(r) : "f"(hi), "f"(lo));
  return r;
}
__device__ __forceinline__ float bf_lo(uint32_t v) { return __uint_as_float(v << 16); }
__device__ __forceinline__ float bf_hi(uint32_t v) { return __uint_as_float(v & 0xffff0000u); }
__device__ __forceinline__ float ex2_fast(float x) { float y; asm("ex2.approx.ftz.f32 %0, %1;" : "=f"(y) : "f"(x)); return y; }
__device__ __forceinline__ float round_bf16(float x) { return __bfloat162float(__float2bfloat16_rn(x)); }
__device__ __forceinline__ uint32_t clk32() { uint32_t t; asm volatile("mov.u32 %0, %%clock;" : "=r"(t) :: "memory"); return t; }

__device__ __forceinline__ void mma16816(float (&d)[4], uint32_t a0, uint32_t a1, uint32_t a2, uint32_t a3,
                                         uint32_t b0, uint32_t b1) {
  asm("mma.sync.aligned.m16n8k16.row.col.f32.bf16.bf16.f32 {%0,%1,%2,%3}, {%4,%5,%6,%7}, {%8,%9}, {%0,%1,%2,%3};"
      : "+f"(d[0]), "+f"(d[1]), "+f"(d[2]), "+f"(d[3])
      : "r"(a0), "r"(a1), "r"(a2), "r"(a3), "r"(b0), "r"(b1));
}
__device__ __forceinline__ void ldsm4t(uint32_t (&r)[4], uint32_t addr) {
  asm volatile("ldmatrix.sync.aligned.m8n8.x4.trans.shared.b16 {%0,%1,%2,%3}, [%4];"
               : "=r"(r[0]), "=r"(r[1]), "=r"(r[2]), "=r"(r[3]) : "r"(addr) : "memory");
}
__device__ __forceinline__ void stsm4(uint32_t addr, uint32_t a, uint32_t b, uint32_t c, uint32_t d) {
  asm volatile("stmatrix.sync.aligned.m8n8.x4.shared.b16 [%0], {%1,%2,%3,%4};" ::"r"(addr), "r"(a), "r"(b), "r"(c), "r"(d) : "memory");
}
__device__ __forceinline__ void stsm4t(uint32_t addr, uint32_t a, uint32_t b, uint32_t c, uint32_t d) {
  asm volatile("stmatrix.sync.aligned.m8n8.x4.trans.shared.b16 [%0], {%1,%2,%3,%4};" ::"r"(addr), "r"(a), "r"(b), "r"(c), "r"(d) : "memory");
}
__device__ __forceinline__ uint4 lds128(uint32_t a) {
  uint4 v; asm volatile("ld.shared.v4.b32 {%0,%1,%2,%3}, [%4];" : "=r"(v.x), "=r"(v.y), "=r"(v.z), "=r"(v.w) : "r"(a) : "memory"); return v;
}
__device__ __forceinline__ uint32_t lds32(uint32_t a) { uint32_t v; asm volatile("ld.shared.b32 %0, [%1];" : "=r"(v) : "r"(a) : "memory"); return v; }
__device__ __forceinline__ void sts32(uint32_t a, uint32_t x) { asm volatile("st.shared.b32 [%0], %1;" ::"r"(a), "r"(x) : "memory"); }
__device__ __forceinline__ void sts128(uint32_t a, uint4 v) {
  asm volatile("st.shared.v4.b32 [%0], {%1,%2,%3,%4};" ::"r"(a), "r"(v.x), "r"(v.y), "r"(v.z), "r"(v.w) : "memory");
}
__device__ __forceinline__ void cp16(uint32_t dst, const void* src) {
  asm volatile("cp.async.cg.shared.global [%0], [%1], 16;" ::"r"(dst), "l"(src) : "memory");
}
__device__ __forceinline__ void mbar_init(uint32_t mbar, uint32_t cnt) {
  asm volatile("mbarrier.init.shared.b64 [%0], %1;" ::"r"(mbar), "r"(cnt) : "memory");
}
__device__ __forceinline__ void mbar_expect_tx(uint32_t mbar, uint32_t bytes) {
  asm volatile("mbarrier.arrive.expect_tx.shared.b64 _, [%0], %1;" ::"r"(mbar), "r"(bytes) : "memory");
}
__device__ __forceinline__ void mbar_arrive_z(uint32_t mbar, uint32_t z) {
  asm volatile("{ .reg .pred p; setp.eq.u32 p, %1, 0; @p mbarrier.arrive.shared.b64 _, [%0]; }" ::"r"(mbar), "r"(z) : "memory");
}
__device__ __forceinline__ void mbar_expect_tx_z(uint32_t mbar, uint32_t bytes, uint32_t z) {
  asm volatile("{ .reg .pred p; setp.eq.u32 p, %2, 0; @p mbarrier.arrive.expect_tx.shared.b64 _, [%0], %1; }" ::"r"(mbar), "r"(bytes), "r"(z) : "memory");
}
__device__ __forceinline__ void mbar_arrive_remote_z(uint32_t mbar, uint32_t z) {
  asm volatile("{ .reg .pred p; setp.eq.u32 p, %1, 0; @p mbarrier.arrive.shared::cluster.b64 _, [%0]; }" ::"r"(mbar), "r"(z) : "memory");
}
__device__ __forceinline__ void warp_sleep(uint32_t ns) { __nanosleep(ns); __syncwarp(); }
__device__ __forceinline__ void fail(int) { __trap(); }
__device__ __forceinline__ void give_up(int it, int limit, int code) { if (it > limit) fail(code); }
__device__ __forceinline__ void mbar_wait(uint32_t mbar, uint32_t par, int code) {
  asm volatile("{ .reg .pred p; .reg .b32 n; mov.b32 n, %2;\n"
               "W: mbarrier.try_wait.parity.shared::cta.b64 p, [%0], %1; @p bra D;\n"
               "add.s32 n, n, -1; setp.eq.s32 p, n, 0; @p trap; bra W;\n"
               "D: }" ::"r"(mbar), "r"(par), "n"(MBAR_LIMIT) : "memory");
}
__device__ __forceinline__ void bulk_g2s(uint32_t dst, const void* src, uint32_t bytes, uint32_t mbar) {
  asm volatile("cp.async.bulk.shared::cluster.global.mbarrier::complete_tx::bytes [%0], [%1], %2, [%3];"
               ::"r"(dst), "l"(src), "r"(bytes), "r"(mbar) : "memory");
}
__device__ __forceinline__ void bulk_s2r(uint32_t dst, uint32_t src, uint32_t bytes, uint32_t mbar) {
  asm volatile("cp.async.bulk.shared::cluster.shared::cta.mbarrier::complete_tx::bytes [%0], [%1], %2, [%3];"
               ::"r"(dst), "r"(src), "r"(bytes), "r"(mbar) : "memory");
}
__device__ __forceinline__ void bulk_s2g(void* dst, uint32_t src, uint32_t bytes) {
  asm volatile("cp.async.bulk.global.shared::cta.bulk_group [%0], [%1], %2;" ::"l"(dst), "r"(src), "r"(bytes) : "memory");
}
__device__ __forceinline__ void fence_async_smem() { asm volatile("fence.proxy.async.shared::cta;" ::: "memory"); }
__device__ __forceinline__ void fence_async_glb() { asm volatile("fence.proxy.async.global;" ::: "memory"); }
__device__ __forceinline__ void bar_sync(int id, int n) { asm volatile("bar.sync %0, %1;" ::"r"(id), "r"(n) : "memory"); }
__device__ __forceinline__ void bar_arrive(int id, int n) { asm volatile("bar.arrive %0, %1;" ::"r"(id), "r"(n) : "memory"); }
__device__ __forceinline__ void cluster_sync() { asm volatile("barrier.cluster.arrive.release; barrier.cluster.wait.acquire;" ::: "memory"); }
__device__ __forceinline__ uint32_t mapa_u32(uint32_t a, uint32_t r) {
  uint32_t o;
  asm("mapa.shared::cluster.u32 %0, %1, %2;" : "=r"(o) : "r"(a), "r"(r));
  return o;
}
template <int OFF>
__device__ __forceinline__ void st_async32(uint32_t a, uint32_t x, uint32_t mbar) {
  asm volatile("st.async.weak.shared::cluster.mbarrier::complete_tx::bytes.b32 [%0 + %3], %1, [%2];" ::"r"(a), "r"(x), "r"(mbar), "n"(OFF) : "memory");
}
__device__ __forceinline__ uint4 ld_rlx128(const void* p) {
  uint4 v;
  asm volatile("ld.relaxed.gpu.global.v4.u32 {%0,%1,%2,%3}, [%4];" : "=r"(v.x), "=r"(v.y), "=r"(v.z), "=r"(v.w) : "l"(p) : "memory");
  return v;
}
__device__ __forceinline__ uint2 ld_rlx64(const void* p) {
  uint2 v; asm volatile("ld.relaxed.gpu.global.v2.u32 {%0,%1}, [%2];" : "=r"(v.x), "=r"(v.y) : "l"(p) : "memory"); return v;
}
__device__ __forceinline__ uint32_t ld_rlx32(const void* p) {
  uint32_t v; asm volatile("ld.relaxed.gpu.global.u32 %0, [%1];" : "=r"(v) : "l"(p) : "memory"); return v;
}
__device__ __forceinline__ void st_rlx32(void* p, uint32_t a) { asm volatile("st.relaxed.gpu.global.u32 [%0], %1;" ::"l"(p), "r"(a) : "memory"); }
__device__ __forceinline__ void red_release(uint32_t* p) { asm volatile("red.release.gpu.global.add.u32 [%0], 1;" ::"l"(p) : "memory"); }
__device__ __forceinline__ void st_release32(void* p, uint32_t a) { asm volatile("st.release.gpu.global.u32 [%0], %1;" ::"l"(p), "r"(a) : "memory"); }
__device__ __forceinline__ void st_release_u64(void* p, u64 a) { asm volatile("st.release.gpu.global.u64 [%0], %1;" ::"l"(p), "l"(a) : "memory"); }
__device__ __forceinline__ void wait_count(const uint32_t* p, uint32_t val, int code) {
  int it = 0;
  while (ld_rlx32(p) < val) {
    give_up(++it, SPIN_LIMIT, code);
    warp_sleep(SLP_C);
  }
}
__device__ __forceinline__ u64 wait_keys(const u64* keys, int lane, int code) {
  u64 k;
  int it = 0;
  while (true) {
    asm volatile("ld.relaxed.gpu.global.u64 %0, [%1];" : "=l"(k) : "l"(keys + lane) : "memory");
    if (__all_sync(~0u, k != 0)) break;
    give_up(++it, SPIN_LIMIT, code);
    warp_sleep(SLP_K);
  }
  const uint32_t hi = __reduce_max_sync(~0u, (uint32_t)(k >> 32));
  const uint32_t lo = __reduce_max_sync(~0u, (uint32_t)(k >> 32) == hi ? (uint32_t)k : 0u);
  return (u64)hi << 32 | lo;
}
__device__ __forceinline__ int key_token(u64 k) { return (int)(~(uint32_t)k) & (NTOK - 1); }
__device__ __forceinline__ float key_score(u64 k) {
  const uint32_t ob = (uint32_t)(k >> 32);
  return __uint_as_float((ob & 0x80000000u) ? (ob & 0x7fffffffu) : ~ob);
}

__device__ __forceinline__ uint64_t mk_desc(uint32_t saddr, uint32_t lbo, uint32_t sbo, uint32_t sw) {
  return (uint64_t)((saddr & 0x3FFFF) >> 4) | (uint64_t)(lbo >> 4) << 16 | (uint64_t)(sbo >> 4) << 32 | (uint64_t)sw << 62;
}
template <int N> __device__ __forceinline__ void reg_inc() { asm volatile("setmaxnreg.inc.sync.aligned.u32 %0;" ::"n"(N)); }
template <int N> __device__ __forceinline__ void reg_dec() { asm volatile("setmaxnreg.dec.sync.aligned.u32 %0;" ::"n"(N)); }
__device__ __forceinline__ void wg_fence() { asm volatile("wgmma.fence.sync.aligned;" ::: "memory"); }
__device__ __forceinline__ void wg_commit() { asm volatile("wgmma.commit_group.sync.aligned;" ::: "memory"); }
template <int N> __device__ __forceinline__ void wg_wait() { asm volatile("wgmma.wait_group.sync.aligned %0;" ::"n"(N) : "memory"); }
template <int N> __device__ __forceinline__ void acc_fence(float (&d)[N]) {
#pragma unroll
  for (int i = 0; i < N; i++) asm volatile("" : "+f"(d[i]) :: "memory");
}
#define O4(d, i) "+f"(d[i]), "+f"(d[i + 1]), "+f"(d[i + 2]), "+f"(d[i + 3])
template <int TB, int ACC>
__device__ __forceinline__ void wg_rs24(float (&d)[12], const uint32_t (&a)[4], uint64_t db) {
  asm volatile("wgmma.mma_async.sync.aligned.m64n24k16.f32.bf16.bf16 {%0,%1,%2,%3,%4,%5,%6,%7,%8,%9,%10,%11}, {%12,%13,%14,%15}, %16, %17, 1, 1, %18;"
               : O4(d, 0), O4(d, 4), O4(d, 8) : "r"(a[0]), "r"(a[1]), "r"(a[2]), "r"(a[3]), "l"(db), "n"(ACC), "n"(TB));
}
template <int TB, int ACC>
__device__ __forceinline__ void wg_rs32(float (&d)[16], const uint32_t (&a)[4], uint64_t db) {
  asm volatile("wgmma.mma_async.sync.aligned.m64n32k16.f32.bf16.bf16 {%0,%1,%2,%3,%4,%5,%6,%7,%8,%9,%10,%11,%12,%13,%14,%15}, {%16,%17,%18,%19}, %20, %21, 1, 1, %22;"
               : O4(d, 0), O4(d, 4), O4(d, 8), O4(d, 12) : "r"(a[0]), "r"(a[1]), "r"(a[2]), "r"(a[3]), "l"(db), "n"(ACC), "n"(TB));
}
template <int ACC>
__device__ __forceinline__ void wg_rs64(float (&d)[32], uint32_t a0, uint32_t a1, uint32_t a2, uint32_t a3, uint64_t db) {
  asm volatile("wgmma.mma_async.sync.aligned.m64n64k16.f32.bf16.bf16 {%0,%1,%2,%3,%4,%5,%6,%7,%8,%9,%10,%11,%12,%13,%14,%15,"
               "%16,%17,%18,%19,%20,%21,%22,%23,%24,%25,%26,%27,%28,%29,%30,%31}, {%32,%33,%34,%35}, %36, %37, 1, 1, 0;"
               : O4(d, 0), O4(d, 4), O4(d, 8), O4(d, 12), O4(d, 16), O4(d, 20), O4(d, 24), O4(d, 28)
               : "r"(a0), "r"(a1), "r"(a2), "r"(a3), "l"(db), "n"(ACC));
}
template <int ACC>
__device__ __forceinline__ void wg_ss24(float (&d)[12], uint64_t da, uint64_t db) {
  asm volatile("wgmma.mma_async.sync.aligned.m64n24k16.f32.bf16.bf16 {%0,%1,%2,%3,%4,%5,%6,%7,%8,%9,%10,%11}, %12, %13, %14, 1, 1, 1, 0;"
               : O4(d, 0), O4(d, 4), O4(d, 8) : "l"(da), "l"(db), "n"(ACC));
}
template <int ACC>
__device__ __forceinline__ void wg_rs40(float (&d)[20], const uint32_t (&a)[4], uint64_t db) {
  asm volatile("wgmma.mma_async.sync.aligned.m64n40k16.f32.bf16.bf16 {%0,%1,%2,%3,%4,%5,%6,%7,%8,%9,%10,%11,%12,%13,%14,%15,%16,%17,%18,%19}, {%20,%21,%22,%23}, %24, %25, 1, 1, 1;"
               : O4(d, 0), O4(d, 4), O4(d, 8), O4(d, 12), O4(d, 16) : "r"(a[0]), "r"(a[1]), "r"(a[2]), "r"(a[3]), "l"(db), "n"(ACC));
}

struct Row { uint32_t w[8]; };
__device__ __forceinline__ uint32_t add_bf16x2(uint32_t a, uint32_t b) {
  uint32_t d; asm("add.rn.bf16x2 %0, %1, %2;" : "=r"(d) : "r"(a), "r"(b)); return d;
}
__device__ __forceinline__ Row warp_ln(const Row& r, float& extra) {
  float x[16];
#pragma unroll
  for (int i = 0; i < 8; i++) { x[2 * i] = bf_lo(r.w[i]); x[2 * i + 1] = bf_hi(r.w[i]); }
  float m = (((x[0] + x[1]) + (x[2] + x[3])) + ((x[4] + x[5]) + (x[6] + x[7]))) + (((x[8] + x[9]) + (x[10] + x[11])) + ((x[12] + x[13]) + (x[14] + x[15])));
  m *= (1.f / 16);
  float v0 = 0.f, v1 = 0.f;
#pragma unroll
  for (int i = 0; i < 16; i += 2) { const float d0 = x[i] - m, d1 = x[i + 1] - m; v0 = fmaf(d0, d0, v0); v1 = fmaf(d1, d1, v1); }
  float v = v0 + v1;
#pragma unroll
  for (int o = 1; o <= 16; o <<= 1) {
    const float mo = __shfl_xor_sync(~0u, m, o), vo = __shfl_xor_sync(~0u, v, o);
    extra += __shfl_xor_sync(~0u, extra, o);
    const float d = mo - m;
    v = fmaf(d * d, 8.f * o, v + vo);
    m = 0.5f * (m + mo);
  }
  const float var = fmaf(v, 1.f / DM, 1e-5f);
  float rs = rsqrtf(var);
  rs = rs * fmaf(-0.5f * var * rs, rs, 1.5f);
  Row y;
#pragma unroll
  for (int i = 0; i < 8; i++) y.w[i] = pack_bf16((x[2 * i] - m) * rs, (x[2 * i + 1] - m) * rs);
  return y;
}
__device__ __forceinline__ Row warp_ln(const Row& r) { float e = 0.f; return warp_ln(r, e); }
__device__ __forceinline__ Row load_row(const bf16* p, int lane) {
  Row r;
#pragma unroll
  for (int q = 0; q < 4; q++) { const uint2 v = ld_rlx64(p + lane * 4 + q * 128); r.w[2 * q] = v.x; r.w[2 * q + 1] = v.y; }
  return r;
}
__device__ __forceinline__ void store_row_img(uint8_t* img, int rr, int lane, const Row& r) {
  uint8_t* p = img + (lane >> 4) * 4096 + rr * 128 + ((((lane & 15) >> 1) ^ (rr & 7)) << 4) + (lane & 1) * 8;
#pragma unroll
  for (int q = 0; q < 4; q++) *(uint2*)(p + q * 8192) = make_uint2(r.w[2 * q], r.w[2 * q + 1]);
}

constexpr int C_WO = 0;
constexpr int C_X = 49152;
constexpr int C_M = C_X + 65536;
constexpr int C_Q = C_M + 24576;
constexpr int C_K = C_Q + 10240, C_V = C_K + 10240;
constexpr int C_SA = C_V + 10240, C_SB = C_SA + 8192;
constexpr int C_O = C_SB + 8192;
constexpr int C_OT = C_O + 6144;
constexpr int C_PI = C_OT + 16384;
constexpr int C_BAR = C_PI + 8192;
constexpr int C_SMEM = C_BAR + 384 + 1024 + TREXTRA;
constexpr int C_STG = C_X + 32768;
static_assert(C_STG + 131072 <= C_BAR, "staging");
enum { B_M0 = 0, B_M1, B_M2, B_R, B_X = B_R + 4, B_O, B_T, B_F, B_XL, B_U, B_P1, B_P2, B_OT, B_XF, B_XA, B_I, B_PI, B_J, B_W, B_WO, B_NUM };
static_assert(B_NUM <= 24, "barriers");
constexpr int C_POL = C_BAR + 192, C_INFO = C_BAR + 208;
enum { NB_ALL = 0, NB_M0, NB_PV, NB_W0, NB_TA, NB_X1, NB_M1, NB_M2, NB_RD, NB_V, NB_SM, NB_C };
constexpr float SCALE_LOG2E = 0.08838834764831845f * 1.4426950408889634f;
#define N0STEPS 9
#define N2STEPS 12
#define FGATE 1
#define NSSTEPS 0
constexpr int KA = 32 - NSSTEPS - N2STEPS, K3 = KA - N0STEPS;
static_assert(KA % 4 == 0, "the rows of layer 1 are refilled in two parts");
#define BGATE 0
#define W0EARLY 0
#define PVEARLY 1
#define S1GATE 0
#define IGRP 0
#define SHIPLATE 7
#define SHIP 1024
#define GATE_P 2250
#define GATE_W 170
#define EXPF 0
#define GATE_G 200
#define GATE_M 3230
#define HOLE0 22
#define HOLE1 28
#define HOLE2 32
__device__ __forceinline__ uint32_t gtime() { uint32_t t; asm volatile("mov.u32 %0, %%globaltimer_lo;" : "=r"(t) :: "memory"); return t; }
__device__ __forceinline__ void wait_clock(uint32_t t) {
  asm volatile("{ .reg .pred p; .reg .b32 c; .reg .b64 cc;\nL: mov.u64 cc, %%clock64; cvt.u32.u64 c, cc; sub.u32 c, c, %0; setp.lt.s32 p, c, 0; @p bra L; }" ::"r"(t) : "memory");
}
__device__ __forceinline__ void bar_sync_z(int id, int n, uint32_t z) {
  asm volatile("{ .reg .pred p; setp.eq.u32 p, %2, 0; @p bar.sync %0, %1; }" ::"r"(id), "r"(n), "r"(z) : "memory");
}

__device__ __forceinline__ int probe_home(uint32_t* p, int lane) {
  uint32_t best[2] = {~0u, ~0u};
#pragma unroll 1
  for (int rep = 0; rep < 3; rep++) {
#pragma unroll
    for (int pg = 0; pg < 2; pg++) {
      uint32_t t0, t1, v = 0;
      asm volatile("mov.u32 %0, %%clock;" : "=r"(t0) :: "memory");
      asm volatile("{ .reg .pred p; setp.eq.u32 p, %2, 0; @p atom.relaxed.gpu.global.exch.b32 %0, [%1], %3; }" : "+r"(v) : "l"(p + pg * 1024), "r"(lane), "r"(rep) : "memory");
      asm volatile("{ .reg .pred p; setp.ne.u32 p, %1, 0x13572468; mov.u32 %0, 0; @p mov.u32 %0, %%clock; }" : "=r"(t1) : "r"(v) : "memory");
      best[pg] = min(best[pg], t1 - t0);
    }
  }
  return __shfl_sync(~0u, max(-150, min(150, (int)(best[1] - best[0]))), 0);
}
__device__ __forceinline__ uint32_t home_flip(const void* p) { const uint32_t a = (uint32_t)(size_t)p; return ((a >> 16) ^ (a >> 17) ^ (a >> 19)) & 1; }
__device__ __forceinline__ uint32_t ppage(uint32_t lp, uint32_t pol) { return lp ? 3 - pol : pol; }
__device__ __forceinline__ uint32_t and_x(uint32_t a, uint32_t b, uint32_t m) {
  uint32_t d; asm("lop3.b32 %0, %1, %2, %3, 0x42;" : "=r"(d) : "r"(a), "r"(b), "r"(m)); return d;
}
__device__ __forceinline__ uint32_t and3(uint32_t a, uint32_t b, uint32_t c) {
  uint32_t d; asm("lop3.b32 %0, %1, %2, %3, 0x80;" : "=r"(d) : "r"(a), "r"(b), "r"(c)); return d;
}

template <int N> struct IC { static constexpr int value = N; };
template <class F> __device__ __forceinline__ void static_for2(F f) { f(IC<0>()); f(IC<1>()); }
template <class F> __device__ __forceinline__ void static_for3(F f) { f(IC<0>()); f(IC<1>()); f(IC<2>()); }
__device__ __forceinline__ void stage_weights(uint32_t stage, const CUtensorMap* map, int col, int row, uint32_t mbar) {
  mbar_expect_tx(mbar, 131072);
#pragma unroll 1
  for (int i = 0; i < 4; i++)
    asm volatile("cp.async.bulk.tensor.2d.shared::cluster.global.mbarrier::complete_tx::bytes [%0], [%1, {%3, %4}], [%2];"
                 ::"r"(stage + (i & 1) * 65536 + (i >> 1) * 32768), "l"(map), "r"(mbar), "r"(col + (i & 1) * 64), "r"(row + (i >> 1) * 256) : "memory");
}
__device__ __forceinline__ void load_wfrags(uint32_t (&wA)[32][4], uint32_t stage, int w, int lane) {
  const int mi = lane >> 3, r = lane & 7;
  const uint32_t a = stage + (w >> 2) * 65536 + ((mi >> 1) * 8 + r) * 128 + ((((w & 3) * 2 + (mi & 1)) ^ r) << 4);
#pragma unroll
  for (int ks = 0; ks < 32; ks++) ldsm4t(wA[ks], a + ks * 2048);
}
template <int K0, int K1>
__device__ __forceinline__ void tok_seq(float (&d)[16], const uint32_t (&wA)[32][4], uint64_t desc, uint32_t wave) {
#pragma unroll
  for (int k = K0; k < K1; k++) {
    const int ks = k & 31;
    constexpr int HM0 = 1, HM1 = 2, HM2 = 4;
    const int hm = (k == HOLE0 ? HM0 : 0) | (k == HOLE1 ? HM1 : 0) | (k == HOLE2 ? HM2 : 0);
    if (hm) bar_sync_z(NB_RD, 384, ((hm >> wave) & 1) ^ 1);
    if (ks == 0) wg_rs32<0, 0>(d, wA[ks], desc);
    else wg_rs32<0, 1>(d, wA[ks], desc + (ks >> 2) * 256 + (ks & 3) * 2);
  }
}
template <int K0, int K1>
__device__ __forceinline__ void mem_part(float (&d)[12], const uint32_t (&wA)[32][4], uint64_t desc) {
#pragma unroll
  for (int ks = K0; ks < K1; ks++) {
    if (ks == 0) wg_rs24<1, 0>(d, wA[ks], desc);
    else wg_rs24<1, 1>(d, wA[ks], desc + ks * 48);
  }
}
__device__ __forceinline__ void out_tile(float (&d)[12], uint64_t da, uint64_t db) {
#pragma unroll
  for (int i = 0; i < 8; i++) { if (i == 0) wg_ss24<0>(d, da, db); else wg_ss24<1>(d, da + i * 128, db + (i >> 1) * 32 + (i & 1) * 2); }
}
__device__ __forceinline__ void tok_pack(uint32_t (&p)[8], const float (&d)[16]) {
#pragma unroll
  for (int i = 0; i < 8; i++) p[i] = pack_bf16(d[2 * i], d[2 * i + 1]);
}
__device__ __forceinline__ void tok_store(uint32_t dst, const uint32_t (&p)[8]) {
  stsm4(dst, p[0], p[1], p[2], p[3]);
  stsm4(dst + 4096, p[4], p[5], p[6], p[7]);
}
template <class T> __device__ __forceinline__ T keep(T v) { asm volatile("" : "+r"(v)); return v; }
__device__ __forceinline__ uint32_t pin(uint32_t v) { return __shfl_sync(~0u, v, threadIdx.x & 31); }

#define TRC blockIdx.x
#define TRS (C_BAR + 384)
__device__ __forceinline__ void chain_proj(const uint32_t sb, const int w, const int lane_, const uint32_t rank) {
  uint32_t wA[32][4];
  mbar_wait(sb + C_BAR + B_W * 8, 0, 30);
  if (w == 0) { HD(2) }
  load_wfrags(wA, sb + C_STG, w, lane_);
  bar_arrive(NB_ALL, 384);
  const int lane = pin(lane_);
  const uint32_t bars = sb + C_BAR;
  const uint32_t quad = pin(sb + (lane_ >> 4) * 2048 + (lane_ & 15) * 16);
  const uint32_t own = C_Q + rank * 10240;
  const uint64_t dX1 = mk_desc(sb + C_X, 16, 1024, 1), dX2 = dX1 + 2048;
  const uint64_t dM = mk_desc(sb + C_M, 128, 256, 0);
  const uint32_t r1 = rank == 0 ? 1 : 0, r2 = rank == 2 ? 1 : 2;
  const uint32_t xa = pin(sb + own + 8192 + w * 256 + lane_ * 4);
  const uint32_t a1x = pin(mapa_u32(xa, r1)), a2x = pin(mapa_u32(xa, r2));
  const uint32_t b1x = pin(mapa_u32(bars + B_X * 8, r1)), b2x = pin(mapa_u32(bars + B_X * 8, r2));
  const uint32_t wave = rank == 2 ? 0 : rank + 1;
  float a[16];
  bar_sync(NB_X1, 288);
  wg_fence();
  tok_seq<32, 32 + KA>(a, wA, mk_desc(__shfl_sync(~0u, sb, 0) + C_X, 16, 1024, 1), 3);
  wg_commit();
  wg_wait<0>();
  mbar_arrive_z(bars + B_XA * 8, lane);
#pragma unroll 1
  for (int st = 0;; st++) {
    uint32_t pk[8];
    wg_fence();
    if (NSSTEPS) bar_sync(NB_SM, 416);
    tok_seq<32 + KA, 32 + KA + NSSTEPS>(a, wA, dX1, 3);
    bar_sync(NB_PV, NSSTEPS ? 384 : 416);
    tok_seq<32 + KA + NSSTEPS, 64>(a, wA, dX1, 3);
    wg_commit();
    wg_wait<0>();
    acc_fence(a);
    mbar_arrive_z(bars + B_XF * 8, lane);
    tok_pack(pk, a);
    TR(1)
    bar_sync(NB_W0, 416);
    tok_store(quad + w * 256 + (rank == 0 ? own : C_SA), pk);
    __syncwarp();
    mbar_arrive_z(bars + B_P1 * 8, lane);
    wg_fence();
    tok_seq<0, 32>(a, wA, dX2, wave);
    wg_commit();
    const uint32_t info = lds32(sb + C_INFO + (st & 1) * 4);
    TR(2)
    wg_wait<0>();
    acc_fence(a);
    TR(3)
    tok_pack(pk, a);
    tok_store(quad + w * 256 + (rank == 0 ? C_SA : own), pk);
    if (rank == 2) tok_store(quad + w * 256 + C_SB, pk);
    __syncwarp();
    mbar_arrive_z(bars + B_P2 * 8, lane);
    TR(4)
    wg_fence();
    tok_seq<32, 32 + K3>(a, wA, dX1, wave);
    TR(6)
    {
      float am[12];
      bar_sync(NB_M0, 384);
      mem_part<0, 10>(am, wA, dM);
      TR(7)
      bar_sync(NB_M1, 384);
      mem_part<10, 21>(am, wA, dM);
      bar_sync(NB_M2, 384);
      mem_part<21, 32>(am, wA, dM);
      wg_commit();
      bar_sync(NB_V, 384);
      const bool redo = __any_sync(~0u, lds32(sb + C_INFO + 16 + (lane & 3) * 32) != 0);
      if (__builtin_expect(redo, 0)) {
        wg_wait<0>();
        wg_fence();
        mem_part<0, 32>(am, wA, dM);
        wg_commit();
      }
      wg_wait<0>();
      acc_fence(am);
      TR(8)
      const uint32_t x00 = pack_bf16(am[0], am[1]), x01 = pack_bf16(am[2], am[3]), x10 = pack_bf16(am[4], am[5]), x11 = pack_bf16(am[6], am[7]);
      const uint32_t y0 = pack_bf16(am[8], am[9]), y1 = pack_bf16(am[10], am[11]), x20 = info ? x10 : y0, x21 = info ? x11 : y1;
      st_async32<0>(a1x, rank == 0 ? x10 : x00, b1x); st_async32<0>(a2x, rank == 2 ? x10 : x20, b2x);
      st_async32<128>(a1x, rank == 0 ? x11 : x01, b1x); st_async32<128>(a2x, rank == 2 ? x11 : x21, b2x);
      sts32(xa, rank == 0 ? x00 : rank == 2 ? x20 : x10); sts32(xa + 128, rank == 0 ? x01 : rank == 2 ? x21 : x11);
      if (__builtin_expect(info, 0)) {
        const uint32_t o = (info & 3) * 2048 - 8192;
        if (rank == 2) { sts32(xa + o, y0); sts32(xa + o + 128, y1); }
        else { st_async32<0>(a2x + o, y0, b2x + (B_T - B_X) * 8); st_async32<128>(a2x + o, y1, b2x + (B_T - B_X) * 8); }
      }
      __syncwarp();
      mbar_arrive_z(bars + B_X * 8, lane);
    }
    TR(9)
    wg_fence();
    tok_seq<32 + K3, 32 + KA>(a, wA, dX1, 3);
    wg_commit();
    TR(0)
    wg_wait<0>();
    if (st == NSTEP - 1) break;
    mbar_arrive_z(bars + B_XA * 8, lane);
  }
  if (NSSTEPS) bar_arrive(NB_SM, 416);
  bar_arrive(NB_PV, NSSTEPS ? 384 : 416);
}

__device__ __forceinline__ void chain_mem(const uint32_t sb, const int w, const int lane_, const uint32_t rank, const int h,
                                          const bf16* __restrict__ mem0) {
  const int lane = pin(lane_);
  const int wave = rank == 2 ? 0 : rank + 1;
  const int c = w - 8, t = c * 32 + lane, b = wave * 32 + h;
  const uint32_t bars = sb + C_BAR;
  const int wi = (lane & 1) * 2 + (lane >> 4), cq = (lane >> 2) & 3;
  mbar_expect_tx_z(bars + B_X * 8, 4096, t); mbar_expect_tx_z(bars + B_O * 8, 4096, t);
  if (NSSTEPS) bar_arrive(NB_SM, 416);
  bar_arrive(NB_PV, NSSTEPS ? 384 : 416); bar_arrive(NB_W0, 416); bar_arrive(NB_RD, 384);
  uint32_t m0[16];
#pragma unroll
  for (int i = 0; i < 16; i++) m0[i] = *(const uint32_t*)(mem0 + (lane >> 2) * DM + (c * 16 + i) * 8 + (lane & 3) * 2);
  uint32_t* pp = g_M + c * 16384 + 14 * 1024 + (blockIdx.x & 31) * 32;
  st_rlx32(pp + lane, 0); st_rlx32(pp + 1024 + lane, 0);
  bar_sync(NB_ALL, 384);
  if (c == 0) { HD(3) }
  mbar_arrive_remote_z(mapa_u32(bars + B_F * 8, (rank + 1 + (t & 1)) % 3), t >> 1);
#pragma unroll
  for (int i = 0; i < 16; i += 4) {
    const uint32_t a = sb + C_M + (c * 8 + i / 2 + (lane >> 4)) * 768 + (lane & 15) * 16;
    stsm4t(a, m0[i], m0[i + 1], m0[i + 2], m0[i + 3]); stsm4t(a + 256, m0[i], m0[i + 1], m0[i + 2], m0[i + 3]); stsm4t(a + 512, m0[i], m0[i + 1], m0[i + 2], m0[i + 3]);
  }
  sts32(sb + C_INFO + 16 + c * 32, 0);
  fence_async_smem();
  bar_arrive(NB_M0, 384); bar_arrive(NB_M1, 384); bar_arrive(NB_M2, 384);
  mbar_wait(bars + B_F * 8, 0, 34);
  bar_arrive(NB_V, 384);
  mbar_wait(bars + B_WO * 8, 0, 33);
  {
    uint32_t* p = pp;
    const int vote = probe_home(p, lane);
    sts32(sb + C_POL + c * 4, home_flip(p) ? -vote : vote);
    bar_sync(NB_C, 128);
    const uint4 v = lds128(sb + C_POL);
    const uint32_t side = (int)(v.x + v.y + v.z + v.w) > 0;
    bar_sync(NB_C, 128);
    sts32(sb + C_POL + c * 4, side ^ home_flip(p));
    sts32(sb + C_INFO + 8, side ^ home_flip(g_P + b * 4096));
    if (c == 0) { HD(0) }
    wait_count(g_ex.ready, 96, 35);
    if (c == 0) { HD(1) }
    st_rlx32(&g_fl.pol[b], (side ^ home_flip(g_P + b * 4096)) + 1);
  }
  uint32_t pgbits, polP;
  {
    const int tl = lane / 3, u = ((tl * 3 + rank) * 4 + c) * 3 + (lane - tl * 3);
    uint32_t pol;
    int it = 0;
    do { pol = ld_rlx32(&g_fl.pol[lane < 9 && u < 96 ? u : b]); give_up(it++, SPIN_LIMIT, 40); } while (__any_sync(~0u, pol == 0));
    pgbits = __reduce_or_sync(~0u, lane < 9 ? ppage(h >> 4, (pol - 1) & 1) << (2 * lane) : 0u);
    polP = __shfl_sync(~0u, pol - 1, 9);
  }
  const int mi = lane >> 3;
  const uint32_t l16 = pin(sb + lane * 16);
  const uint32_t r1 = rank == 2 ? 0 : rank + 1, r2 = rank == 0 ? 2 : rank - 1;
  const uint32_t oa = pin(sb + C_O + rank * 2048 + (lane >> 2) * 64 + (((lane & 3) ^ (lane >> 3)) << 4));
  const uint32_t a1 = mapa_u32(oa, r1), b1 = mapa_u32(bars + B_O * 8, r1), a2 = mapa_u32(oa, r2), b2 = mapa_u32(bars + B_O * 8, r2);
  const uint64_t dWo = mk_desc(sb + C_WO, 8192, 1024, 1), dO = mk_desc(sb + C_O, 16, 2048, 2);
  const uint64_t dK = mk_desc(sb + C_K, 128, 2048, 0);
  const uint64_t dV = mk_desc(sb + C_V, 2048, 128, 0), dVm = mk_desc(sb + C_V + 8192, 0, 128, 0);
  const uint32_t qa = pin(sb + C_Q + (c ? c + 1 : mi & 1) * 2048 + (mi >> 1) * 128 + (lane & 7) * 16);
  const uint32_t dg = ((lane >> 2) < 2 * (lane & 3) ? 1 : 0) | ((lane >> 2) < 2 * (lane & 3) + 1 ? 2 : 0);
  const uint32_t msk = pin(c == 0 ? dg | dg << 4 : c == 1 ? dg << 2 | 3 << 4 : c == 2 ? dg << 4 : 0);
  uint8_t* Pw = (uint8_t*)g_P + (rank * 4 + c) * 3 * 16384 + (h & 15) * 256 + ((lane * 4) ^ ((h & 3) << 5));
  const uint32_t pia = pin(sb + C_PI + ((lane >> 4) * 4 + (lane & 3)) * 256 + ((c * 64 + cq * 16) ^ ((lane & 3) << 5)));
  uint8_t* Mw = (uint8_t*)g_M + (b >> 5) * 16384 + ((lane & 2) ? 4096 : 12288) + (b & 31) * 256 + c * 64 + cq * 16 + wi * 4;
  uint32_t nretry = 0, nupd = 0;

  { const int st = 71; (void)st; STAT(0, lds32(sb + C_POL + c * 4)) STAT(1, polP) STAT(2, (uint32_t)(size_t)(g_M + c * 16384)) STAT(3, (uint32_t)(size_t)(g_P + b * 4096)) }
#pragma unroll 1
  for (int st = 0;; st++) {
    mbar_wait(bars + B_P1 * 8, st & 1, 38);
    mbar_wait(bars + B_T * 8, st & 1, 42);
    STAT(10, clk32())
    {
      float s[20];
      {
        uint32_t q[8][4];
        if (c == 3) mbar_wait(bars + B_X * 8, st & 1, 41);
#pragma unroll
        for (int i = 0; i < 8; i++) ldsm4t(q[i], qa + i * 256);
        if (c != 3) { mbar_wait(bars + B_X * 8, st & 1, 41); fence_async_smem(); }
        STAT(11, clk32())
        TR(0)
        wg_fence();
#pragma unroll
        for (int i = 0; i < 8; i++) { if (i == 0) wg_rs40<0>(s, q[i], dK); else wg_rs40<1>(s, q[i], dK + i * 16); }
        wg_commit();
        wg_wait<0>();
        if (NSSTEPS) bar_arrive(NB_SM, 416);
        acc_fence(s);
      }
      TR(1)
      const bool w0 = c == 0;
      float z[10] = {s[16], s[17], s[0], s[1], w0 ? s[18] : s[4], w0 ? s[19] : s[5], w0 ? s[2] : s[8], w0 ? s[3] : s[9], w0 ? s[6] : s[12], w0 ? s[7] : s[13]};
      if (msk & 1) z[2] = -INFINITY;
      if (msk & 2) z[3] = -INFINITY;
      if (msk & 4) z[6] = -INFINITY;
      if (msk & 8) z[7] = -INFINITY;
      if (msk & 16) z[8] = -INFINITY;
      if (msk & 32) z[9] = -INFINITY;
      float m0 = fmaxf(fmaxf(z[0], z[1]), fmaxf(z[2], z[3])), m1 = fmaxf(fmaxf(fmaxf(z[4], z[5]), fmaxf(z[6], z[7])), fmaxf(z[8], z[9]));
      m0 = fmaxf(m0, __shfl_xor_sync(~0u, m0, 1)); m1 = fmaxf(m1, __shfl_xor_sync(~0u, m1, 1));
      m0 = fmaxf(m0, __shfl_xor_sync(~0u, m0, 2)); m1 = fmaxf(m1, __shfl_xor_sync(~0u, m1, 2));
      if (!w0) m0 = m1 = fmaxf(m0, m1);
      m0 *= -SCALE_LOG2E; m1 *= -SCALE_LOG2E;
      uint32_t p[5];
#pragma unroll
      for (int k = 0; k < 5; k++) {
        z[2 * k] = ex2_fast(fmaf(z[2 * k], SCALE_LOG2E, k < 2 ? m0 : m1)); z[2 * k + 1] = ex2_fast(fmaf(z[2 * k + 1], SCALE_LOG2E, k < 2 ? m0 : m1));
        p[k] = pack_bf16(z[2 * k], z[2 * k + 1]);
      }
      const uint32_t p2 = w0 ? 0 : p[2], p3 = w0 ? 0 : p[3], p4 = w0 ? 0 : p[4];
      float oA[32], oB[32];
      wg_fence();
      wg_rs64<0>(oA, p[0], p[2], 0, 0, dVm); wg_rs64<1>(oA, p[1], p[3], p2, p[4], dV); wg_rs64<1>(oA, p3, 0, p4, 0, dV + 256);
      wg_commit();
      wg_rs64<0>(oB, p[0], p[2], 0, 0, dVm + 64); wg_rs64<1>(oB, p[1], p[3], p2, p[4], dV + 64); wg_rs64<1>(oB, p3, 0, p4, 0, dV + 320);
      wg_commit();
      float l0 = (z[0] + z[1]) + (z[2] + z[3]), l1 = ((z[4] + z[5]) + (z[6] + z[7])) + (z[8] + z[9]);
      if (!w0) l0 += l1;
      l0 += __shfl_xor_sync(~0u, l0, 1); l1 += __shfl_xor_sync(~0u, l1, 1);
      l0 += __shfl_xor_sync(~0u, l0, 2); l1 += __shfl_xor_sync(~0u, l1, 2);
      float i0, i1;
      asm volatile("rcp.approx.ftz.f32 %0, %2; rcp.approx.ftz.f32 %1, %3;" : "=f"(i0), "=f"(i1) : "f"(l0), "f"(l1));
      asm volatile("st.shared.v2.f32 [%0], {%1,%2};" ::"r"(sb + C_INFO + 24), "f"(i0), "f"(i1) : "memory");
      const uint32_t ta = l16 + C_OT + (st & 1) * 8192 + (c ? c + 1 : 0) * 2048;
      auto leave = [&](const float (&o)[32], auto hc) {
        constexpr int H = decltype(hc)::value;
        uint32_t e[8];
#pragma unroll
        for (int j = 0; j < 8; j++) e[j] = pack_bf16(o[4 * j] * i0, o[4 * j + 1] * i0);
        if (c == 3) {
          static_for2([&](auto bc) {
            constexpr int B = decltype(bc)::value;
            asm volatile("st.async.weak.shared::cluster.mbarrier::complete_tx::bytes.v4.b32 [%0 + %9], {%5,%6,%7,%8}, [%1];\n"
                         "st.async.weak.shared::cluster.mbarrier::complete_tx::bytes.v4.b32 [%2 + %9], {%5,%6,%7,%8}, [%3];\n"
                         "st.shared.v4.b32 [%4 + %9], {%5,%6,%7,%8};"
                         ::"r"(a1), "r"(b1), "r"(a2), "r"(b2), "r"(oa), "r"(e[4 * B]), "r"(e[4 * B + 1]), "r"(e[4 * B + 2]), "r"(e[4 * B + 3]),
                           "n"(H * 1024 + B * 512) : "memory");
          });
        } else {
          stsm4(ta + H * 1024, e[0], e[1], e[2], e[3]); stsm4(ta + H * 1024 + 512, e[4], e[5], e[6], e[7]);
          if (w0) {
#pragma unroll
            for (int j = 0; j < 8; j++) e[j] = pack_bf16(o[4 * j + 2] * i1, o[4 * j + 3] * i1);
            stsm4(ta + 2048 + H * 1024, e[0], e[1], e[2], e[3]); stsm4(ta + 2048 + H * 1024 + 512, e[4], e[5], e[6], e[7]);
          }
        }
      };
      wg_wait<1>();
      acc_fence(oA);
      leave(oA, IC<0>());
      wg_wait<0>();
      if (PVEARLY) bar_arrive(NB_PV, NSSTEPS ? 384 : 416);
      acc_fence(oB);
      leave(oB, IC<1>());
      if (!PVEARLY) bar_arrive(NB_PV, NSSTEPS ? 384 : 416);
      __syncwarp();
      mbar_arrive_z(bars + (c == 3 ? B_O : B_OT) * 8, lane);
      TR(2)
    }
    mbar_wait(bars + B_O * 8, st & 1, 43);
    if (st == NSTEP - 1) break;
    uint32_t info;
    {
      const uint32_t tag = (st & 1) ^ 1;
      float oc0[12], oc1[12], oc2[12];
      fence_async_smem();
      TR(3)
      wg_fence();
      out_tile(oc0, dWo, dO);
      wg_commit();
      out_tile(oc1, dWo + 1024, dO);
      wg_commit();
      asm volatile("" : "+r"(pgbits));
      auto put = [&](const float (&oc)[12], auto tlc) {
        constexpr int TL = decltype(tlc)::value;
        static_for3([&](auto jc) {
          constexpr int j = decltype(jc)::value;
          uint8_t* p = Pw + ((pgbits >> (2 * (TL * 3 + j))) & 3) * 4096;
          asm volatile("st.relaxed.gpu.global.u32 [%0 + %3], %1; st.relaxed.gpu.global.u32 [%0 + %3 + 128], %2;" ::"l"(p),
                       "r"((pack_bf16(oc[4 * j], oc[4 * j + 1]) & ~1u) | tag), "r"((pack_bf16(oc[4 * j + 2], oc[4 * j + 3]) & ~1u) | tag),
                       "n"((TL * 36 + j) * 16384) : "memory");
        });
      };
      wg_wait<1>();
      acc_fence(oc0);
      put(oc0, IC<0>());
      sts32(sb + C_INFO + 24, clk32());
      TR(4)
      out_tile(oc2, dWo + 2048, dO);
      wg_commit();
      wg_wait<1>();
      acc_fence(oc1);
      put(oc1, IC<1>());
      if (W0EARLY) bar_arrive(NB_W0, 416);
      bar_sync(NB_TA, 192);
      TR(5)
      wg_wait<0>();
      if (!W0EARLY) bar_arrive(NB_W0, 416);
      info = lds32(sb + C_INFO + ((st + 1) & 1) * 4);
      acc_fence(oc2);
      if (rank != 2) put(oc2, IC<2>());
      mbar_arrive_remote_z(((t & 1) ? b2 : b1) + (B_F - B_O) * 8, t >> 1);
      mbar_expect_tx_z(bars + ((t & 1) ? B_O : B_X) * 8, 4096, t >> 1);
      TR(6)
    }
    const int sn = (st + 1) & 3;
    uint8_t* mw = Mw + sn * 65536;
    asm volatile("" : "+l"(mw));
    if (__builtin_expect((st < DELTA && b % 3 != 0) || (info && b % 3 == 2), 0)) {
      bar_arrive(NB_RD, 384);
      const int col = b / 3 * 16 + c * 4 + ((lane >> 2) & 3), r0 = (lane & 1) * 4 + (lane >> 4) * 2;
      const bool upd = info && b % 3 == 2;
      if (upd) mbar_wait(bars + B_U * 8, nupd & 1, 39);
      uint32_t hv[2];
#pragma unroll
      for (int i = 0; i < 2; i++) {
        const int r = r0 + i, sg = st + 1 - DELTA;
        const void* p = !upd ? (const void*)(mem0 + r * DM + col) : r == (int)(info >> 4) ? (const void*)(g_x2p[sg][1] + col)
                      : (const void*)(g_xs[1] + sg * 32768 + (col >> 6) * 4096 + ((info & 3) * 8 + r) * 128 + ((((col >> 3) ^ r) & 7) << 4) + (col & 7) * 2);
        asm volatile("ld.relaxed.gpu.global.u16 %0, [%1];" : "=r"(hv[i]) : "l"(p) : "memory");
      }
      st_rlx32(mw, hv[0] | hv[1] << 16);
      STAT(1, 0) STAT(2, 0) STAT(4, 0)
    } else {
      const uint32_t flip = (st & 1) ? ~0u : 0u;
      const bool u16 = lane & 16;
      const uint32_t bs = (lane & 4) ? 0x3f800000u : 0x00003f80u, bs0 = (lane & 8) ? 0u : bs, bs1 = (lane & 8) ? bs : 0u;
      STATC(c_rdy)
      mbar_wait(bars + B_PI * 8, st & 1, 37);
      TR(7)
      uint4 q0 = lds128(pia), q1 = lds128(pia + 2048), q2 = lds128(pia + 4096), q3 = lds128(pia + 6144);
      int it = 0;
#pragma unroll 1
      while (true) {
        float d0[4] = {0.f, 0.f, 0.f, 0.f}, d1[4] = {0.f, 0.f, 0.f, 0.f};
        mma16816(d0, q0.x, q0.y, q0.z, q0.w, bs0, bs1);
        mma16816(d1, q1.x, q1.y, q1.z, q1.w, bs0, bs1);
        mma16816(d0, q2.x, q2.y, q2.z, q2.w, bs0, bs1);
        mma16816(d1, q3.x, q3.y, q3.z, q3.w, bs0, bs1);
        const bool all = __all_sync(~0u, (int)and3(and_x(q0.x, q1.x, flip), and_x(q2.x, q3.x, flip), 1u));
        const float a0 = d0[0] + d1[0], a1 = d0[1] + d1[1], a2 = d0[2] + d1[2], a3 = d0[3] + d1[3];
        asm volatile("{ .reg .pred p; setp.ne.u32 p, %0, 0; @p bar.arrive %1, 384; }" ::"r"((uint32_t)all), "n"((int)NB_RD) : "memory");
        const uint32_t mword = pack_bf16((u16 ? a2 : a0) + __shfl_xor_sync(~0u, u16 ? a0 : a2, 16), (u16 ? a3 : a1) + __shfl_xor_sync(~0u, u16 ? a1 : a3, 16));
        asm volatile("{ .reg .pred p; setp.ne.u32 p, %2, 0; @p st.relaxed.gpu.global.u32 [%0], %1; }" ::"l"(mw), "r"(mword), "r"((uint32_t)all) : "memory");
        if (__builtin_expect(all, 1)) break;
        give_up(++it, SPIN_LIMIT, 44);
        const uint8_t* Pr0 = (const uint8_t*)g_P + b * 16384 + (pia - sb - C_PI) + polP * 4096;
        const uint8_t* Pr1 = Pr0 + (3 - 2 * polP) * 4096;
        q0 = ld_rlx128(Pr0); q1 = ld_rlx128(Pr0 + 2048); q2 = ld_rlx128(Pr1); q3 = ld_rlx128(Pr1 + 2048);
      }
      STATC(c_mst)
      STAT(1, c_rdy - tref) STAT(2, c_mst - tref) STAT(4, it)
      TRV(14, it)
    }
    STAT(0, lds32(sb + C_INFO + 24) - tref) STAT(3, tref)
    nupd += info != 0;
    TR(9)
    {
      const uint32_t ma = l16 + C_M + c * 2048 + mi * 4;
      auto scan = [&](uint32_t m, uint32_t a) { return __vimax3_u32(__vimax3_u32(m, lds32(a), lds32(a + 512)), lds32(a + 1024), lds32(a + 1536)); };
      mbar_wait(bars + B_M0 * 8, (st + 1) & 1, 45);
      bar_arrive(NB_M0, 384);
      STATC(c_g0)
      TR(10)
      uint32_t m = scan(0, ma);
      mbar_wait(bars + B_M1 * 8, (st + 1) & 1, 46);
      bar_arrive(NB_M1, 384);
      STATC(c_g1)
      TR(11)
      m = scan(m, ma + 8192);
      mbar_wait(bars + B_M2 * 8, (st + 1) & 1, 47);
      STATC(c_g2)
      TR(12)
      int it = 0;
      bar_arrive(NB_M2, 384);
      const bool redo = __any_sync(~0u, scan(m, ma + 16384) == ~0u);
      sts32(sb + C_INFO + 16 + c * 32, redo);
      if (__builtin_expect(redo, 0)) {
#pragma unroll 1
        for (int g = 0; g < 3;) {
          if (!__any_sync(~0u, scan(0, ma + g * 8192) == ~0u)) { g++; continue; }
          give_up(++it, SPIN_LIMIT, 48);
          if (lane == 0) {
            mbar_expect_tx(bars + (B_R + c) * 8, 2048);
            bulk_g2s(sb + C_M + g * 8192 + c * 2048, (const uint8_t*)g_M + sn * 65536 + (lds32(sb + C_POL + sn * 4) ? 4096 : 12288) + g * 16384 + c * 2048,
                     2048, bars + (B_R + c) * 8);
          }
          __syncwarp();
          mbar_wait(bars + (B_R + c) * 8, nretry++ & 1, 49);
        }
      }
      bar_arrive(NB_V, 384);
      STAT(5, c_g0 - tref) STAT(7, c_g1 - tref) STAT(8, c_g2 - tref)
      STAT(9, clk32() - tref) STAT(6, it + redo * 256)
      TR(13)
      TRV(15, it)
      st_rlx32(Mw + (st & 3) * 65536, ~0u);
    }
  }
}

__device__ __forceinline__ void chain_dma(const uint32_t sb, const int w, const int lane, const uint32_t rank, const int h) {
  const uint32_t bars = sb + C_BAR;
  const int expf_ = EXPF;
  if (w == 12) {
    u64 best = 0;
    uint32_t nx = 0;
    auto load = [&](uint32_t dst, const uint8_t* src, uint32_t bytes) {
      mbar_expect_tx_z(bars + B_XL * 8, bytes, lane >> 1);
      if (lane < 2 && bytes) {
        fence_async_glb();
        bulk_g2s(sb + dst, src, bytes, bars + B_XL * 8);
      }
      __syncwarp();
      mbar_wait(bars + B_XL * 8, nx++ & 1, 52);
    };
    wait_count(g_ex.ready, 96, 59);
    load(C_X + lane * 16384, g_xs[0] + lane * 16384, 16384);
    HD(6)
    bar_arrive(NB_X1, 288); bar_arrive(NSSTEPS ? NB_SM : NB_PV, 416);
#pragma unroll 1
    for (int st = 0; st < NSTEP; st++) {
      const int sg = st - DELTA;
      const bool more = st + 1 < NSEG && !(expf_ & 4);
      uint32_t info = 0;
      if (sg >= 0) {
        const u64 k = wait_keys(g_fl.key[0][sg], lane, 50);
        if (k > best) { best = k; info = 4 | ((key_token(k) >> 3) & 3) | (key_token(k) & 7) << 4; }
      }
      TR(0)
      mbar_wait(bars + B_XA * 8, st & 1, 58);
      sts32(sb + C_INFO + (st & 1) * 4, info);
      if (st > 0) bar_arrive(NB_TA, 192);
      TR(1)
      load(lane ? C_X : C_X + 32768, lane ? g_xs[0] + (st + 1) * 32768 : g_xs[1] + sg * 32768, lane ? (more ? KA * 1024 : 0) : (sg >= 0 && !(expf_ & 8) ? 32768 : 0));
      bar_arrive(NB_W0, 416);
      TR(2)
      if (__builtin_expect(info, 0)) {
        int it = 0;
        while (ld_rlx32(g_fl.patch[sg]) == 0) { give_up(++it, SPIN_LIMIT, 56); warp_sleep(250); }
        mbar_arrive_z(bars + B_U * 8, lane);
      }
      mbar_wait(bars + B_XF * 8, st & 1, 53);
      mbar_wait(bars + (B_M0 + BGATE) * 8, st & 1, 54);
      load(C_X + KA * 1024, g_xs[0] + (st + 1) * 32768 + KA * 1024, more && lane == 0 ? 32768 - KA * 1024 : 0);
      TR(3)
      bar_arrive(NSSTEPS ? NB_SM : NB_PV, 416);
    }
  } else if (w == 13) {
    constexpr uint32_t NP = 8192 / SHIP;
    const uint32_t o = (lane >> 1) * SHIP, own = sb + C_Q + rank * 10240, bt = bars + B_T * 8;
    const uint32_t d2 = 1 + (lane & 1);
    const uint32_t src2 = (rank == 0 ? sb + C_SA : rank == 1 ? own : sb + C_SB) + o;
    const uint32_t skip = (lane & 1) ? 4 | (o >> 11) : 8;
#pragma unroll 1
    for (int st = 0; st < NSTEP; st++) {
      mbar_wait(bars + B_P1 * 8, st & 1, 61);
      fence_async_smem();
      mbar_wait(bars + B_F * 8, st & 1, 60);
      if (st > 0) mbar_wait(bars + (S1GATE ? B_PI : B_J) * 8, (st - 1) & 1, 65);
      const uint32_t info = lds32(sb + C_INFO + (st & 1) * 4);
      TR(2)
      if (st < NSEG && rank != 0 && lane < 2 * NP && d2 == 1 && !(expf_ & 1)) bulk_s2r(mapa_u32(own + o, 0), sb + C_SA + o, SHIP, mapa_u32(bt, 0));
      __syncwarp();
      TR(3)
      mbar_wait(bars + B_P2 * 8, st & 1, 62);
      fence_async_smem();
      if (st > 0 && (SHIPLATE >> rank & 1)) mbar_wait(bars + B_I * 8, (st - 1) & 1, 64);
      TR(0)
      if (st >= DELTA && lane < 2 * NP && d2 != rank && (info & 7) != skip && !(expf_ & 2)) bulk_s2r(mapa_u32(own + o, d2), src2, SHIP, mapa_u32(bt, d2));
      __syncwarp();
      TR(1)
    }
  } else if (w == 14) {
    const int s0 = rank == 0 ? 0 : DELTA;
    const uint32_t tbytes = (expf_ & (rank ? 2 : 1)) ? 0 : 16384;
    mbar_expect_tx_z(bars + B_T * 8, s0 == 0 ? tbytes : 0, lane);
#pragma unroll 1
    for (int st = 0; st < NSTEP; st++) {
      const int sg = st - s0;
      const bool act = (unsigned)sg < (unsigned)NSEG;
      mbar_wait(bars + B_OT * 8, st & 1, 70);
      mbar_expect_tx_z(bars + B_T * 8, (unsigned)(sg + 1) < (unsigned)NSEG ? tbytes : 0, lane);
      fence_async_smem();
      const int s1 = rank && st < NSEG - 1 ? st + 1 : st;
      if (s1 != st) mbar_wait(bars + B_X * 8, s1 & 1, 71);
      TR(0)
      if (act && lane == 0 && !(expf_ & (rank ? 32 : 16))) {
        bulk_s2g(g_O[st & (OSLOTS - 1)][rank] + h * 8192, sb + C_OT + (st & 1) * 8192, 8192);
        asm volatile("cp.async.bulk.commit_group;" ::: "memory");
        asm volatile("cp.async.bulk.wait_group 0;" ::: "memory");
        asm volatile("fence.acq_rel.gpu;" ::: "memory");
      }
      __syncwarp();
      if (WLAG && s1 < NSTEP - 1) mbar_wait(bars + (FGATE ? B_M0 + FGATE - 1 : B_I) * 8, (s1 + (FGATE > 0)) & 1, 72);
      if (act && lane == 0) asm volatile("red.relaxed.gpu.global.add.u32 [%0], 1;" ::"l"(&g_fl.oflag[rank][sg][h >> 2]) : "memory");
      __syncwarp();
      TR(1)
    }
  } else {
    mbar_arrive_z(bars + B_M0 * 8, lane); mbar_arrive_z(bars + B_M1 * 8, lane); mbar_arrive_z(bars + B_M2 * 8, lane);
    const uint32_t wave = rank == 2 ? 0 : rank + 1, gate_p = GATE_P + wave * GATE_W, gate_g = GATE_G, gate_m = GATE_M;
    uint32_t nupd = 0, late = 0;
#pragma unroll 1
    for (int st = 0; st < NSTEP - 1; st++) {
      mbar_wait(bars + B_X * 8, st & 1, 75);
      if (st < 4) { HD(8 + st) }
      if (st == NSTEP - 2) { HD(12) }
      mbar_wait(bars + B_T * 8, st & 1, 77);
      const uint32_t now = gtime() & ~31u, tag = (st + 1) & 31;
      if (lane == 0) st_rlx32(&g_fl.stamp[blockIdx.x], (now + late) | tag);
      late = 0;
      __syncwarp();
      wait_clock(clk32() + 550);
      uint32_t s0, s1, s2;
      int it = 0;
#pragma unroll 1
      do {
        s0 = ld_rlx32(&g_fl.stamp[lane]) ^ tag; s1 = ld_rlx32(&g_fl.stamp[32 + lane]) ^ tag; s2 = ld_rlx32(&g_fl.stamp[64 + lane]) ^ tag;
        give_up(it++, SPIN_LIMIT, 76);
      } while (__any_sync(~0u, ((s0 | s1 | s2) & 31) != 0));
      const uint32_t tref = now + __reduce_max_sync(~0u, __vimax3_s32((int)(s0 - now), (int)(s1 - now), (int)(s2 - now)));
      const uint32_t g0 = gtime();
      uint32_t g1, c1;
      it = 0;
      do { g1 = gtime(); c1 = clk32(); } while (g1 == g0 && ++it < 64);
      c1 -= (g1 - tref) * 7 / 4;
      sts32(sb + C_INFO + 12, c1);
      TR(0)
      bar_sync(NB_TA, 192);
      const int sn = (st + 1) & 3;
      const uint8_t* src = (const uint8_t*)g_M + sn * 65536 + (lds32(sb + C_POL + sn * 4) ? 4096 : 12288);
      {
        const uint32_t pol = lds32(sb + C_INFO + 8);
        const uint8_t* ps = (const uint8_t*)g_P + (wave * 32 + h) * 16384;
        if (lane == 0) {
          mbar_expect_tx(bars + B_PI * 8, 8192);
          wait_clock(c1 + gate_p);
          bulk_g2s(sb + C_PI, ps + pol * 4096, 4096, bars + B_PI * 8);
          bulk_g2s(sb + C_PI + 4096, ps + (3 - pol) * 4096, 4096, bars + B_PI * 8);
          mbar_arrive_z(bars + B_J * 8, 0);
        }
        __syncwarp();
      }
      c1 += gate_m;
      if (__builtin_expect(lds32(sb + C_INFO + ((st + 1) & 1) * 4), 0)) {
        late = rank == 2 ? 160 : 0;
        mbar_wait(bars + B_U * 8, nupd++ & 1, 78);
        const uint32_t c2 = clk32() + 1300;
        if ((int)(c2 - c1) > 0) c1 = c2;
      }
      mbar_expect_tx_z(bars + (B_M0 + lane) * 8, 8192, lane / 3);
      if (lane == 0) {
#pragma unroll
        for (int g = 0; g < 3; g++) {
          wait_clock(c1 + g * gate_g);
          bulk_g2s(sb + C_M + g * 8192, src + g * 16384, 8192, bars + (B_M0 + g) * 8);
          if (g == IGRP) mbar_arrive_z(bars + B_I * 8, 0);
        }
      }
      __syncwarp();
      TR(3)
    }
  }
}

struct ChainMaps { CUtensorMap w[3], wo; };
__global__ void __cluster_dims__(3, 1, 1) __launch_bounds__(512, 1)
chain_kernel(const __grid_constant__ ChainMaps maps, const bf16* __restrict__ mem0, const bf16* __restrict__ x0) {
  extern __shared__ __align__(1024) uint8_t smem_raw[];
  const uint32_t sb = (smem_u32(smem_raw) + 1023) & ~1023u;
  const int tid = threadIdx.x, lane = tid & 31;
  const int w = __shfl_sync(~0u, tid >> 5, 0);
  uint32_t rank;
  asm volatile("mov.u32 %0, %%cluster_ctarank;" : "=r"(rank));
  const int h = blockIdx.x / 3;
  asm volatile("griddepcontrol.launch_dependents;" ::: "memory");
  TG(0)
  const int row0 = blockIdx.x * 16 + w, row1 = min(1536 + w * 96 + (int)blockIdx.x, NTOK - 1);
  const Row xr0 = load_row(x0 + row0 * DM, lane), xr1 = load_row(x0 + row1 * DM, lane);
  if (tid == 0) {
    const uint32_t bars = sb + C_BAR;
    mbar_init(bars + B_M0 * 8, 1); mbar_init(bars + B_M1 * 8, 1); mbar_init(bars + B_M2 * 8, 1);
    for (int i = 0; i < 4; i++) mbar_init(bars + (B_R + i) * 8, 1);
    mbar_init(bars + B_X * 8, 9); mbar_init(bars + B_O * 8, 2); mbar_init(bars + B_T * 8, 1); mbar_init(bars + B_F * 8, 2);
    mbar_init(bars + B_XL * 8, 2); mbar_init(bars + B_U * 8, 1);
    mbar_init(bars + B_P1 * 8, 8); mbar_init(bars + B_P2 * 8, 8); mbar_init(bars + B_OT * 8, 3); mbar_init(bars + B_XF * 8, 8); mbar_init(bars + B_XA * 8, 8); mbar_init(bars + B_I * 8, 1); mbar_init(bars + B_PI * 8, 1); mbar_init(bars + B_J * 8, 1);
    mbar_init(bars + B_W * 8, 1); mbar_init(bars + B_WO * 8, 1);
    asm volatile("fence.mbarrier_init.release.cluster;" ::: "memory");
    fence_async_smem();
    stage_weights(sb + C_STG, &maps.w[rank], h * 128, 0, bars + B_W * 8);
    const int nt = rank == 2 ? 2 : 3;
    mbar_expect_tx(bars + B_WO * 8, nt * 16384);
    for (int tl = 0; tl < nt; tl++)
      asm volatile("cp.async.bulk.tensor.5d.shared::cluster.global.mbarrier::complete_tx::bytes [%0], [%1, {%3, 0, 0, 0, %4}], [%2];"
                   ::"r"(sb + C_WO + tl * 16384), "l"(&maps.wo), "r"(bars + B_WO * 8), "r"((tl * 3 + rank) * 64), "r"(h * 4) : "memory");
  }
  __syncwarp();
  {
    const int gt = blockIdx.x * 512 + tid, g1 = gt - 12288, g2 = gt - 12288 - 16384;
    static_assert(12288 + 16384 + sizeof(Flags) / 16 <= 96 * 512, "reset");
    if (g1 < 0) ((uint4*)g_M)[gt / 3072 * 4096 + 256 + gt % 3072] = make_uint4(~0u, ~0u, ~0u, ~0u);
    else if (g2 < 0) ((uint4*)(g_part[1] + 32 * 8192))[g1] = make_uint4(0, 0, 0, 0);
    else if (g2 < (int)(sizeof(Flags) / 16)) ((uint4*)&g_fl)[g2] = make_uint4(0, 0, 0, 0);
    if ((NSTEP - 1) & 1) { ((uint4*)g_P)[gt] = make_uint4(0, 0, 0, 0); ((uint4*)g_P)[gt + 49152] = make_uint4(0, 0, 0, 0); }
#pragma unroll 1
    for (int i = 0; i < (w < 6 ? 2 : 1); i++) {
      const int row = i ? row1 : row0;
      Row r;
#pragma unroll
      for (int k = 0; k < 8; k++) r.w[k] = i ? xr1.w[k] : xr0.w[k];
      store_row_img(g_xs[0] + (row >> 5) * 32768, row & 31, lane, warp_ln(r));
    }
  }
  cluster_sync();
  if (tid == 448) red_release(g_ex.ready);
  __syncwarp();
  if (w < 8) {
    reg_inc<184>();
    chain_proj(sb, w, lane, rank);
    TG(1)
    TRDUMP
    cluster_sync();
  } else if (w < 12) {
    reg_dec<120>();
    chain_mem(sb, w, lane, rank, h, mem0);
    STATDUMP
    TRDUMP
    cluster_sync();
  } else {
    reg_dec<24>();
    chain_dma(sb, w, lane, rank, h);
    TRDUMP
    cluster_sync();
  }
}
#undef TRC
#undef TRS

constexpr int K_BAR = 0, K_LN = 128, K_FH = 320, K_FS = 512, K_FY = 1536;
constexpr int K_W = 3072;
constexpr int K_O = K_W + 3 * 49152;
constexpr int K_ST = K_O + 65536;
constexpr int K_SMEM = K_ST + 16384;
static_assert(K_SMEM <= 232448, "shared memory");
enum { KB_FULL = 0, KB_EMPTY = 2, KB_OK = 4, KB_GO = 7, KB_ST = 10, KB_REL = 12, KB_W = 13 };
enum { KN_ST = 1, KN_ST1, KN_REL, KN_FFN, KN_INIT, KN_RES, KN_RES1, KN_CAND, KN_TAKEN, KN_FF2 };
#define GATE_R 850
struct WorkerParams {
  CUtensorMap wo;
  const bf16 *x0, *w_r, *w_gate, *w_up, *w_down;
  bf16* out;
};
#define TRC (96 + blockIdx.x)
#define FT(e)
#define QUIET 4900
__device__ __forceinline__ void quiet_until(uint32_t t) {
  int d;
  while ((d = (int)(t - clk32())) > 0) warp_sleep(min(d / 3 + 20, 1000));
}
#define FOR_UNITS _Pragma("unroll 1") for (int st = 0, n = 0; st < WSTEP; st++) \
                  _Pragma("unroll 1") for (int v = st < NSEG ? 0 : st < WSTEP - 1 ? 1 : 2, sg = v ? st - WD : st; v < (st >= WD ? 3 : 1); v++, n++, sg = st - WD)

template <int ACC>
__device__ __forceinline__ void wg_ss8(float (&d)[4], uint64_t da, uint64_t db) {
  asm volatile("wgmma.mma_async.sync.aligned.m64n8k16.f32.bf16.bf16 {%0,%1,%2,%3}, %4, %5, %6, 1, 1, 1, 0;" : O4(d, 0) : "l"(da), "l"(db), "n"(ACC));
}
template <int NU>
__device__ __forceinline__ void ffn_slice(uint32_t sb, int t, const bf16* yrow, int ev) {
  const int lane = t & 31, c = t >> 5;
  FT(1)
  {
    const uint2 r = ld_rlx64(yrow + t * 4);
    asm volatile("st.shared.v2.b32 [%0], {%1,%2};" ::"r"(sb + K_FY + ((t >> 1) & 31) * 32 + (t >> 6) * 16 + (t & 1) * 8), "r"(r.x), "r"(r.y) : "memory");
  }
  fence_async_smem();
  bar_sync(KN_FFN, 128);
  FT(2)
  {
    float g[NU][4];
    const uint64_t da = mk_desc(sb + K_W, 16384, 512, 2), db = mk_desc(sb + K_FY, 32, 0, 0);
    wg_fence();
#pragma unroll
    for (int i = 0; i < 16; i++)
#pragma unroll
      for (int u = 0; u < NU; u++) { if (i == 0) wg_ss8<0>(g[u], da + u * 3072, db); else wg_ss8<1>(g[u], da + u * 3072 + i * 64, db + i * 4); }
    wg_commit();
    wg_wait<0>();
#pragma unroll
    for (int u = 0; u < NU; u++) {
      acc_fence(g[u]);
      if ((lane & 3) == 0) {
        const uint32_t a = sb + K_FS + u * 256 + c * 64 + lane;
        sts32(a, __float_as_uint(c < 2 ? g[u][0] : g[u][1])); sts32(a + 32, __float_as_uint(c < 2 ? g[u][2] : g[u][3]));
      }
    }
  }
  FT(3)
  bar_sync(KN_FFN, 128);
  {
    const uint32_t pa = sb + K_FS + c * 256 + lane * 4;
    const float gt = round_bf16(__uint_as_float(lds32(pa)) + __uint_as_float(lds32(pa + 128)));
    const float up = __shfl_xor_sync(~0u, gt, 16);
    const uint32_t hv = pack_bf16(round_bf16(__fdividef(gt, 1.f + __expf(-gt))) * up, 0.f);
    if (lane < 16) asm volatile("st.shared.b16 [%0], %1;" ::"r"(sb + K_FH + (c * 16 + lane) * 2), "h"((unsigned short)hv) : "memory");
  }
  fence_async_smem();
  bar_sync(KN_FFN, 128);
  FT(4)
#pragma unroll 1
  for (int hf = 0; hf < 2; hf++) {
    float o[4][4];
    const uint64_t da = mk_desc(sb + K_W + 32768 + hf * 8192, 16, 1024, 1), db = mk_desc(sb + K_FH, 16, 0, 0);
    wg_fence();
#pragma unroll
    for (int u = 0; u < NU; u++)
#pragma unroll
      for (int j = 0; j < 4; j++) { if (u == 0) wg_ss8<0>(o[j], da + j * 128, db); else wg_ss8<1>(o[j], da + u * 3072 + j * 128, db + u * 2); }
    wg_commit();
    wg_wait<0>();
    float lo = 0.f, hi = 0.f;
#pragma unroll
    for (int j = 0; j < 4; j++) {
      acc_fence(o[j]);
      const float a = __shfl_sync(~0u, o[j][0], lane & 28), b = __shfl_sync(~0u, o[j][2], lane & 28);
      if ((lane & 3) == j) { lo = a; hi = b; }
    }
    float* p = &g_fl.upd[ev][hf * 256 + (lane & 3) * 64 + c * 16 + (lane >> 2)];
    asm volatile("red.relaxed.gpu.global.add.f32 [%0], %1; red.relaxed.gpu.global.add.f32 [%0 + 32], %2;" ::"l"(p), "f"(lo), "f"(hi) : "memory");
  }
  FT(5)
  bar_sync(KN_FFN, 128);
  if (t == 96) red_release(g_fl.ffncnt[ev]);
  __syncwarp();
}
__device__ __forceinline__ uint4 pair_ln(uint4 r, float& e, uint32_t sl, int bar, int t) {
  const float x[8] = {bf_lo(r.x), bf_hi(r.x), bf_lo(r.y), bf_hi(r.y), bf_lo(r.z), bf_hi(r.z), bf_lo(r.w), bf_hi(r.w)};
  const float s = ((x[0] + x[1]) + (x[2] + x[3])) + ((x[4] + x[5]) + (x[6] + x[7]));
  const float q = (fmaf(x[0], x[0], x[1] * x[1]) + fmaf(x[2], x[2], x[3] * x[3])) + (fmaf(x[4], x[4], x[5] * x[5]) + fmaf(x[6], x[6], x[7] * x[7]));
  const bool u16 = t & 16, u8 = t & 8;
  const float a = (u16 ? q : s) + __shfl_xor_sync(~0u, u16 ? s : q, 16), b = e + __shfl_xor_sync(~0u, e, 16);
  float v = (u8 ? b : a) + __shfl_xor_sync(~0u, u8 ? a : b, 8);
  v += __shfl_xor_sync(~0u, v, 4); v += __shfl_xor_sync(~0u, v, 2); v += __shfl_xor_sync(~0u, v, 1);
  sts32(sl + (t >> 3) * 4, __float_as_uint(v));
  bar_sync(bar, 64);
  const uint4 s0 = lds128(sl), s1 = lds128(sl + 16);
  const float m = (__uint_as_float(s0.x) + __uint_as_float(s1.x)) * (1.f / DM), m2 = (__uint_as_float(s0.z) + __uint_as_float(s1.z)) * (1.f / DM);
  e = __uint_as_float(s0.y) + __uint_as_float(s1.y);
  float rs;
  asm("rsqrt.approx.ftz.f32 %0, %1;" : "=f"(rs) : "f"(fmaxf(fmaf(-m, m, m2), 0.f) + 1e-5f));
  return make_uint4(pack_bf16((x[0] - m) * rs, (x[1] - m) * rs), pack_bf16((x[2] - m) * rs, (x[3] - m) * rs),
                    pack_bf16((x[4] - m) * rs, (x[5] - m) * rs), pack_bf16((x[6] - m) * rs, (x[7] - m) * rs));
}
__device__ __forceinline__ uint32_t score_bits(float r) {
  const uint32_t b = pack_bf16(0.f, r);
  return (b & 0x80000000u) ? ~b : (b | 0x80000000u);
}

__global__ void __launch_bounds__(640, 1) worker_kernel(const __grid_constant__ WorkerParams prm) {
  extern __shared__ __align__(1024) uint8_t smem_raw[];
  const uint32_t sb = smem_u32(smem_raw);
  if (sb & 1023) __trap();
  const int tid = threadIdx.x, lane = tid & 31;
  const int w = __shfl_sync(~0u, tid >> 5, 0);
  const int me = blockIdx.x, kb = me >> 2, cb = me & 3;
  const bool full = me < 32;
  const uint32_t bars = sb + K_BAR;
  TG(0)
  if (tid == 0) {
    for (int i = 0; i < 2; i++) { mbar_init(bars + (KB_FULL + i) * 8, 1); mbar_init(bars + (KB_EMPTY + i) * 8, 1); }
    for (int i = 0; i < 10; i++) mbar_init(bars + (KB_OK + i) * 8, i < 3 ? 2 : 1);
    sts32(sb + K_LN + 144, 0);
    asm volatile("fence.mbarrier_init.release.cluster;" ::: "memory");
    fence_async_smem();
  }
  if (tid == 0 && full) stage_weights(sb + K_W, &prm.wo, cb * 128, kb * 512, bars + KB_W * 8);
  __syncthreads();
  if (w < 8) {
    reg_inc<176>();
    if (full) {
      uint32_t wA[32][4];
      mbar_wait(bars + KB_W * 8, 0, 79);
      load_wfrags(wA, sb + K_W, w, lane);
      bar_arrive(KN_INIT, 384);
      const uint32_t sp = pin(sb + K_ST + ((lane >> 4) * 8 + (lane & 7)) * 256 + (((2 * w + ((lane >> 3) & 1)) ^ (lane & 7)) << 4));
      const uint32_t tm = pin(lane < 4 ? 0x00010001u : 0u);
      FOR_UNITS {
        float d[16];
        mbar_wait(bars + (KB_FULL + (n & 1)) * 8, (n >> 1) & 1, 81);
        TR(4 * v)
        const uint64_t db = mk_desc(sb + K_O + (n & 1) * 32768, 128, 2048, 0);
        wg_fence();
#pragma unroll
        for (int ks = 0; ks < 32; ks++) {
          if (ks == 0) wg_rs32<0, 0>(d, wA[ks], db);
          else wg_rs32<0, 1>(d, wA[ks], db + (ks >> 3) * 512 + (ks & 7) * 16);
        }
        wg_commit();
        mbar_wait(bars + (KB_ST + (n & 1)) * 8, ((n >> 1) & 1) ^ 1, 82);
        wg_wait<0>();
        acc_fence(d);
        TR(4 * v + 1)
        const uint32_t tag = (sg & 2) ? 0u : tm;
        uint32_t pk[8];
#pragma unroll
        for (int i = 0; i < 8; i++) pk[i] = (pack_bf16(d[2 * i], d[2 * i + 1]) & ~tm) | tag;
        stsm4t(sp + (n & 1) * 8192, pk[0], pk[1], pk[2], pk[3]);
        stsm4t(sp + (n & 1) * 8192 + 4096, pk[4], pk[5], pk[6], pk[7]);
        bar_arrive(KN_ST + (n & 1), 288);
        TR(4 * v + 2)
      }
    }
  } else if (w < 12) {
    reg_dec<56>();
    if (full) {
      const int ly = (w >> 1) & 1, t = pin(tid & 63);
      const uint32_t so = pin((t >> 4) * 8192 + me * 256 + (((t & 15) ^ (me & 7)) << 4));
      int sstar = -1;
      uint32_t sl = sb + K_LN + ly * 64;
      float rr = 0.f;
      int kprev = -1;
      auto records = [&](int sg, uint32_t off) {
        int it = 0;
        while (__any_sync(~0u, (int)lds32(sb + K_LN + 144) <= sg)) { give_up(++it, SPIN_LIMIT, 86); warp_sleep(50); }
        return lds32(sb + K_LN + off);
      };
#pragma unroll 1
      for (int n = ly ? 2 * WD : 0; n < 2 * WSTEP; n++) {
        const int st = n >> 1, v = (n & 1) ? 2 : ly, sg = v ? st - WD : st, tok = sg * 32 + me;
        if (n == 2 * NSEG) bar_sync(KN_INIT, 128);
        if (n == 2 * NSEG + 2) sstar = records(NSEG - 1, 156);
        if (v == 2 ? sg < 0 || (st < NSEG ? st & 1 : 0) != ly : sg >= NSEG - v) continue;
        const bf16* xin = v ? g_rows[tok][0][2] : prm.x0 + tok * DM;
        if (v == 2 && ((records(sg, 148 + (sg >> 5) * 4) >> (sg & 31)) & 1)) xin = g_x2p[sg][0];
        const uint8_t* src = g_part[v] + (sg & 1) * (32 * 8192) + so;
        const uint32_t flip = (sg & 2) ? ~0u : 0u;
        mbar_wait(bars + (KB_GO + v) * 8, sg & 1, 87);
        TR(4 * v)
        uint4 p[8], x;
        int it = 0;
#pragma unroll 1
        do {
#pragma unroll
          for (int k = 0; k < 8; k++) p[k] = ld_rlx128(src + k * 32768);
          x = ld_rlx128(((WEXP & 2) ? prm.x0 : xin) + t * 8);
          give_up(it++, SPIN_LIMIT, 85);
        } while (__builtin_expect(!__all_sync(~0u, (int)and3(and3(and_x(p[0].x, p[1].x, flip), and_x(p[2].x, p[3].x, flip), 1u),
                                                             and_x(p[4].x, p[5].x, flip), and_x(p[6].x, p[7].x, flip))), 0));
        mbar_arrive_z(bars + (KB_OK + v) * 8, t & 31);
#define P8(h, f) (((h(p[0].f) + h(p[1].f)) + (h(p[2].f) + h(p[3].f))) + ((h(p[4].f) + h(p[5].f)) + (h(p[6].f) + h(p[7].f))))
#define X8(f) x.f = add_bf16x2(x.f, pack_bf16(P8(bf_lo, f), P8(bf_hi, f)));
        X8(x) X8(y) X8(z) X8(w)
#undef X8
#undef P8
        TRV(12 + v, it - 1)
        TR(4 * v + 1)
        bf16* dst = g_rows[tok][v][0] + t * 8;
        *(uint4*)dst = x;
        const uint4 wr = ld_rlx128(prm.w_r + t * 8);
        sl ^= 32;
        uint4 y = pair_ln(x, rr, sl, KN_RES + ly, t);
        *(uint4*)(dst + DM) = y;
        x = make_uint4(add_bf16x2(x.x, y.x), add_bf16x2(x.y, y.y), add_bf16x2(x.z, y.z), add_bf16x2(x.w, y.w));
        *(uint4*)(v == (sg < sstar ? 1 : 2) ? prm.out + tok * DM + t * 8 : dst + 2 * DM) = x;
        asm volatile("{ .reg .pred p; setp.eq.u32 p, %2, 0; @p st.relaxed.gpu.global.u64 [%0], %1; }" ::"l"(&g_fl.key[0][0][0] + max(kprev, 0)),
                     "l"((u64)score_bits(rr) << 32 | (uint32_t)~(kprev & (NTOK - 1))), "r"(t | (kprev < 0)) : "memory");
        kprev = v * NTOK + tok;
        rr = (fmaf(bf_lo(y.x), bf_lo(wr.x), bf_hi(y.x) * bf_hi(wr.x)) + fmaf(bf_lo(y.y), bf_lo(wr.y), bf_hi(y.y) * bf_hi(wr.y))) +
             (fmaf(bf_lo(y.z), bf_lo(wr.z), bf_hi(y.z) * bf_hi(wr.z)) + fmaf(bf_lo(y.w), bf_lo(wr.w), bf_hi(y.w) * bf_hi(wr.w)));
        if (v == 0 || st >= NSEG) {
          sl ^= 32;
          y = pair_ln(x, rr, sl, KN_RES + ly, t);
          if (v == 0) *(uint4*)(g_xs[1] + sg * 32768 + (t >> 3) * 4096 + me * 128 + (((t ^ me) & 7) << 4)) = y;
          sts32(sb + K_LN + 128 + ly * 4, score_bits(rr));
          bar_arrive(KN_REL, v == 0 || st == WSTEP - 1 ? 96 : 160);
          kprev = -1;
        }
        TR(4 * v + 2)
      }
    }
  } else if (w < 16) {
    reg_dec<48>();
    const int t = tid - 384, nu = full ? 3 : 4;
    if (full) bar_sync(KN_INIT, 384);
    {
      const int j0 = (full ? me * 3 : 96 + (me - 32) * 4) * 16;
#pragma unroll 1
      for (int i = t; i < nu * 3072; i += 128) {
        const int u = i / 3072, r = i - u * 3072;
        const int q = (r ^ (r >> 3)) & 3, r2 = r - 2048;
        const bf16* src = r < 2048 ? ((q & 2) ? prm.w_up : prm.w_gate) + (size_t)(r >> 2) * FF + j0 + u * 16 + (q & 1) * 8
                                   : prm.w_down + (size_t)(j0 + u * 16 + ((r2 >> 3) & 15)) * DM + (r2 >> 7) * 64 + ((r2 ^ (r2 >> 3)) & 7) * 8;
        cp16(sb + K_W + i * 16, src);
      }
      asm volatile("cp.async.wait_all;" ::: "memory");
    }
    bar_arrive(KN_TAKEN, 160);
#pragma unroll 1
    while (true) {
      bar_sync(KN_CAND, 160);
      const uint4 cand = lds128(sb + K_LN + 160);
      const u64 k = (u64)cand.y << 32 | cand.x;
      const int ev = cand.z, ver = cand.w & 3, tok = key_token(k);
      const bool last = cand.w & 4;
      if (!last) {
        bar_arrive(KN_TAKEN, 160);
        FT(0)
        if (full) ffn_slice<3>(sb, t, g_rows[tok][ver][1], ev); else ffn_slice<4>(sb, t, g_rows[tok][ver][1], ev);
      }
      if ((tok & 31) == me && (ver == 0 || last)) {
        if (t < 64) {
          FT(6)
          uint4 x = ld_rlx128(g_rows[tok][ver][0] + t * 8);
          const uint4 y = ld_rlx128(g_rows[tok][ver][1] + t * 8);
          const float sig = round_bf16(__fdividef(1.f, 1.f + __expf(-key_score(k))));
          int it = 0;
          while (ld_rlx32(g_fl.ffncnt[ev]) < NWORK) { give_up(++it, SPIN_LIMIT, 80); warp_sleep(40); }
          const uint4 u0 = ld_rlx128(&g_fl.upd[ev][t * 8]), u1 = ld_rlx128(&g_fl.upd[ev][t * 8 + 4]);
          auto upd = [&](uint32_t xw, uint32_t yw, uint32_t a, uint32_t b) {
            const uint32_t r = pack_bf16(__uint_as_float(a), __uint_as_float(b));
            return add_bf16x2(xw, add_bf16x2(yw, pack_bf16(bf_lo(r) * sig, bf_hi(r) * sig)));
          };
          x = make_uint4(upd(x.x, y.x, u0.x, u0.y), upd(x.y, y.y, u0.z, u0.w), upd(x.z, y.z, u1.x, u1.y), upd(x.w, y.w, u1.z, u1.w));
          FT(7)
          *(uint4*)((ver ? prm.out + tok * DM : g_x2p[ev][0]) + t * 8) = x;
          if (ver == 0) {
            float e = 0.f;
            *(uint4*)(g_x2p[ev][1] + t * 8) = pair_ln(x, e, sb + K_FS, KN_FF2, t);
            bar_sync(KN_FF2, 64);
            if (t == 0) st_release32(g_fl.patch[ev], 1);
            __syncwarp();
          }
        }
      }
      if (ev == NSEG && !last && full) {
        const int nc = min((int)lds32(sb + K_LN + 156), NSEG + 1 - WD);
#pragma unroll 1
        for (int s0 = (t >> 6) * 4; s0 < nc; s0 += 8) {
          uint4 q[4];
#pragma unroll
          for (int i = 0; i < 4; i++) q[i] = ld_rlx128(g_rows[min(s0 + i, nc - 1) * 32 + me][1][2] + (t & 63) * 8);
#pragma unroll
          for (int i = 0; i < 4; i++) *(uint4*)(prm.out + (min(s0 + i, nc - 1) * 32 + me) * DM + (t & 63) * 8) = q[i];
        }
      }
      FT(8)
      if (last) break;
    }
  } else {
    reg_dec<24>();
    if (w < 18) wait_count(g_ex.ready, 96, 94);
    if (w == 16) {
      u64 best = 0, mask = 0;
      int sstar = 0;
      uint32_t ver = 0, ev = 0;
      auto post = [&](uint32_t cmd) {
        bar_sync(KN_TAKEN, 160);
        sts128(sb + K_LN + 160, make_uint4((uint32_t)best, (uint32_t)(best >> 32), ev, ver | cmd));
        bar_arrive(KN_CAND, 160);
      };
      u64 accn = 0, acca = 0;
      uint32_t recs = 0;
      int j = 0;
      uint32_t tq = clk32();
#pragma unroll 1
      for (int st = 0; st < WSTEP; st++) {
        const u64* keys = st < NSEG ? g_fl.key[0][st] : g_fl.key[2][st - WD];
        const bool early = __any_sync(~0u, ld_rlx32(keys + lane) == 0);
        if (early && st < NSEG) quiet_until(tq);
        u64 k = wait_keys(keys, lane, 91);
        if (early) tq = clk32() + QUIET;
        if (st < NSEG) {
          const bool rec = k > best;
          recs &= ~(1u << (st & 31));
          if (rec) {
            best = k; ev = sstar = st;
            recs |= 1u << (st & 31);
            if ((key_token(k) & 31) == me) mask |= 1ull << st;
          }
          if (lane == 0) sts128(sb + K_LN + 144, make_uint4(st + 1, (uint32_t)mask, (uint32_t)(mask >> 32), sstar));
          __syncwarp();
          if (rec) post(0);
        }
#pragma unroll 1
        for (; j <= st - WD - (st < NSEG ? 2 : 0); j++) {
          u64 kn = 1, kc;
          int it = 0;
          do {
            if (j < NSEG - 1) asm volatile("ld.relaxed.gpu.global.u64 %0, [%1];" : "=l"(kn) : "l"(&g_fl.key[1][j][lane]) : "memory");
            asm volatile("ld.relaxed.gpu.global.u64 %0, [%1];" : "=l"(kc) : "l"(&g_fl.key[2][j][lane]) : "memory");
            give_up(it++, SPIN_LIMIT, 92);
          } while (__any_sync(~0u, kn == 0 || kc == 0));
          if ((recs >> (j & 31)) & 1) acca = accn;
          if (kc > acca) acca = kc;
          if (kn > accn) accn = kn;
        }
        if (st >= NSEG) {
          const u64 m = j <= sstar ? accn : acca;
          const uint32_t hi = __reduce_max_sync(~0u, (uint32_t)(m >> 32));
          k = (u64)hi << 32 | __reduce_max_sync(~0u, (uint32_t)(m >> 32) == hi ? (uint32_t)m : 0u);
          if (st == NSEG || k != best) {
            best = k; ev = st;
            ver = (key_token(k) >> 5) < sstar ? 1 : 2;
            post(0);
          }
        }
      }
      HD(6)
      post(4);
      if (me == 0 && lane == 0) st_rlx32(g_ex.ready, 0);
    } else if (!full) {
    } else if (w == 17) {
      uint32_t tq = clk32();
      FOR_UNITS {
        if (ld_rlx32(&g_fl.oflag[v][sg][kb]) < 4) {
          if (v == (st < NSEG ? 0 : 1) && st < WSTEP - 3) quiet_until(tq);
          wait_count(&g_fl.oflag[v][sg][kb], 4, 84);
          if (v == (st < NSEG ? 0 : 1)) tq = clk32() + QUIET;
        }
        mbar_wait(bars + (KB_EMPTY + (n & 1)) * 8, ((n >> 1) & 1) ^ 1, 83);
        TR(v)
        if (st == WSTEP - 1) { HD(v) }
        if (lane == 0) {
          fence_async_glb();
          mbar_expect_tx(bars + (KB_FULL + (n & 1)) * 8, (WEXP & 4) ? 4096 : 32768);
          bulk_g2s(sb + K_O + (n & 1) * 32768, g_O[(v ? sg + DELTA : sg) & (OSLOTS - 1)][v] + kb * 32768, (WEXP & 4) ? 4096 : 32768, bars + (KB_FULL + (n & 1)) * 8);
        }
        __syncwarp();
      }
    } else if (w == 18) {
      FOR_UNITS {
        if (sg > 0) mbar_wait(bars + (KB_OK + v) * 8, (sg - 1) & 1, 90);
        bar_sync(KN_ST + (n & 1), 288);
        fence_async_smem();
        const uint32_t tg = clk32() + GATE_R;
        if (lane == 0) {
          bulk_s2g(g_part[v] + ((sg & 1) * 32 + me) * 8192, sb + K_ST + (n & 1) * 8192, 8192);
          asm volatile("cp.async.bulk.commit_group;" ::: "memory");
          mbar_arrive_z(bars + (KB_EMPTY + (n & 1)) * 8, 0);
          asm volatile("cp.async.bulk.wait_group.read 0;" ::: "memory");
        }
        __syncwarp();
        mbar_arrive_z(bars + (KB_ST + (n & 1)) * 8, lane);
        TR(v)
        if (v == (st < NSEG ? 0 : st < WSTEP - 1 ? 1 : 2) && st > 0) mbar_wait(bars + KB_REL * 8, (st - 1) & 1, 93);
        wait_clock(tg);
        if (st == WSTEP - 1) { HD(2 + v) }
        mbar_arrive_z(bars + (KB_GO + v) * 8, lane);
      }
    } else {
#pragma unroll 1
      for (int st = 0; st < WSTEP; st++) {
        const int sg = st < NSEG ? st : st - WD;
        const bool both = st >= NSEG && st < WSTEP - 1;
        bar_sync(KN_REL, both ? 160 : 96);
        const uint32_t ob = __shfl_sync(~0u, lds32(sb + K_LN + 128), 0), obn = __shfl_sync(~0u, lds32(sb + K_LN + 132), 0);
        mbar_arrive_z(bars + KB_REL * 8, lane);
        if (st == WSTEP - 1) { HD(5) }
        if (lane == 0) {
          if (both) asm volatile("st.relaxed.gpu.global.u64 [%0], %1;" ::"l"(&g_fl.key[1][sg][me]), "l"((u64)obn << 32 | (uint32_t)~(sg * 32 + me)) : "memory");
          st_release_u64(&g_fl.key[st < NSEG ? 0 : 2][sg][me], (u64)ob << 32 | (uint32_t)~(sg * 32 + me));
        }
        __syncwarp();
        TR(0)
      }
    }
  }
}
#undef TRC

typedef CUresult (*EncodeFn)(CUtensorMap*, CUtensorMapDataType, cuuint32_t, void*, const cuuint64_t*, const cuuint64_t*,
                             const cuuint32_t*, const cuuint32_t*, CUtensorMapInterleave, CUtensorMapSwizzle,
                             CUtensorMapL2promotion, CUtensorMapFloatOOBfill);
void make_map(EncodeFn fn, CUtensorMap* m, const void* ptr, int rank, const cuuint64_t* dims, const cuuint64_t* strides, const cuuint32_t* box) {
  const cuuint32_t es[5] = {1, 1, 1, 1, 1};
  fn(m, CU_TENSOR_MAP_DATA_TYPE_BFLOAT16, rank, (void*)ptr, dims, strides, box, es, CU_TENSOR_MAP_INTERLEAVE_NONE,
     CU_TENSOR_MAP_SWIZZLE_128B, CU_TENSOR_MAP_L2_PROMOTION_L2_256B, CU_TENSOR_MAP_FLOAT_OOB_FILL_NONE);
}
struct HostState {
  const void* key[4];
  ChainMaps cm;
  CUtensorMap wo;
};
HostState g_hs;

}

extern "C" void kernel_launch(void* const* d_in, const int* in_sizes, int n_in, void* d_out, int out_size) {
  (void)in_sizes; (void)n_in; (void)out_size;
  HostState& hs = g_hs;
  if (hs.key[0] != d_in[2] || hs.key[1] != d_in[3] || hs.key[2] != d_in[4] || hs.key[3] != d_in[5]) {
    void* fnp = nullptr;
    cudaDriverEntryPointQueryResult qr;
    cudaGetDriverEntryPoint("cuTensorMapEncodeTiled", &fnp, cudaEnableDefault, &qr);
    const cuuint32_t box[2] = {64, 256}, box5[5] = {64, 2, 4, 4, 4};
    const cuuint64_t dw[2] = {HD, DM}, sw[1] = {HD * 2}, dwo[2] = {DM, HD}, swo[1] = {DM * 2};
    const cuuint64_t d5[5] = {DM, 2, 4, 4, HD / 32}, s5[4] = {DM * 2, 8 * DM * 2, 2 * DM * 2, 32 * DM * 2};
    for (int i = 0; i < 3; i++) make_map((EncodeFn)fnp, &hs.cm.w[i], d_in[2 + i], 2, dw, sw, box);
    make_map((EncodeFn)fnp, &hs.cm.wo, d_in[5], 5, d5, s5, box5);
    make_map((EncodeFn)fnp, &hs.wo, d_in[5], 2, dwo, swo, box);
    cudaFuncSetAttribute(worker_kernel, cudaFuncAttributeMaxDynamicSharedMemorySize, K_SMEM);
    cudaFuncSetAttribute(chain_kernel, cudaFuncAttributeMaxDynamicSharedMemorySize, C_SMEM);
    for (int i = 0; i < 4; i++) hs.key[i] = d_in[2 + i];
  }
  cudaStream_t st = cudaStreamPerThread;
  WorkerParams wp;
  wp.wo = hs.wo; wp.x0 = (const bf16*)d_in[0]; wp.w_r = (const bf16*)d_in[8]; wp.w_gate = (const bf16*)d_in[9];
  wp.w_up = (const bf16*)d_in[10]; wp.w_down = (const bf16*)d_in[11]; wp.out = (bf16*)d_out;
  chain_kernel<<<96, 512, C_SMEM, st>>>(hs.cm, (const bf16*)d_in[1], wp.x0);
  cudaLaunchAttribute pdl[1];
  pdl[0].id = cudaLaunchAttributeProgrammaticStreamSerialization;
  pdl[0].val.programmaticStreamSerializationAllowed = 1;
  cudaLaunchConfig_t cfg = {};
  cfg.gridDim = dim3(NWORK); cfg.blockDim = dim3(640); cfg.dynamicSmemBytes = K_SMEM; cfg.stream = st;
  cfg.attrs = pdl; cfg.numAttrs = 1;
  cudaLaunchKernelEx(&cfg, worker_kernel, wp);
}
```

```cpp
#include <cuda_runtime.h>
#include <cuda_bf16.h>
#include <cuda.h>
#include <stdint.h>

namespace {

typedef __nv_bfloat16 bf16;
typedef unsigned long long u64;

constexpr int NTOK = 2048, DM = 512, HD = 4096, NSEG = 64, FF = 1792;
#define DELTA 5
constexpr int NSTEP = NSEG + DELTA;
#define WLAG 1
constexpr int WD = DELTA + WLAG, WSTEP = NSEG + WD;
constexpr int SPIN_LIMIT = 40000;
constexpr int MBAR_LIMIT = 20000;
constexpr int NWORK = 36;
constexpr int OSLOTS = 8;
#define SLP_C 100
#define SLP_K 200
#define WEXP 0

__device__ __align__(1024) uint8_t g_xs[2][NSEG * 32768];
__device__ __align__(1024) uint8_t g_O[OSLOTS][3][32 * 8192];
__device__ __align__(1024) uint8_t g_part[3][2 * 32 * 8192];
__device__ __align__(1024) bf16 g_rows[NTOK][3][3][DM];
__device__ __align__(1024) bf16 g_x2p[NSEG][2][DM];
struct Flags {
  uint32_t pol[96];
  uint32_t stamp[96];
  uint32_t oflag[3][NSEG][8];
  uint32_t ffncnt[WSTEP][8];
  uint32_t patch[NSEG][8];
  u64 key[3][NSEG][32];
  float upd[WSTEP][DM];
};
struct Exchange { uint32_t M[4 * 16384], P[96 * 4096]; Flags fl; uint32_t ready[32]; };
__device__ __align__(65536) Exchange g_ex;
#define g_M g_ex.M
#define g_P g_ex.P
#define g_fl g_ex.fl
#define TR(e)
#define TRV(e, v)
#define TG(i)
#define HD(e)
#define TRDUMP
#define TREXTRA 0

#define STAT(e, v)
#define STATC(n)
#define STATDUMP
__device__ __forceinline__ uint32_t smem_u32(const void* p) { return (uint32_t)__cvta_generic_to_shared(p); }
__device__ __forceinline__ uint32_t pack_bf16(float lo, float hi) {
  uint32_t r;
  asm("cvt.rn.bf16x2.f32 %0, %1, %2;" : "=r"(r) : "f"(hi), "f"(lo));
  return r;
}
__device__ __forceinline__ float bf_lo(uint32_t v) { return __uint_as_float(v << 16); }
__device__ __forceinline__ float bf_hi(uint32_t v) { return __uint_as_float(v & 0xffff0000u); }
__device__ __forceinline__ float ex2_fast(float x) { float y; asm("ex2.approx.ftz.f32 %0, %1;" : "=f"(y) : "f"(x)); return y; }
__device__ __forceinline__ float round_bf16(float x) { return __bfloat162float(__float2bfloat16_rn(x)); }
__device__ __forceinline__ uint32_t clk32() { uint32_t t; asm volatile("mov.u32 %0, %%clock;" : "=r"(t) :: "memory"); return t; }

__device__ __forceinline__ void mma16816(float (&d)[4], uint32_t a0, uint32_t a1, uint32_t a2, uint32_t a3,
                                         uint32_t b0, uint32_t b1) {
  asm("mma.sync.aligned.m16n8k16.row.col.f32.bf16.bf16.f32 {%0,%1,%2,%3}, {%4,%5,%6,%7}, {%8,%9}, {%0,%1,%2,%3};"
      : "+f"(d[0]), "+f"(d[1]), "+f"(d[2]), "+f"(d[3])
      : "r"(a0), "r"(a1), "r"(a2), "r"(a3), "r"(b0), "r"(b1));
}
__device__ __forceinline__ void ldsm4t(uint32_t (&r)[4], uint32_t addr) {
  asm volatile("ldmatrix.sync.aligned.m8n8.x4.trans.shared.b16 {%0,%1,%2,%3}, [%4];"
               : "=r"(r[0]), "=r"(r[1]), "=r"(r[2]), "=r"(r[3]) : "r"(addr) : "memory");
}
__device__ __forceinline__ void stsm4(uint32_t addr, uint32_t a, uint32_t b, uint32_t c, uint32_t d) {
  asm volatile("stmatrix.sync.aligned.m8n8.x4.shared.b16 [%0], {%1,%2,%3,%4};" ::"r"(addr), "r"(a), "r"(b), "r"(c), "r"(d) : "memory");
}
__device__ __forceinline__ void stsm4t(uint32_t addr, uint32_t a, uint32_t b, uint32_t c, uint32_t d) {
  asm volatile("stmatrix.sync.aligned.m8n8.x4.trans.shared.b16 [%0], {%1,%2,%3,%4};" ::"r"(addr), "r"(a), "r"(b), "r"(c), "r"(d) : "memory");
}
__device__ __forceinline__ uint4 lds128(uint32_t a) {
  uint4 v; asm volatile("ld.shared.v4.b32 {%0,%1,%2,%3}, [%4];" : "=r"(v.x), "=r"(v.y), "=r"(v.z), "=r"(v.w) : "r"(a) : "memory"); return v;
}
__device__ __forceinline__ uint32_t lds32(uint32_t a) { uint32_t v; asm volatile("ld.shared.b32 %0, [%1];" : "=r"(v) : "r"(a) : "memory"); return v; }
__device__ __forceinline__ void sts32(uint32_t a, uint32_t x) { asm volatile("st.shared.b32 [%0], %1;" ::"r"(a), "r"(x) : "memory"); }
__device__ __forceinline__ void sts128(uint32_t a, uint4 v) {
  asm volatile("st.shared.v4.b32 [%0], {%1,%2,%3,%4};" ::"r"(a), "r"(v.x), "r"(v.y), "r"(v.z), "r"(v.w) : "memory");
}
__device__ __forceinline__ void cp16(uint32_t dst, const void* src) {
  asm volatile("cp.async.cg.shared.global [%0], [%1], 16;" ::"r"(dst), "l"(src) : "memory");
}
__device__ __forceinline__ void mbar_init(uint32_t mbar, uint32_t cnt) {
  asm volatile("mbarrier.init.shared.b64 [%0], %1;" ::"r"(mbar), "r"(cnt) : "memory");
}
__device__ __forceinline__ void mbar_expect_tx(uint32_t mbar, uint32_t bytes) {
  asm volatile("mbarrier.arrive.expect_tx.shared.b64 _, [%0], %1;" ::"r"(mbar), "r"(bytes) : "memory");
}
__device__ __forceinline__ void mbar_arrive_z(uint32_t mbar, uint32_t z) {
  asm volatile("{ .reg .pred p; setp.eq.u32 p, %1, 0; @p mbarrier.arrive.shared.b64 _, [%0]; }" ::"r"(mbar), "r"(z) : "memory");
}
__device__ __forceinline__ void mbar_expect_tx_z(uint32_t mbar, uint32_t bytes, uint32_t z) {
  asm volatile("{ .reg .pred p; setp.eq.u32 p, %2, 0; @p mbarrier.arrive.expect_tx.shared.b64 _, [%0], %1; }" ::"r"(mbar), "r"(bytes), "r"(z) : "memory");
}
__device__ __forceinline__ void mbar_arrive_remote_z(uint32_t mbar, uint32_t z) {
  asm volatile("{ .reg .pred p; setp.eq.u32 p, %1, 0; @p mbarrier.arrive.shared::cluster.b64 _, [%0]; }" ::"r"(mbar), "r"(z) : "memory");
}
__device__ __forceinline__ void warp_sleep(uint32_t ns) { __nanosleep(ns); __syncwarp(); }
__device__ __forceinline__ void fail(int) { __trap(); }
__device__ __forceinline__ void give_up(int it, int limit, int code) { if (it > limit) fail(code); }
__device__ __forceinline__ void mbar_wait(uint32_t mbar, uint32_t par, int code) {
  asm volatile("{ .reg .pred p; .reg .b32 n; mov.b32 n, %2;\n"
               "W: mbarrier.try_wait.parity.shared::cta.b64 p, [%0], %1; @p bra D;\n"
               "add.s32 n, n, -1; setp.eq.s32 p, n, 0; @p trap; bra W;\n"
               "D: }" ::"r"(mbar), "r"(par), "n"(MBAR_LIMIT) : "memory");
}
__device__ __forceinline__ void bulk_g2s(uint32_t dst, const void* src, uint32_t bytes, uint32_t mbar) {
  asm volatile("cp.async.bulk.shared::cluster.global.mbarrier::complete_tx::bytes [%0], [%1], %2, [%3];"
               ::"r"(dst), "l"(src), "r"(bytes), "r"(mbar) : "memory");
}
__device__ __forceinline__ void bulk_s2r(uint32_t dst, uint32_t src, uint32_t bytes, uint32_t mbar) {
  asm volatile("cp.async.bulk.shared::cluster.shared::cta.mbarrier::complete_tx::bytes [%0], [%1], %2, [%3];"
               ::"r"(dst), "r"(src), "r"(bytes), "r"(mbar) : "memory");
}
__device__ __forceinline__ void bulk_s2g(void* dst, uint32_t src, uint32_t bytes) {
  asm volatile("cp.async.bulk.global.shared::cta.bulk_group [%0], [%1], %2;" ::"l"(dst), "r"(src), "r"(bytes) : "memory");
}
__device__ __forceinline__ void fence_async_smem() { asm volatile("fence.proxy.async.shared::cta;" ::: "memory"); }
__device__ __forceinline__ void fence_async_glb() { asm volatile("fence.proxy.async.global;" ::: "memory"); }
__device__ __forceinline__ void bar_sync(int id, int n) { asm volatile("bar.sync %0, %1;" ::"r"(id), "r"(n) : "memory"); }
__device__ __forceinline__ void bar_arrive(int id, int n) { asm volatile("bar.arrive %0, %1;" ::"r"(id), "r"(n) : "memory"); }
__device__ __forceinline__ void cluster_sync() { asm volatile("barrier.cluster.arrive.release; barrier.cluster.wait.acquire;" ::: "memory"); }
__device__ __forceinline__ uint32_t mapa_u32(uint32_t a, uint32_t r) {
  uint32_t o;
  asm("mapa.shared::cluster.u32 %0, %1, %2;" : "=r"(o) : "r"(a), "r"(r));
  return o;
}
template <int OFF>
__device__ __forceinline__ void st_async32(uint32_t a, uint32_t x, uint32_t mbar) {
  asm volatile("st.async.weak.shared::cluster.mbarrier::complete_tx::bytes.b32 [%0 + %3], %1, [%2];" ::"r"(a), "r"(x), "r"(mbar), "n"(OFF) : "memory");
}
__device__ __forceinline__ uint4 ld_rlx128(const void* p) {
  uint4 v;
  asm volatile("ld.relaxed.gpu.global.v4.u32 {%0,%1,%2,%3}, [%4];" : "=r"(v.x), "=r"(v.y), "=r"(v.z), "=r"(v.w) : "l"(p) : "memory");
  return v;
}
__device__ __forceinline__ uint2 ld_rlx64(const void* p) {
  uint2 v; asm volatile("ld.relaxed.gpu.global.v2.u32 {%0,%1}, [%2];" : "=r"(v.x), "=r"(v.y) : "l"(p) : "memory"); return v;
}
__device__ __forceinline__ uint32_t ld_rlx32(const void* p) {
  uint32_t v; asm volatile("ld.relaxed.gpu.global.u32 %0, [%1];" : "=r"(v) : "l"(p) : "memory"); return v;
}
__device__ __forceinline__ void st_rlx32(void* p, uint32_t a) { asm volatile("st.relaxed.gpu.global.u32 [%0], %1;" ::"l"(p), "r"(a) : "memory"); }
__device__ __forceinline__ void red_release(uint32_t* p) { asm volatile("red.release.gpu.global.add.u32 [%0], 1;" ::"l"(p) : "memory"); }
__device__ __forceinline__ void st_release32(void* p, uint32_t a) { asm volatile("st.release.gpu.global.u32 [%0], %1;" ::"l"(p), "r"(a) : "memory"); }
__device__ __forceinline__ void st_release_u64(void* p, u64 a) { asm volatile("st.release.gpu.global.u64 [%0], %1;" ::"l"(p), "l"(a) : "memory"); }
__device__ __forceinline__ void wait_count(const uint32_t* p, uint32_t val, int code) {
  int it = 0;
  while (ld_rlx32(p) < val) {
    give_up(++it, SPIN_LIMIT, code);
    warp_sleep(SLP_C);
  }
}
__device__ __forceinline__ u64 wait_keys(const u64* keys, int lane, int code) {
  u64 k;
  int it = 0;
  while (true) {
    asm volatile("ld.relaxed.gpu.global.u64 %0, [%1];" : "=l"(k) : "l"(keys + lane) : "memory");
    if (__all_sync(~0u, k != 0)) break;
    give_up(++it, SPIN_LIMIT, code);
    warp_sleep(SLP_K);
  }
  const uint32_t hi = __reduce_max_sync(~0u, (uint32_t)(k >> 32));
  const uint32_t lo = __reduce_max_sync(~0u, (uint32_t)(k >> 32) == hi ? (uint32_t)k : 0u);
  return (u64)hi << 32 | lo;
}
__device__ __forceinline__ int key_token(u64 k) { return (int)(~(uint32_t)k) & (NTOK - 1); }
__device__ __forceinline__ float key_score(u64 k) {
  const uint32_t ob = (uint32_t)(k >> 32);
  return __uint_as_float((ob & 0x80000000u) ? (ob & 0x7fffffffu) : ~ob);
}

__device__ __forceinline__ uint64_t mk_desc(uint32_t saddr, uint32_t lbo, uint32_t sbo, uint32_t sw) {
  return (uint64_t)((saddr & 0x3FFFF) >> 4) | (uint64_t)(lbo >> 4) << 16 | (uint64_t)(sbo >> 4) << 32 | (uint64_t)sw << 62;
}
template <int N> __device__ __forceinline__ void reg_inc() { asm volatile("setmaxnreg.inc.sync.aligned.u32 %0;" ::"n"(N)); }
template <int N> __device__ __forceinline__ void reg_dec() { asm volatile("setmaxnreg.dec.sync.aligned.u32 %0;" ::"n"(N)); }
__device__ __forceinline__ void wg_fence() { asm volatile("wgmma.fence.sync.aligned;" ::: "memory"); }
__device__ __forceinline__ void wg_commit() { asm volatile("wgmma.commit_group.sync.aligned;" ::: "memory"); }
template <int N> __device__ __forceinline__ void wg_wait() { asm volatile("wgmma.wait_group.sync.aligned %0;" ::"n"(N) : "memory"); }
template <int N> __device__ __forceinline__ void acc_fence(float (&d)[N]) {
#pragma unroll
  for (int i = 0; i < N; i++) asm volatile("" : "+f"(d[i]) :: "memory");
}
#define O4(d, i) "+f"(d[i]), "+f"(d[i + 1]), "+f"(d[i + 2]), "+f"(d[i + 3])
template <int TB, int ACC>
__device__ __forceinline__ void wg_rs24(float (&d)[12], const uint32_t (&a)[4], uint64_t db) {
  asm volatile("wgmma.mma_async.sync.aligned.m64n24k16.f32.bf16.bf16 {%0,%1,%2,%3,%4,%5,%6,%7,%8,%9,%10,%11}, {%12,%13,%14,%15}, %16, %17, 1, 1, %18;"
               : O4(d, 0), O4(d, 4), O4(d, 8) : "r"(a[0]), "r"(a[1]), "r"(a[2]), "r"(a[3]), "l"(db), "n"(ACC), "n"(TB));
}
template <int TB, int ACC>
__device__ __forceinline__ void wg_rs32(float (&d)[16], const uint32_t (&a)[4], uint64_t db) {
  asm volatile("wgmma.mma_async.sync.aligned.m64n32k16.f32.bf16.bf16 {%0,%1,%2,%3,%4,%5,%6,%7,%8,%9,%10,%11,%12,%13,%14,%15}, {%16,%17,%18,%19}, %20, %21, 1, 1, %22;"
               : O4(d, 0), O4(d, 4), O4(d, 8), O4(d, 12) : "r"(a[0]), "r"(a[1]), "r"(a[2]), "r"(a[3]), "l"(db), "n"(ACC), "n"(TB));
}
template <int ACC>
__device__ __forceinline__ void wg_rs64(float (&d)[32], uint32_t a0, uint32_t a1, uint32_t a2, uint32_t a3, uint64_t db) {
  asm volatile("wgmma.mma_async.sync.aligned.m64n64k16.f32.bf16.bf16 {%0,%1,%2,%3,%4,%5,%6,%7,%8,%9,%10,%11,%12,%13,%14,%15,"
               "%16,%17,%18,%19,%20,%21,%22,%23,%24,%25,%26,%27,%28,%29,%30,%31}, {%32,%33,%34,%35}, %36, %37, 1, 1, 0;"
               : O4(d, 0), O4(d, 4), O4(d, 8), O4(d, 12), O4(d, 16), O4(d, 20), O4(d, 24), O4(d, 28)
               : "r"(a0), "r"(a1), "r"(a2), "r"(a3), "l"(db), "n"(ACC));
}
template <int ACC>
__device__ __forceinline__ void wg_ss24(float (&d)[12], uint64_t da, uint64_t db) {
  asm volatile("wgmma.mma_async.sync.aligned.m64n24k16.f32.bf16.bf16 {%0,%1,%2,%3,%4,%5,%6,%7,%8,%9,%10,%11}, %12, %13, %14, 1, 1, 1, 0;"
               : O4(d, 0), O4(d, 4), O4(d, 8) : "l"(da), "l"(db), "n"(ACC));
}
template <int ACC>
__device__ __forceinline__ void wg_rs40(float (&d)[20], const uint32_t (&a)[4], uint64_t db) {
  asm volatile("wgmma.mma_async.sync.aligned.m64n40k16.f32.bf16.bf16 {%0,%1,%2,%3,%4,%5,%6,%7,%8,%9,%10,%11,%12,%13,%14,%15,%16,%17,%18,%19}, {%20,%21,%22,%23}, %24, %25, 1, 1, 1;"
               : O4(d, 0), O4(d, 4), O4(d, 8), O4(d, 12), O4(d, 16) : "r"(a[0]), "r"(a[1]), "r"(a[2]), "r"(a[3]), "l"(db), "n"(ACC));
}

struct Row { uint32_t w[8]; };
__device__ __forceinline__ uint32_t add_bf16x2(uint32_t a, uint32_t b) {
  uint32_t d; asm("add.rn.bf16x2 %0, %1, %2;" : "=r"(d) : "r"(a), "r"(b)); return d;
}
__device__ __forceinline__ Row warp_ln(const Row& r, float& extra) {
  float x[16];
#pragma unroll
  for (int i = 0; i < 8; i++) { x[2 * i] = bf_lo(r.w[i]); x[2 * i + 1] = bf_hi(r.w[i]); }
  float m = (((x[0] + x[1]) + (x[2] + x[3])) + ((x[4] + x[5]) + (x[6] + x[7]))) + (((x[8] + x[9]) + (x[10] + x[11])) + ((x[12] + x[13]) + (x[14] + x[15])));
  m *= (1.f / 16);
  float v0 = 0.f, v1 = 0.f;
#pragma unroll
  for (int i = 0; i < 16; i += 2) { const float d0 = x[i] - m, d1 = x[i + 1] - m; v0 = fmaf(d0, d0, v0); v1 = fmaf(d1, d1, v1); }
  float v = v0 + v1;
#pragma unroll
  for (int o = 1; o <= 16; o <<= 1) {
    const float mo = __shfl_xor_sync(~0u, m, o), vo = __shfl_xor_sync(~0u, v, o);
    extra += __shfl_xor_sync(~0u, extra, o);
    const float d = mo - m;
    v = fmaf(d * d, 8.f * o, v + vo);
    m = 0.5f * (m + mo);
  }
  const float var = fmaf(v, 1.f / DM, 1e-5f);
  float rs = rsqrtf(var);
  rs = rs * fmaf(-0.5f * var * rs, rs, 1.5f);
  Row y;
#pragma unroll
  for (int i = 0; i < 8; i++) y.w[i] = pack_bf16((x[2 * i] - m) * rs, (x[2 * i + 1] - m) * rs);
  return y;
}
__device__ __forceinline__ Row warp_ln(const Row& r) { float e = 0.f; return warp_ln(r, e); }
__device__ __forceinline__ Row load_row(const bf16* p, int lane) {
  Row r;
#pragma unroll
  for (int q = 0; q < 4; q++) { const uint2 v = ld_rlx64(p + lane * 4 + q * 128); r.w[2 * q] = v.x; r.w[2 * q + 1] = v.y; }
  return r;
}
__device__ __forceinline__ void store_row_img(uint8_t* img, int rr, int lane, const Row& r) {
  uint8_t* p = img + (lane >> 4) * 4096 + rr * 128 + ((((lane & 15) >> 1) ^ (rr & 7)) << 4) + (lane & 1) * 8;
#pragma unroll
  for (int q = 0; q < 4; q++) *(uint2*)(p + q * 8192) = make_uint2(r.w[2 * q], r.w[2 * q + 1]);
}

constexpr int C_WO = 0;
constexpr int C_X = 49152;
constexpr int C_M = C_X + 65536;
constexpr int C_Q = C_M + 24576;
constexpr int C_K = C_Q + 10240, C_V = C_K + 10240;
constexpr int C_SA = C_V + 10240, C_SB = C_SA + 8192;
constexpr int C_O = C_SB + 8192;
constexpr int C_OT = C_O + 6144;
constexpr int C_PI = C_OT + 16384;
constexpr int C_BAR = C_PI + 8192;
constexpr int C_SMEM = C_BAR + 384 + 1024 + TREXTRA;
constexpr int C_STG = C_X + 32768;
static_assert(C_STG + 131072 <= C_BAR, "staging");
enum { B_M0 = 0, B_M1, B_M2, B_R, B_X = B_R + 4, B_O, B_T, B_F, B_XL, B_U, B_P1, B_P2, B_OT, B_XF, B_XA, B_I, B_PI, B_J, B_W, B_WO, B_NUM };
static_assert(B_NUM <= 24, "barriers");
constexpr int C_POL = C_BAR + 192, C_INFO = C_BAR + 208;
enum { NB_ALL = 0, NB_M0, NB_PV, NB_W0, NB_TA, NB_M1, NB_M2, NB_RD, NB_V, NB_SM, NB_C, NB_GO };
constexpr float SCALE_LOG2E = 0.08838834764831845f * 1.4426950408889634f;
#define N0STEPS 9
#define N2STEPS 12
#define FGATE 1
#define NSSTEPS 0
constexpr int KA = 32 - NSSTEPS - N2STEPS, K3 = KA - N0STEPS;
static_assert(KA % 4 == 0, "the rows of layer 1 are refilled in two parts");
#define BGATE 0
#define W0EARLY 0
#define PVEARLY 1
#define S1GATE 0
#define IGRP 0
#define SHIPLATE 7
#define SHIP 1024
#define GATE_P 2250
#define GATE_W 170
#define EXPF 0
#define GATE_G 200
#define GATE_M 3230
#define HOLE0 22
#define HOLE1 28
#define HOLE2 32
__device__ __forceinline__ uint32_t gtime() { uint32_t t; asm volatile("mov.u32 %0, %%globaltimer_lo;" : "=r"(t) :: "memory"); return t; }
__device__ __forceinline__ void wait_clock(uint32_t t) {
  asm volatile("{ .reg .pred p; .reg .b32 c; .reg .b64 cc;\nL: mov.u64 cc, %%clock64; cvt.u32.u64 c, cc; sub.u32 c, c, %0; setp.lt.s32 p, c, 0; @p bra L; }" ::"r"(t) : "memory");
}
__device__ __forceinline__ void bar_sync_z(int id, int n, uint32_t z) {
  asm volatile("{ .reg .pred p; setp.eq.u32 p, %2, 0; @p bar.sync %0, %1; }" ::"r"(id), "r"(n), "r"(z) : "memory");
}

__device__ __forceinline__ int probe_home(uint32_t* p, int lane) {
  uint32_t best[2] = {~0u, ~0u};
#pragma unroll 1
  for (int rep = 0; rep < 3; rep++) {
#pragma unroll
    for (int pg = 0; pg < 2; pg++) {
      uint32_t t0, t1, v = 0;
      asm volatile("mov.u32 %0, %%clock;" : "=r"(t0) :: "memory");
      asm volatile("{ .reg .pred p; setp.eq.u32 p, %2, 0; @p atom.relaxed.gpu.global.exch.b32 %0, [%1], %3; }" : "+r"(v) : "l"(p + pg * 1024), "r"(lane), "r"(rep) : "memory");
      asm volatile("{ .reg .pred p; setp.ne.u32 p, %1, 0x13572468; mov.u32 %0, 0; @p mov.u32 %0, %%clock; }" : "=r"(t1) : "r"(v) : "memory");
      best[pg] = min(best[pg], t1 - t0);
    }
  }
  return __shfl_sync(~0u, max(-150, min(150, (int)(best[1] - best[0]))), 0);
}
__device__ __forceinline__ uint32_t home_flip(const void* p) { const uint32_t a = (uint32_t)(size_t)p; return ((a >> 16) ^ (a >> 17) ^ (a >> 19)) & 1; }
__device__ __forceinline__ uint32_t ppage(uint32_t lp, uint32_t pol) { return lp ? 3 - pol : pol; }
__device__ __forceinline__ uint32_t and_x(uint32_t a, uint32_t b, uint32_t m) {
  uint32_t d; asm("lop3.b32 %0, %1, %2, %3, 0x42;" : "=r"(d) : "r"(a), "r"(b), "r"(m)); return d;
}
__device__ __forceinline__ uint32_t and3(uint32_t a, uint32_t b, uint32_t c) {
  uint32_t d; asm("lop3.b32 %0, %1, %2, %3, 0x80;" : "=r"(d) : "r"(a), "r"(b), "r"(c)); return d;
}

template <int N> struct IC { static constexpr int value = N; };
template <class F> __device__ __forceinline__ void static_for2(F f) { f(IC<0>()); f(IC<1>()); }
template <class F> __device__ __forceinline__ void static_for3(F f) { f(IC<0>()); f(IC<1>()); f(IC<2>()); }
__device__ __forceinline__ void stage_weights(uint32_t stage, const CUtensorMap* map, int col, int row, uint32_t mbar) {
  mbar_expect_tx(mbar, 131072);
#pragma unroll 1
  for (int i = 0; i < 4; i++)
    asm volatile("cp.async.bulk.tensor.2d.shared::cluster.global.mbarrier::complete_tx::bytes [%0], [%1, {%3, %4}], [%2];"
                 ::"r"(stage + (i & 1) * 65536 + (i >> 1) * 32768), "l"(map), "r"(mbar), "r"(col + (i & 1) * 64), "r"(row + (i >> 1) * 256) : "memory");
}
__device__ __forceinline__ void load_wfrags(uint32_t (&wA)[32][4], uint32_t stage, int w, int lane) {
  const int mi = lane >> 3, r = lane & 7;
  const uint32_t a = stage + (w >> 2) * 65536 + ((mi >> 1) * 8 + r) * 128 + ((((w & 3) * 2 + (mi & 1)) ^ r) << 4);
#pragma unroll
  for (int ks = 0; ks < 32; ks++) ldsm4t(wA[ks], a + ks * 2048);
}
template <int K0, int K1>
__device__ __forceinline__ void tok_seq(float (&d)[16], const uint32_t (&wA)[32][4], uint64_t desc, uint32_t wave) {
#pragma unroll
  for (int k = K0; k < K1; k++) {
    const int ks = k & 31;
    constexpr int HM0 = 1, HM1 = 2, HM2 = 4;
    const int hm = (k == HOLE0 ? HM0 : 0) | (k == HOLE1 ? HM1 : 0) | (k == HOLE2 ? HM2 : 0);
    if (hm) bar_sync_z(NB_RD, 384, ((hm >> wave) & 1) ^ 1);
    if (ks == 0) wg_rs32<0, 0>(d, wA[ks], desc);
    else wg_rs32<0, 1>(d, wA[ks], desc + (ks >> 2) * 256 + (ks & 3) * 2);
  }
}
template <int K0, int K1>
__device__ __forceinline__ void mem_part(float (&d)[12], const uint32_t (&wA)[32][4], uint64_t desc) {
#pragma unroll
  for (int ks = K0; ks < K1; ks++) {
    if (ks == 0) wg_rs24<1, 0>(d, wA[ks], desc);
    else wg_rs24<1, 1>(d, wA[ks], desc + ks * 48);
  }
}
__device__ __forceinline__ void out_tile(float (&d)[12], uint64_t da, uint64_t db) {
#pragma unroll
  for (int i = 0; i < 8; i++) { if (i == 0) wg_ss24<0>(d, da, db); else wg_ss24<1>(d, da + i * 128, db + (i >> 1) * 32 + (i & 1) * 2); }
}
__device__ __forceinline__ void tok_pack(uint32_t (&p)[8], const float (&d)[16]) {
#pragma unroll
  for (int i = 0; i < 8; i++) p[i] = pack_bf16(d[2 * i], d[2 * i + 1]);
}
__device__ __forceinline__ void tok_store(uint32_t dst, const uint32_t (&p)[8]) {
  stsm4(dst, p[0], p[1], p[2], p[3]);
  stsm4(dst + 4096, p[4], p[5], p[6], p[7]);
}
template <class T> __device__ __forceinline__ T keep(T v) { asm volatile("" : "+r"(v)); return v; }
__device__ __forceinline__ uint32_t pin(uint32_t v) { return __shfl_sync(~0u, v, threadIdx.x & 31); }

#define TRC blockIdx.x
#define TRS (C_BAR + 384)
__device__ __forceinline__ void chain_proj(const uint32_t sb, const int w, const int lane_, const uint32_t rank) {
  uint32_t wA[32][4];
  mbar_wait(sb + C_BAR + B_W * 8, 0, 30);
  if (w == 0) { HD(2) }
  load_wfrags(wA, sb + C_STG, w, lane_);
  bar_arrive(NB_ALL, 384);
  const int lane = pin(lane_);
  const uint32_t bars = sb + C_BAR;
  const uint32_t quad = pin(sb + (lane_ >> 4) * 2048 + (lane_ & 15) * 16);
  const uint32_t own = C_Q + rank * 10240;
  const uint64_t dX1 = mk_desc(sb + C_X, 16, 1024, 1), dX2 = dX1 + 2048;
  const uint64_t dM = mk_desc(sb + C_M, 128, 256, 0);
  const uint32_t r1 = rank == 0 ? 1 : 0, r2 = rank == 2 ? 1 : 2;
  const uint32_t xa = pin(sb + own + 8192 + w * 256 + lane_ * 4);
  const uint32_t a1x = pin(mapa_u32(xa, r1)), a2x = pin(mapa_u32(xa, r2));
  const uint32_t b1x = pin(mapa_u32(bars + B_X * 8, r1)), b2x = pin(mapa_u32(bars + B_X * 8, r2));
  const uint32_t wave = rank == 2 ? 0 : rank + 1;
  float a[16];
  wg_fence();
  tok_seq<32, 32 + KA>(a, wA, mk_desc(__shfl_sync(~0u, sb, 0) + C_X, 16, 1024, 1), 3);
  wg_commit();
  wg_wait<0>();
  mbar_arrive_z(bars + B_XA * 8, lane);
#pragma unroll 1
  for (int st = 0;; st++) {
    uint32_t pk[8];
    wg_fence();
    if (NSSTEPS) bar_sync(NB_SM, 416);
    tok_seq<32 + KA, 32 + KA + NSSTEPS>(a, wA, dX1, 3);
    bar_sync(NB_PV, NSSTEPS ? 384 : 416);
    tok_seq<32 + KA + NSSTEPS, 64>(a, wA, dX1, 3);
    wg_commit();
    wg_wait<0>();
    acc_fence(a);
    mbar_arrive_z(bars + B_XF * 8, lane);
    tok_pack(pk, a);
    TR(1)
    bar_sync(NB_W0, 416);
    tok_store(quad + w * 256 + (rank == 0 ? own : C_SA), pk);
    __syncwarp();
    mbar_arrive_z(bars + B_P1 * 8, lane);
    wg_fence();
    tok_seq<0, 32>(a, wA, dX2, wave);
    wg_commit();
    const uint32_t info = lds32(sb + C_INFO + (st & 1) * 4);
    TR(2)
    wg_wait<0>();
    acc_fence(a);
    TR(3)
    tok_pack(pk, a);
    tok_store(quad + w * 256 + (rank == 0 ? C_SA : own), pk);
    if (rank == 2) tok_store(quad + w * 256 + C_SB, pk);
    __syncwarp();
    mbar_arrive_z(bars + B_P2 * 8, lane);
    TR(4)
    wg_fence();
    tok_seq<32, 32 + K3>(a, wA, dX1, wave);
    TR(6)
    {
      float am[12];
      bar_sync(NB_M0, 384);
      mem_part<0, 10>(am, wA, dM);
      TR(7)
      bar_sync(NB_M1, 384);
      mem_part<10, 21>(am, wA, dM);
      bar_sync(NB_M2, 384);
      mem_part<21, 32>(am, wA, dM);
      wg_commit();
      bar_sync(NB_V, 384);
      const bool redo = __any_sync(~0u, lds32(sb + C_INFO + 16 + (lane & 3) * 32) != 0);
      if (__builtin_expect(redo, 0)) {
        wg_wait<0>();
        wg_fence();
        mem_part<0, 32>(am, wA, dM);
        wg_commit();
      }
      wg_wait<0>();
      acc_fence(am);
      TR(8)
      const uint32_t x00 = pack_bf16(am[0], am[1]), x01 = pack_bf16(am[2], am[3]), x10 = pack_bf16(am[4], am[5]), x11 = pack_bf16(am[6], am[7]);
      const uint32_t y0 = pack_bf16(am[8], am[9]), y1 = pack_bf16(am[10], am[11]), x20 = info ? x10 : y0, x21 = info ? x11 : y1;
      st_async32<0>(a1x, rank == 0 ? x10 : x00, b1x); st_async32<0>(a2x, rank == 2 ? x10 : x20, b2x);
      st_async32<128>(a1x, rank == 0 ? x11 : x01, b1x); st_async32<128>(a2x, rank == 2 ? x11 : x21, b2x);
      sts32(xa, rank == 0 ? x00 : rank == 2 ? x20 : x10); sts32(xa + 128, rank == 0 ? x01 : rank == 2 ? x21 : x11);
      if (__builtin_expect(info, 0)) {
        const uint32_t o = (info & 3) * 2048 - 8192;
        if (rank == 2) { sts32(xa + o, y0); sts32(xa + o + 128, y1); }
        else { st_async32<0>(a2x + o, y0, b2x + (B_T - B_X) * 8); st_async32<128>(a2x + o, y1, b2x + (B_T - B_X) * 8); }
      }
      __syncwarp();
      mbar_arrive_z(bars + B_X * 8, lane);
    }
    TR(9)
    wg_fence();
    tok_seq<32 + K3, 32 + KA>(a, wA, dX1, 3);
    wg_commit();
    TR(0)
    wg_wait<0>();
    if (st == NSTEP - 1) break;
    mbar_arrive_z(bars + B_XA * 8, lane);
  }
  if (NSSTEPS) bar_arrive(NB_SM, 416);
  bar_arrive(NB_PV, NSSTEPS ? 384 : 416);
}

__device__ __forceinline__ void chain_mem(const uint32_t sb, const int w, const int lane_, const uint32_t rank, const int h,
                                          const bf16* __restrict__ mem0) {
  const int lane = pin(lane_);
  const int wave = rank == 2 ? 0 : rank + 1;
  const int c = w - 8, t = c * 32 + lane, b = wave * 32 + h;
  const uint32_t bars = sb + C_BAR;
  const int wi = (lane & 1) * 2 + (lane >> 4), cq = (lane >> 2) & 3;
  mbar_expect_tx_z(bars + B_X * 8, 4096, t); mbar_expect_tx_z(bars + B_O * 8, 4096, t);
  if (NSSTEPS) bar_arrive(NB_SM, 416);
  bar_arrive(NB_PV, NSSTEPS ? 384 : 416); bar_arrive(NB_W0, 416); bar_arrive(NB_RD, 384);
  uint32_t m0[16];
#pragma unroll
  for (int i = 0; i < 16; i++) m0[i] = *(const uint32_t*)(mem0 + (lane >> 2) * DM + (c * 16 + i) * 8 + (lane & 3) * 2);
  uint32_t* pp = g_M + c * 16384 + 14 * 1024 + (blockIdx.x & 31) * 32;
  st_rlx32(pp + lane, 0); st_rlx32(pp + 1024 + lane, 0);
  mbar_wait(bars + B_W * 8, 0, 32);
  {
    uint32_t* p = pp;
    const int vote = probe_home(p, lane);
    sts32(sb + C_POL + c * 4, home_flip(p) ? -vote : vote);
    bar_sync(NB_C, 128);
    const uint4 v = lds128(sb + C_POL);
    const uint32_t side = (int)(v.x + v.y + v.z + v.w) > 0;
    bar_sync(NB_C, 128);
    sts32(sb + C_POL + c * 4, side ^ home_flip(p));
    sts32(sb + C_INFO + 8, side ^ home_flip(g_P + b * 4096));
    if (c == 0) { HD(0) }
    wait_count(g_ex.ready, 96, 35);
    if (c == 0) { HD(1) }
    st_rlx32(&g_fl.pol[b], (side ^ home_flip(g_P + b * 4096)) + 1);
  }
  bar_sync(NB_ALL, 384);
  if (c == 0) { HD(3) }
  mbar_arrive_remote_z(mapa_u32(bars + B_F * 8, (rank + 1 + (t & 1)) % 3), t >> 1);
#pragma unroll
  for (int i = 0; i < 16; i += 4) {
    const uint32_t a = sb + C_M + (c * 8 + i / 2 + (lane >> 4)) * 768 + (lane & 15) * 16;
    stsm4t(a, m0[i], m0[i + 1], m0[i + 2], m0[i + 3]); stsm4t(a + 256, m0[i], m0[i + 1], m0[i + 2], m0[i + 3]); stsm4t(a + 512, m0[i], m0[i + 1], m0[i + 2], m0[i + 3]);
  }
  sts32(sb + C_INFO + 16 + c * 32, 0);
  fence_async_smem();
  bar_arrive(NB_M0, 384); bar_arrive(NB_M1, 384); bar_arrive(NB_M2, 384);
  mbar_wait(bars + B_F * 8, 0, 34);
  bar_arrive(NB_V, 384);
  mbar_wait(bars + B_WO * 8, 0, 33);
  uint32_t pgbits, polP;
  {
    const int tl = lane / 3, u = ((tl * 3 + rank) * 4 + c) * 3 + (lane - tl * 3);
    uint32_t pol;
    int it = 0;
    do { pol = ld_rlx32(&g_fl.pol[lane < 9 && u < 96 ? u : b]); give_up(it++, SPIN_LIMIT, 40); } while (__any_sync(~0u, pol == 0));
    pgbits = __reduce_or_sync(~0u, lane < 9 ? ppage(h >> 4, (pol - 1) & 1) << (2 * lane) : 0u);
    polP = __shfl_sync(~0u, pol - 1, 9);
  }
  const int mi = lane >> 3;
  const uint32_t l16 = pin(sb + lane * 16);
  const uint32_t r1 = rank == 2 ? 0 : rank + 1, r2 = rank == 0 ? 2 : rank - 1;
  const uint32_t oa = pin(sb + C_O + rank * 2048 + (lane >> 2) * 64 + (((lane & 3) ^ (lane >> 3)) << 4));
  const uint32_t a1 = mapa_u32(oa, r1), b1 = mapa_u32(bars + B_O * 8, r1), a2 = mapa_u32(oa, r2), b2 = mapa_u32(bars + B_O * 8, r2);
  const uint64_t dWo = mk_desc(sb + C_WO, 8192, 1024, 1), dO = mk_desc(sb + C_O, 16, 2048, 2);
  const uint64_t dK = mk_desc(sb + C_K, 128, 2048, 0);
  const uint64_t dV = mk_desc(sb + C_V, 2048, 128, 0), dVm = mk_desc(sb + C_V + 8192, 0, 128, 0);
  const uint32_t qa = pin(sb + C_Q + (c ? c + 1 : mi & 1) * 2048 + (mi >> 1) * 128 + (lane & 7) * 16);
  const uint32_t dg = ((lane >> 2) < 2 * (lane & 3) ? 1 : 0) | ((lane >> 2) < 2 * (lane & 3) + 1 ? 2 : 0);
  const uint32_t msk = pin(c == 0 ? dg | dg << 4 : c == 1 ? dg << 2 | 3 << 4 : c == 2 ? dg << 4 : 0);
  uint8_t* Pw = (uint8_t*)g_P + (rank * 4 + c) * 3 * 16384 + (h & 15) * 256 + ((lane * 4) ^ ((h & 3) << 5));
  const uint32_t pia = pin(sb + C_PI + ((lane >> 4) * 4 + (lane & 3)) * 256 + ((c * 64 + cq * 16) ^ ((lane & 3) << 5)));
  uint8_t* Mw = (uint8_t*)g_M + (b >> 5) * 16384 + ((lane & 2) ? 4096 : 12288) + (b & 31) * 256 + c * 64 + cq * 16 + wi * 4;
  uint32_t nretry = 0, nupd = 0;
  bar_arrive(NB_GO, 160);

  { const int st = 71; (void)st; STAT(0, lds32(sb + C_POL + c * 4)) STAT(1, polP) STAT(2, (uint32_t)(size_t)(g_M + c * 16384)) STAT(3, (uint32_t)(size_t)(g_P + b * 4096)) }
#pragma unroll 1
  for (int st = 0;; st++) {
    mbar_wait(bars + B_P1 * 8, st & 1, 38);
    mbar_wait(bars + B_T * 8, st & 1, 42);
    STAT(10, clk32())
    {
      float s[20];
      {
        uint32_t q[8][4];
        if (c == 3) mbar_wait(bars + B_X * 8, st & 1, 41);
#pragma unroll
        for (int i = 0; i < 8; i++) ldsm4t(q[i], qa + i * 256);
        if (c != 3) { mbar_wait(bars + B_X * 8, st & 1, 41); fence_async_smem(); }
        STAT(11, clk32())
        TR(0)
        wg_fence();
#pragma unroll
        for (int i = 0; i < 8; i++) { if (i == 0) wg_rs40<0>(s, q[i], dK); else wg_rs40<1>(s, q[i], dK + i * 16); }
        wg_commit();
        wg_wait<0>();
        if (NSSTEPS) bar_arrive(NB_SM, 416);
        acc_fence(s);
      }
      TR(1)
      const bool w0 = c == 0;
      float z[10] = {s[16], s[17], s[0], s[1], w0 ? s[18] : s[4], w0 ? s[19] : s[5], w0 ? s[2] : s[8], w0 ? s[3] : s[9], w0 ? s[6] : s[12], w0 ? s[7] : s[13]};
      if (msk & 1) z[2] = -INFINITY;
      if (msk & 2) z[3] = -INFINITY;
      if (msk & 4) z[6] = -INFINITY;
      if (msk & 8) z[7] = -INFINITY;
      if (msk & 16) z[8] = -INFINITY;
      if (msk & 32) z[9] = -INFINITY;
      float m0 = fmaxf(fmaxf(z[0], z[1]), fmaxf(z[2], z[3])), m1 = fmaxf(fmaxf(fmaxf(z[4], z[5]), fmaxf(z[6], z[7])), fmaxf(z[8], z[9]));
      m0 = fmaxf(m0, __shfl_xor_sync(~0u, m0, 1)); m1 = fmaxf(m1, __shfl_xor_sync(~0u, m1, 1));
      m0 = fmaxf(m0, __shfl_xor_sync(~0u, m0, 2)); m1 = fmaxf(m1, __shfl_xor_sync(~0u, m1, 2));
      if (!w0) m0 = m1 = fmaxf(m0, m1);
      m0 *= -SCALE_LOG2E; m1 *= -SCALE_LOG2E;
      uint32_t p[5];
#pragma unroll
      for (int k = 0; k < 5; k++) {
        z[2 * k] = ex2_fast(fmaf(z[2 * k], SCALE_LOG2E, k < 2 ? m0 : m1)); z[2 * k + 1] = ex2_fast(fmaf(z[2 * k + 1], SCALE_LOG2E, k < 2 ? m0 : m1));
        p[k] = pack_bf16(z[2 * k], z[2 * k + 1]);
      }
      const uint32_t p2 = w0 ? 0 : p[2], p3 = w0 ? 0 : p[3], p4 = w0 ? 0 : p[4];
      float oA[32], oB[32];
      wg_fence();
      wg_rs64<0>(oA, p[0], p[2], 0, 0, dVm); wg_rs64<1>(oA, p[1], p[3], p2, p[4], dV); wg_rs64<1>(oA, p3, 0, p4, 0, dV + 256);
      wg_commit();
      wg_rs64<0>(oB, p[0], p[2], 0, 0, dVm + 64); wg_rs64<1>(oB, p[1], p[3], p2, p[4], dV + 64); wg_rs64<1>(oB, p3, 0, p4, 0, dV + 320);
      wg_commit();
      float l0 = (z[0] + z[1]) + (z[2] + z[3]), l1 = ((z[4] + z[5]) + (z[6] + z[7])) + (z[8] + z[9]);
      if (!w0) l0 += l1;
      l0 += __shfl_xor_sync(~0u, l0, 1); l1 += __shfl_xor_sync(~0u, l1, 1);
      l0 += __shfl_xor_sync(~0u, l0, 2); l1 += __shfl_xor_sync(~0u, l1, 2);
      float i0, i1;
      asm volatile("rcp.approx.ftz.f32 %0, %2; rcp.approx.ftz.f32 %1, %3;" : "=f"(i0), "=f"(i1) : "f"(l0), "f"(l1));
      asm volatile("st.shared.v2.f32 [%0], {%1,%2};" ::"r"(sb + C_INFO + 24), "f"(i0), "f"(i1) : "memory");
      const uint32_t ta = l16 + C_OT + (st & 1) * 8192 + (c ? c + 1 : 0) * 2048;
      auto leave = [&](const float (&o)[32], auto hc) {
        constexpr int H = decltype(hc)::value;
        uint32_t e[8];
#pragma unroll
        for (int j = 0; j < 8; j++) e[j] = pack_bf16(o[4 * j] * i0, o[4 * j + 1] * i0);
        if (c == 3) {
          static_for2([&](auto bc) {
            constexpr int B = decltype(bc)::value;
            asm volatile("st.async.weak.shared::cluster.mbarrier::complete_tx::bytes.v4.b32 [%0 + %9], {%5,%6,%7,%8}, [%1];\n"
                         "st.async.weak.shared::cluster.mbarrier::complete_tx::bytes.v4.b32 [%2 + %9], {%5,%6,%7,%8}, [%3];\n"
                         "st.shared.v4.b32 [%4 + %9], {%5,%6,%7,%8};"
                         ::"r"(a1), "r"(b1), "r"(a2), "r"(b2), "r"(oa), "r"(e[4 * B]), "r"(e[4 * B + 1]), "r"(e[4 * B + 2]), "r"(e[4 * B + 3]),
                           "n"(H * 1024 + B * 512) : "memory");
          });
        } else {
          stsm4(ta + H * 1024, e[0], e[1], e[2], e[3]); stsm4(ta + H * 1024 + 512, e[4], e[5], e[6], e[7]);
          if (w0) {
#pragma unroll
            for (int j = 0; j < 8; j++) e[j] = pack_bf16(o[4 * j + 2] * i1, o[4 * j + 3] * i1);
            stsm4(ta + 2048 + H * 1024, e[0], e[1], e[2], e[3]); stsm4(ta + 2048 + H * 1024 + 512, e[4], e[5], e[6], e[7]);
          }
        }
      };
      wg_wait<1>();
      acc_fence(oA);
      leave(oA, IC<0>());
      wg_wait<0>();
      if (PVEARLY) bar_arrive(NB_PV, NSSTEPS ? 384 : 416);
      acc_fence(oB);
      leave(oB, IC<1>());
      if (!PVEARLY) bar_arrive(NB_PV, NSSTEPS ? 384 : 416);
      __syncwarp();
      mbar_arrive_z(bars + (c == 3 ? B_O : B_OT) * 8, lane);
      TR(2)
    }
    mbar_wait(bars + B_O * 8, st & 1, 43);
    if (st == NSTEP - 1) break;
    uint32_t info;
    {
      const uint32_t tag = (st & 1) ^ 1;
      float oc0[12], oc1[12], oc2[12];
      fence_async_smem();
      TR(3)
      wg_fence();
      out_tile(oc0, dWo, dO);
      wg_commit();
      out_tile(oc1, dWo + 1024, dO);
      wg_commit();
      asm volatile("" : "+r"(pgbits));
      auto put = [&](const float (&oc)[12], auto tlc) {
        constexpr int TL = decltype(tlc)::value;
        static_for3([&](auto jc) {
          constexpr int j = decltype(jc)::value;
          uint8_t* p = Pw + ((pgbits >> (2 * (TL * 3 + j))) & 3) * 4096;
          asm volatile("st.relaxed.gpu.global.u32 [%0 + %3], %1; st.relaxed.gpu.global.u32 [%0 + %3 + 128], %2;" ::"l"(p),
                       "r"((pack_bf16(oc[4 * j], oc[4 * j + 1]) & ~1u) | tag), "r"((pack_bf16(oc[4 * j + 2], oc[4 * j + 3]) & ~1u) | tag),
                       "n"((TL * 36 + j) * 16384) : "memory");
        });
      };
      wg_wait<1>();
      acc_fence(oc0);
      put(oc0, IC<0>());
      sts32(sb + C_INFO + 24, clk32());
      TR(4)
      out_tile(oc2, dWo + 2048, dO);
      wg_commit();
      wg_wait<1>();
      acc_fence(oc1);
      put(oc1, IC<1>());
      if (W0EARLY) bar_arrive(NB_W0, 416);
      bar_sync(NB_TA, 192);
      TR(5)
      wg_wait<0>();
      if (!W0EARLY) bar_arrive(NB_W0, 416);
      info = lds32(sb + C_INFO + ((st + 1) & 1) * 4);
      acc_fence(oc2);
      if (rank != 2) put(oc2, IC<2>());
      mbar_arrive_remote_z(((t & 1) ? b2 : b1) + (B_F - B_O) * 8, t >> 1);
      mbar_expect_tx_z(bars + ((t & 1) ? B_O : B_X) * 8, 4096, t >> 1);
      TR(6)
    }
    const int sn = (st + 1) & 3;
    uint8_t* mw = Mw + sn * 65536;
    asm volatile("" : "+l"(mw));
    if (__builtin_expect((st < DELTA && b % 3 != 0) || (info && b % 3 == 2), 0)) {
      bar_arrive(NB_RD, 384);
      const int col = b / 3 * 16 + c * 4 + ((lane >> 2) & 3), r0 = (lane & 1) * 4 + (lane >> 4) * 2;
      const bool upd = info && b % 3 == 2;
      if (upd) mbar_wait(bars + B_U * 8, nupd & 1, 39);
      uint32_t hv[2];
#pragma unroll
      for (int i = 0; i < 2; i++) {
        const int r = r0 + i, sg = st + 1 - DELTA;
        const void* p = !upd ? (const void*)(mem0 + r * DM + col) : r == (int)(info >> 4) ? (const void*)(g_x2p[sg][1] + col)
                      : (const void*)(g_xs[1] + sg * 32768 + (col >> 6) * 4096 + ((info & 3) * 8 + r) * 128 + ((((col >> 3) ^ r) & 7) << 4) + (col & 7) * 2);
        asm volatile("ld.relaxed.gpu.global.u16 %0, [%1];" : "=r"(hv[i]) : "l"(p) : "memory");
      }
      st_rlx32(mw, hv[0] | hv[1] << 16);
      STAT(1, 0) STAT(2, 0) STAT(4, 0)
    } else {
      const uint32_t flip = (st & 1) ? ~0u : 0u;
      const bool u16 = lane & 16;
      const uint32_t bs = (lane & 4) ? 0x3f800000u : 0x00003f80u, bs0 = (lane & 8) ? 0u : bs, bs1 = (lane & 8) ? bs : 0u;
      STATC(c_rdy)
      mbar_wait(bars + B_PI * 8, st & 1, 37);
      TR(7)
      uint4 q0 = lds128(pia), q1 = lds128(pia + 2048), q2 = lds128(pia + 4096), q3 = lds128(pia + 6144);
      int it = 0;
#pragma unroll 1
      while (true) {
        float d0[4] = {0.f, 0.f, 0.f, 0.f}, d1[4] = {0.f, 0.f, 0.f, 0.f};
        mma16816(d0, q0.x, q0.y, q0.z, q0.w, bs0, bs1);
        mma16816(d1, q1.x, q1.y, q1.z, q1.w, bs0, bs1);
        mma16816(d0, q2.x, q2.y, q2.z, q2.w, bs0, bs1);
        mma16816(d1, q3.x, q3.y, q3.z, q3.w, bs0, bs1);
        const bool all = __all_sync(~0u, (int)and3(and_x(q0.x, q1.x, flip), and_x(q2.x, q3.x, flip), 1u));
        const float a0 = d0[0] + d1[0], a1 = d0[1] + d1[1], a2 = d0[2] + d1[2], a3 = d0[3] + d1[3];
        asm volatile("{ .reg .pred p; setp.ne.u32 p, %0, 0; @p bar.arrive %1, 384; }" ::"r"((uint32_t)all), "n"((int)NB_RD) : "memory");
        const uint32_t mword = pack_bf16((u16 ? a2 : a0) + __shfl_xor_sync(~0u, u16 ? a0 : a2, 16), (u16 ? a3 : a1) + __shfl_xor_sync(~0u, u16 ? a1 : a3, 16));
        asm volatile("{ .reg .pred p; setp.ne.u32 p, %2, 0; @p st.relaxed.gpu.global.u32 [%0], %1; }" ::"l"(mw), "r"(mword), "r"((uint32_t)all) : "memory");
        if (__builtin_expect(all, 1)) break;
        give_up(++it, SPIN_LIMIT, 44);
        const uint8_t* Pr0 = (const uint8_t*)g_P + b * 16384 + (pia - sb - C_PI) + polP * 4096;
        const uint8_t* Pr1 = Pr0 + (3 - 2 * polP) * 4096;
        q0 = ld_rlx128(Pr0); q1 = ld_rlx128(Pr0 + 2048); q2 = ld_rlx128(Pr1); q3 = ld_rlx128(Pr1 + 2048);
      }
      STATC(c_mst)
      STAT(1, c_rdy - tref) STAT(2, c_mst - tref) STAT(4, it)
      TRV(14, it)
    }
    STAT(0, lds32(sb + C_INFO + 24) - tref) STAT(3, tref)
    nupd += info != 0;
    TR(9)
    {
      const uint32_t ma = l16 + C_M + c * 2048 + mi * 4;
      auto scan = [&](uint32_t m, uint32_t a) { return __vimax3_u32(__vimax3_u32(m, lds32(a), lds32(a + 512)), lds32(a + 1024), lds32(a + 1536)); };
      mbar_wait(bars + B_M0 * 8, (st + 1) & 1, 45);
      bar_arrive(NB_M0, 384);
      STATC(c_g0)
      TR(10)
      uint32_t m = scan(0, ma);
      mbar_wait(bars + B_M1 * 8, (st + 1) & 1, 46);
      bar_arrive(NB_M1, 384);
      STATC(c_g1)
      TR(11)
      m = scan(m, ma + 8192);
      mbar_wait(bars + B_M2 * 8, (st + 1) & 1, 47);
      STATC(c_g2)
      TR(12)
      int it = 0;
      bar_arrive(NB_M2, 384);
      const bool redo = __any_sync(~0u, scan(m, ma + 16384) == ~0u);
      sts32(sb + C_INFO + 16 + c * 32, redo);
      if (__builtin_expect(redo, 0)) {
#pragma unroll 1
        for (int g = 0; g < 3;) {
          if (!__any_sync(~0u, scan(0, ma + g * 8192) == ~0u)) { g++; continue; }
          give_up(++it, SPIN_LIMIT, 48);
          if (lane == 0) {
            mbar_expect_tx(bars + (B_R + c) * 8, 2048);
            bulk_g2s(sb + C_M + g * 8192 + c * 2048, (const uint8_t*)g_M + sn * 65536 + (lds32(sb + C_POL + sn * 4) ? 4096 : 12288) + g * 16384 + c * 2048,
                     2048, bars + (B_R + c) * 8);
          }
          __syncwarp();
          mbar_wait(bars + (B_R + c) * 8, nretry++ & 1, 49);
        }
      }
      bar_arrive(NB_V, 384);
      STAT(5, c_g0 - tref) STAT(7, c_g1 - tref) STAT(8, c_g2 - tref)
      STAT(9, clk32() - tref) STAT(6, it + redo * 256)
      TR(13)
      TRV(15, it)
      st_rlx32(Mw + (st & 3) * 65536, ~0u);
    }
  }
}

__device__ __forceinline__ void chain_dma(const uint32_t sb, const int w, const int lane, const uint32_t rank, const int h) {
  const uint32_t bars = sb + C_BAR;
  const int expf_ = EXPF;
  if (w == 12) {
    u64 best = 0;
    uint32_t nx = 0;
    auto load = [&](uint32_t dst, const uint8_t* src, uint32_t bytes) {
      mbar_expect_tx_z(bars + B_XL * 8, bytes, lane >> 1);
      if (lane < 2 && bytes) {
        fence_async_glb();
        bulk_g2s(sb + dst, src, bytes, bars + B_XL * 8);
      }
      __syncwarp();
      mbar_wait(bars + B_XL * 8, nx++ & 1, 52);
    };
    bar_arrive(NSSTEPS ? NB_SM : NB_PV, 416);
    wait_count(g_ex.ready, 96, 59);
    HD(6)
#pragma unroll 1
    for (int st = 0; st < NSTEP; st++) {
      const int sg = st - DELTA;
      const bool more = st + 1 < NSEG && !(expf_ & 4);
      uint32_t info = 0;
      if (sg >= 0) {
        const u64 k = wait_keys(g_fl.key[0][sg], lane, 50);
        if (k > best) { best = k; info = 4 | ((key_token(k) >> 3) & 3) | (key_token(k) & 7) << 4; }
      }
      TR(0)
      mbar_wait(bars + B_XA * 8, st & 1, 58);
      sts32(sb + C_INFO + (st & 1) * 4, info);
      if (st > 0) bar_arrive(NB_TA, 192);
      TR(1)
      load(lane ? C_X : C_X + 32768, lane ? g_xs[0] + (st + 1) * 32768 : g_xs[1] + sg * 32768, lane ? (more ? KA * 1024 : 0) : (sg >= 0 && !(expf_ & 8) ? 32768 : 0));
      bar_arrive(NB_W0, 416);
      TR(2)
      if (__builtin_expect(info, 0)) {
        int it = 0;
        while (ld_rlx32(g_fl.patch[sg]) == 0) { give_up(++it, SPIN_LIMIT, 56); warp_sleep(250); }
        sts32(sb + C_INFO + 20, clk32());
        __syncwarp();
        mbar_arrive_z(bars + B_U * 8, lane);
      }
      mbar_wait(bars + B_XF * 8, st & 1, 53);
      mbar_wait(bars + (B_M0 + BGATE) * 8, st & 1, 54);
      load(C_X + KA * 1024, g_xs[0] + (st + 1) * 32768 + KA * 1024, more && lane == 0 ? 32768 - KA * 1024 : 0);
      TR(3)
      bar_arrive(NSSTEPS ? NB_SM : NB_PV, 416);
    }
  } else if (w == 13) {
    constexpr uint32_t NP = 8192 / SHIP;
    const uint32_t o = (lane >> 1) * SHIP, own = sb + C_Q + rank * 10240, bt = bars + B_T * 8;
    const uint32_t d2 = 1 + (lane & 1);
    const uint32_t src2 = (rank == 0 ? sb + C_SA : rank == 1 ? own : sb + C_SB) + o;
    const uint32_t skip = (lane & 1) ? 4 | (o >> 11) : 8;
#pragma unroll 1
    for (int st = 0; st < NSTEP; st++) {
      mbar_wait(bars + B_P1 * 8, st & 1, 61);
      fence_async_smem();
      mbar_wait(bars + B_F * 8, st & 1, 60);
      if (st > 0) mbar_wait(bars + (S1GATE ? B_PI : B_J) * 8, (st - 1) & 1, 65);
      const uint32_t info = lds32(sb + C_INFO + (st & 1) * 4);
      TR(2)
      if (st < NSEG && rank != 0 && lane < 2 * NP && d2 == 1 && !(expf_ & 1)) bulk_s2r(mapa_u32(own + o, 0), sb + C_SA + o, SHIP, mapa_u32(bt, 0));
      __syncwarp();
      TR(3)
      mbar_wait(bars + B_P2 * 8, st & 1, 62);
      fence_async_smem();
      if (st > 0 && (SHIPLATE >> rank & 1)) mbar_wait(bars + B_I * 8, (st - 1) & 1, 64);
      TR(0)
      if (st >= DELTA && lane < 2 * NP && d2 != rank && (info & 7) != skip && !(expf_ & 2)) bulk_s2r(mapa_u32(own + o, d2), src2, SHIP, mapa_u32(bt, d2));
      __syncwarp();
      TR(1)
    }
  } else if (w == 14) {
    const int s0 = rank == 0 ? 0 : DELTA;
    const uint32_t tbytes = (expf_ & (rank ? 2 : 1)) ? 0 : 16384;
    mbar_expect_tx_z(bars + B_T * 8, s0 == 0 ? tbytes : 0, lane);
#pragma unroll 1
    for (int st = 0; st < NSTEP; st++) {
      const int sg = st - s0;
      const bool act = (unsigned)sg < (unsigned)NSEG;
      mbar_wait(bars + B_OT * 8, st & 1, 70);
      mbar_expect_tx_z(bars + B_T * 8, (unsigned)(sg + 1) < (unsigned)NSEG ? tbytes : 0, lane);
      fence_async_smem();
      const int s1 = rank && st < NSEG - 1 ? st + 1 : st;
      if (s1 != st) mbar_wait(bars + B_X * 8, s1 & 1, 71);
      TR(0)
      if (act && lane == 0 && !(expf_ & (rank ? 32 : 16))) {
        bulk_s2g(g_O[st & (OSLOTS - 1)][rank] + h * 8192, sb + C_OT + (st & 1) * 8192, 8192);
        asm volatile("cp.async.bulk.commit_group;" ::: "memory");
        asm volatile("cp.async.bulk.wait_group 0;" ::: "memory");
        asm volatile("fence.acq_rel.gpu;" ::: "memory");
      }
      __syncwarp();
      if (WLAG && s1 < NSTEP - 1) mbar_wait(bars + (FGATE ? B_M0 + FGATE - 1 : B_I) * 8, (s1 + (FGATE > 0)) & 1, 72);
      if (act && lane == 0) asm volatile("red.relaxed.gpu.global.add.u32 [%0], 1;" ::"l"(&g_fl.oflag[rank][sg][h >> 2]) : "memory");
      __syncwarp();
      TR(1)
    }
  } else {
    mbar_arrive_z(bars + B_M0 * 8, lane); mbar_arrive_z(bars + B_M1 * 8, lane); mbar_arrive_z(bars + B_M2 * 8, lane);
    const uint32_t wave = rank == 2 ? 0 : rank + 1, gate_p = GATE_P + wave * GATE_W, gate_g = GATE_G, gate_m = GATE_M;
    uint32_t nupd = 0, late = 128;
    bar_sync(NB_GO, 160);
#pragma unroll 1
    for (int st = 0; st < NSTEP - 1; st++) {
      mbar_wait(bars + B_X * 8, st & 1, 75);
      if (st < 4) { HD(8 + st) }
      if (st == NSTEP - 2) { HD(12) }
      mbar_wait(bars + B_T * 8, st & 1, 77);
      const uint32_t now = gtime() & ~31u, tag = (st + 1) & 31;
      if (lane == 0) st_rlx32(&g_fl.stamp[blockIdx.x], (now + late) | tag);
      late = 0;
      __syncwarp();
      wait_clock(clk32() + 550);
      uint32_t s0, s1, s2;
      int it = 0;
#pragma unroll 1
      do {
        s0 = ld_rlx32(&g_fl.stamp[lane]) ^ tag; s1 = ld_rlx32(&g_fl.stamp[32 + lane]) ^ tag; s2 = ld_rlx32(&g_fl.stamp[64 + lane]) ^ tag;
        give_up(it++, SPIN_LIMIT, 76);
      } while (__any_sync(~0u, ((s0 | s1 | s2) & 31) != 0));
      const uint32_t tref = now + __reduce_max_sync(~0u, __vimax3_s32((int)(s0 - now), (int)(s1 - now), (int)(s2 - now)));
      const uint32_t g0 = gtime();
      uint32_t g1, c1;
      it = 0;
      do { g1 = gtime(); c1 = clk32(); } while (g1 == g0 && ++it < 64);
      c1 -= (g1 - tref) * 7 / 4;
      sts32(sb + C_INFO + 12, c1);
      TR(0)
      bar_sync(NB_TA, 192);
      const int sn = (st + 1) & 3;
      const uint8_t* src = (const uint8_t*)g_M + sn * 65536 + (lds32(sb + C_POL + sn * 4) ? 4096 : 12288);
      {
        const uint32_t pol = lds32(sb + C_INFO + 8);
        const uint8_t* ps = (const uint8_t*)g_P + (wave * 32 + h) * 16384;
        if (lane == 0) {
          mbar_expect_tx(bars + B_PI * 8, 8192);
          wait_clock(c1 + gate_p);
          bulk_g2s(sb + C_PI, ps + pol * 4096, 4096, bars + B_PI * 8);
          bulk_g2s(sb + C_PI + 4096, ps + (3 - pol) * 4096, 4096, bars + B_PI * 8);
          mbar_arrive_z(bars + B_J * 8, 0);
        }
        __syncwarp();
      }
      c1 += gate_m;
      if (__builtin_expect(lds32(sb + C_INFO + ((st + 1) & 1) * 4), 0)) {
        late = rank == 2 ? 96 : 0;
        mbar_wait(bars + B_U * 8, nupd++ & 1, 78);
        const uint32_t c2 = lds32(sb + C_INFO + 20) + 1200;
        if ((int)(c2 - c1) > 0) c1 = c2;
      }
      mbar_expect_tx_z(bars + (B_M0 + lane) * 8, 8192, lane / 3);
      if (lane == 0) {
#pragma unroll
        for (int g = 0; g < 3; g++) {
          wait_clock(c1 + g * gate_g);
          bulk_g2s(sb + C_M + g * 8192, src + g * 16384, 8192, bars + (B_M0 + g) * 8);
          if (g == IGRP) mbar_arrive_z(bars + B_I * 8, 0);
        }
      }
      __syncwarp();
      TR(3)
    }
  }
}

struct ChainMaps { CUtensorMap w[3], wo; };
__global__ void __cluster_dims__(3, 1, 1) __launch_bounds__(512, 1)
chain_kernel(const __grid_constant__ ChainMaps maps, const bf16* __restrict__ mem0, const bf16* __restrict__ x0) {
  extern __shared__ __align__(1024) uint8_t smem_raw[];
  const uint32_t sb = (smem_u32(smem_raw) + 1023) & ~1023u;
  const int tid = threadIdx.x, lane = tid & 31;
  const int w = __shfl_sync(~0u, tid >> 5, 0);
  uint32_t rank;
  asm volatile("mov.u32 %0, %%cluster_ctarank;" : "=r"(rank));
  const int h = blockIdx.x / 3;
  asm volatile("griddepcontrol.launch_dependents;" ::: "memory");
  TG(0)
  const int row2 = 32 + blockIdx.x * 16 + w, row3 = 1568 + min(w, 4) * 96 + blockIdx.x;
  Row xr[4] = {load_row(x0 + row2 * DM, lane), load_row(x0 + row3 * DM, lane), load_row(x0 + w * DM, lane), load_row(x0 + (w + 16) * DM, lane)};
  if (tid == 0) {
    const uint32_t bars = sb + C_BAR;
    mbar_init(bars + B_M0 * 8, 1); mbar_init(bars + B_M1 * 8, 1); mbar_init(bars + B_M2 * 8, 1);
    for (int i = 0; i < 4; i++) mbar_init(bars + (B_R + i) * 8, 1);
    mbar_init(bars + B_X * 8, 9); mbar_init(bars + B_O * 8, 2); mbar_init(bars + B_T * 8, 1); mbar_init(bars + B_F * 8, 2);
    mbar_init(bars + B_XL * 8, 2); mbar_init(bars + B_U * 8, 1);
    mbar_init(bars + B_P1 * 8, 8); mbar_init(bars + B_P2 * 8, 8); mbar_init(bars + B_OT * 8, 3); mbar_init(bars + B_XF * 8, 8); mbar_init(bars + B_XA * 8, 8); mbar_init(bars + B_I * 8, 1); mbar_init(bars + B_PI * 8, 1); mbar_init(bars + B_J * 8, 1);
    mbar_init(bars + B_W * 8, 1); mbar_init(bars + B_WO * 8, 1);
    asm volatile("fence.mbarrier_init.release.cluster;" ::: "memory");
    fence_async_smem();
    stage_weights(sb + C_STG, &maps.w[rank], h * 128, 0, bars + B_W * 8);
    const int nt = rank == 2 ? 2 : 3;
    mbar_expect_tx(bars + B_WO * 8, nt * 16384);
    for (int tl = 0; tl < nt; tl++)
      asm volatile("cp.async.bulk.tensor.5d.shared::cluster.global.mbarrier::complete_tx::bytes [%0], [%1, {%3, 0, 0, 0, %4}], [%2];"
                   ::"r"(sb + C_WO + tl * 16384), "l"(&maps.wo), "r"(bars + B_WO * 8), "r"((tl * 3 + rank) * 64), "r"(h * 4) : "memory");
  }
  __syncwarp();
  asm volatile("barrier.cluster.arrive.relaxed.aligned;" ::: "memory");
  {
    const int gt = blockIdx.x * 512 + tid, g1 = gt - 12288, g2 = gt - 12288 - 16384;
    static_assert(12288 + 16384 + sizeof(Flags) / 16 <= 96 * 512, "reset");
    if (g1 < 0) ((uint4*)g_M)[gt / 3072 * 4096 + 256 + gt % 3072] = make_uint4(~0u, ~0u, ~0u, ~0u);
    else if (g2 < 0) ((uint4*)(g_part[1] + 32 * 8192))[g1] = make_uint4(0, 0, 0, 0);
    else if (g2 < (int)(sizeof(Flags) / 16)) ((uint4*)&g_fl)[g2] = make_uint4(0, 0, 0, 0);
    if ((NSTEP - 1) & 1) { ((uint4*)g_P)[gt] = make_uint4(0, 0, 0, 0); ((uint4*)g_P)[gt + 49152] = make_uint4(0, 0, 0, 0); }
#pragma unroll 1
    for (int i = 0; i < 4; i++) {
      if (i != 1 || w < 5) {
        const int row = i == 0 ? row2 : i == 1 ? row3 : (i - 2) * 16 + w;
        store_row_img(i < 2 ? g_xs[0] + (row >> 5) * 32768 : smem_raw + (sb - smem_u32(smem_raw)) + C_X, row & 31, lane, warp_ln(xr[0]));
      }
      xr[0] = xr[1]; xr[1] = xr[2]; xr[2] = xr[3];
    }
  }
  fence_async_smem();
  __syncthreads();
  asm volatile("barrier.cluster.wait.aligned;" ::: "memory");
  if (tid == 448) red_release(g_ex.ready);
  __syncwarp();
  if (w < 8) {
    reg_inc<184>();
    chain_proj(sb, w, lane, rank);
    TG(1)
    TRDUMP
    cluster_sync();
  } else if (w < 12) {
    reg_dec<120>();
    chain_mem(sb, w, lane, rank, h, mem0);
    STATDUMP
    TRDUMP
    cluster_sync();
  } else {
    reg_dec<24>();
    chain_dma(sb, w, lane, rank, h);
    TRDUMP
    cluster_sync();
  }
}
#undef TRC
#undef TRS

constexpr int K_BAR = 0, K_LN = 128, K_FH = 320, K_FS = 512, K_FY = 1536;
constexpr int K_W = 3072;
constexpr int K_O = K_W + 3 * 49152;
constexpr int K_ST = K_O + 65536;
constexpr int K_SMEM = K_ST + 16384;
static_assert(K_SMEM <= 232448, "shared memory");
enum { KB_FULL = 0, KB_EMPTY = 2, KB_OK = 4, KB_GO = 7, KB_ST = 10, KB_REL = 12, KB_W = 13 };
enum { KN_ST = 1, KN_ST1, KN_REL, KN_FFN, KN_INIT, KN_RES, KN_RES1, KN_CAND, KN_TAKEN, KN_FF2 };
#define GATE_R 850
struct WorkerParams {
  CUtensorMap wo;
  const bf16 *x0, *w_r, *w_gate, *w_up, *w_down;
  bf16* out;
};
#define TRC (96 + blockIdx.x)
#define FT(e)
#define QUIET 4900
__device__ __forceinline__ void quiet_until(uint32_t t) {
  int d;
  while ((d = (int)(t - clk32())) > 0) warp_sleep(min(d / 3 + 20, 1000));
}
#define FOR_UNITS _Pragma("unroll 1") for (int st = 0, n = 0; st < WSTEP; st++) \
                  _Pragma("unroll 1") for (int v = st < NSEG ? 0 : st < WSTEP - 1 ? 1 : 2, sg = v ? st - WD : st; v < (st >= WD ? 3 : 1); v++, n++, sg = st - WD)

template <int ACC>
__device__ __forceinline__ void wg_ss8(float (&d)[4], uint64_t da, uint64_t db) {
  asm volatile("wgmma.mma_async.sync.aligned.m64n8k16.f32.bf16.bf16 {%0,%1,%2,%3}, %4, %5, %6, 1, 1, 1, 0;" : O4(d, 0) : "l"(da), "l"(db), "n"(ACC));
}
template <int NU>
__device__ __forceinline__ void ffn_slice(uint32_t sb, int t, const bf16* yrow, int ev) {
  const int lane = t & 31, c = t >> 5;
  FT(1)
  {
    const uint2 r = ld_rlx64(yrow + t * 4);
    asm volatile("st.shared.v2.b32 [%0], {%1,%2};" ::"r"(sb + K_FY + ((t >> 1) & 31) * 32 + (t >> 6) * 16 + (t & 1) * 8), "r"(r.x), "r"(r.y) : "memory");
  }
  fence_async_smem();
  bar_sync(KN_FFN, 128);
  FT(2)
  {
    float g[NU][4];
    const uint64_t da = mk_desc(sb + K_W, 16384, 512, 2), db = mk_desc(sb + K_FY, 32, 0, 0);
    wg_fence();
#pragma unroll
    for (int i = 0; i < 16; i++)
#pragma unroll
      for (int u = 0; u < NU; u++) { if (i == 0) wg_ss8<0>(g[u], da + u * 3072, db); else wg_ss8<1>(g[u], da + u * 3072 + i * 64, db + i * 4); }
    wg_commit();
    wg_wait<0>();
#pragma unroll
    for (int u = 0; u < NU; u++) {
      acc_fence(g[u]);
      if ((lane & 3) == 0) {
        const uint32_t a = sb + K_FS + u * 256 + c * 64 + lane;
        sts32(a, __float_as_uint(c < 2 ? g[u][0] : g[u][1])); sts32(a + 32, __float_as_uint(c < 2 ? g[u][2] : g[u][3]));
      }
    }
  }
  FT(3)
  bar_sync(KN_FFN, 128);
  {
    const uint32_t pa = sb + K_FS + c * 256 + lane * 4;
    const float gt = round_bf16(__uint_as_float(lds32(pa)) + __uint_as_float(lds32(pa + 128)));
    const float up = __shfl_xor_sync(~0u, gt, 16);
    const uint32_t hv = pack_bf16(round_bf16(__fdividef(gt, 1.f + __expf(-gt))) * up, 0.f);
    if (lane < 16) asm volatile("st.shared.b16 [%0], %1;" ::"r"(sb + K_FH + (c * 16 + lane) * 2), "h"((unsigned short)hv) : "memory");
  }
  fence_async_smem();
  bar_sync(KN_FFN, 128);
  FT(4)
#pragma unroll 1
  for (int hf = 0; hf < 2; hf++) {
    float o[4][4];
    const uint64_t da = mk_desc(sb + K_W + 32768 + hf * 8192, 16, 1024, 1), db = mk_desc(sb + K_FH, 16, 0, 0);
    wg_fence();
#pragma unroll
    for (int u = 0; u < NU; u++)
#pragma unroll
      for (int j = 0; j < 4; j++) { if (u == 0) wg_ss8<0>(o[j], da + j * 128, db); else wg_ss8<1>(o[j], da + u * 3072 + j * 128, db + u * 2); }
    wg_commit();
    wg_wait<0>();
    float lo = 0.f, hi = 0.f;
#pragma unroll
    for (int j = 0; j < 4; j++) {
      acc_fence(o[j]);
      const float a = __shfl_sync(~0u, o[j][0], lane & 28), b = __shfl_sync(~0u, o[j][2], lane & 28);
      if ((lane & 3) == j) { lo = a; hi = b; }
    }
    float* p = &g_fl.upd[ev][hf * 256 + (lane & 3) * 64 + c * 16 + (lane >> 2)];
    asm volatile("red.relaxed.gpu.global.add.f32 [%0], %1; red.relaxed.gpu.global.add.f32 [%0 + 32], %2;" ::"l"(p), "f"(lo), "f"(hi) : "memory");
  }
  FT(5)
  bar_sync(KN_FFN, 128);
  if (t == 96) red_release(g_fl.ffncnt[ev]);
  __syncwarp();
}
__device__ __forceinline__ uint4 pair_ln(uint4 r, float& e, uint32_t sl, int bar, int t) {
  const float x[8] = {bf_lo(r.x), bf_hi(r.x), bf_lo(r.y), bf_hi(r.y), bf_lo(r.z), bf_hi(r.z), bf_lo(r.w), bf_hi(r.w)};
  const float s = ((x[0] + x[1]) + (x[2] + x[3])) + ((x[4] + x[5]) + (x[6] + x[7]));
  const float q = (fmaf(x[0], x[0], x[1] * x[1]) + fmaf(x[2], x[2], x[3] * x[3])) + (fmaf(x[4], x[4], x[5] * x[5]) + fmaf(x[6], x[6], x[7] * x[7]));
  const bool u16 = t & 16, u8 = t & 8;
  const float a = (u16 ? q : s) + __shfl_xor_sync(~0u, u16 ? s : q, 16), b = e + __shfl_xor_sync(~0u, e, 16);
  float v = (u8 ? b : a) + __shfl_xor_sync(~0u, u8 ? a : b, 8);
  v += __shfl_xor_sync(~0u, v, 4); v += __shfl_xor_sync(~0u, v, 2); v += __shfl_xor_sync(~0u, v, 1);
  sts32(sl + (t >> 3) * 4, __float_as_uint(v));
  bar_sync(bar, 64);
  const uint4 s0 = lds128(sl), s1 = lds128(sl + 16);
  const float m = (__uint_as_float(s0.x) + __uint_as_float(s1.x)) * (1.f / DM), m2 = (__uint_as_float(s0.z) + __uint_as_float(s1.z)) * (1.f / DM);
  e = __uint_as_float(s0.y) + __uint_as_float(s1.y);
  float rs;
  asm("rsqrt.approx.ftz.f32 %0, %1;" : "=f"(rs) : "f"(fmaxf(fmaf(-m, m, m2), 0.f) + 1e-5f));
  return make_uint4(pack_bf16((x[0] - m) * rs, (x[1] - m) * rs), pack_bf16((x[2] - m) * rs, (x[3] - m) * rs),
                    pack_bf16((x[4] - m) * rs, (x[5] - m) * rs), pack_bf16((x[6] - m) * rs, (x[7] - m) * rs));
}
__device__ __forceinline__ uint32_t score_bits(float r) {
  const uint32_t b = pack_bf16(0.f, r);
  return (b & 0x80000000u) ? ~b : (b | 0x80000000u);
}

__global__ void __launch_bounds__(640, 1) worker_kernel(const __grid_constant__ WorkerParams prm) {
  extern __shared__ __align__(1024) uint8_t smem_raw[];
  const uint32_t sb = smem_u32(smem_raw);
  if (sb & 1023) __trap();
  const int tid = threadIdx.x, lane = tid & 31;
  const int w = __shfl_sync(~0u, tid >> 5, 0);
  const int me = blockIdx.x, kb = me >> 2, cb = me & 3;
  const bool full = me < 32;
  const uint32_t bars = sb + K_BAR;
  TG(0)
  if (tid == 0) {
    for (int i = 0; i < 2; i++) { mbar_init(bars + (KB_FULL + i) * 8, 1); mbar_init(bars + (KB_EMPTY + i) * 8, 1); }
    for (int i = 0; i < 10; i++) mbar_init(bars + (KB_OK + i) * 8, i < 3 ? 2 : 1);
    sts32(sb + K_LN + 144, 0);
    asm volatile("fence.mbarrier_init.release.cluster;" ::: "memory");
    fence_async_smem();
  }
  __syncwarp();
  if (w == 0) {
    wait_count(g_ex.ready, 96, 94);
    if (lane == 0 && full) stage_weights(sb + K_W, &prm.wo, cb * 128, kb * 512, bars + KB_W * 8);
  }
  __syncthreads();
  if (w < 8) {
    reg_inc<176>();
    if (full) {
      uint32_t wA[32][4];
      mbar_wait(bars + KB_W * 8, 0, 79);
      load_wfrags(wA, sb + K_W, w, lane);
      bar_arrive(KN_INIT, 384);
      const uint32_t sp = pin(sb + K_ST + ((lane >> 4) * 8 + (lane & 7)) * 256 + (((2 * w + ((lane >> 3) & 1)) ^ (lane & 7)) << 4));
      const uint32_t tm = pin(lane < 4 ? 0x00010001u : 0u);
      FOR_UNITS {
        float d[16];
        mbar_wait(bars + (KB_FULL + (n & 1)) * 8, (n >> 1) & 1, 81);
        TR(4 * v)
        const uint64_t db = mk_desc(sb + K_O + (n & 1) * 32768, 128, 2048, 0);
        wg_fence();
#pragma unroll
        for (int ks = 0; ks < 32; ks++) {
          if (ks == 0) wg_rs32<0, 0>(d, wA[ks], db);
          else wg_rs32<0, 1>(d, wA[ks], db + (ks >> 3) * 512 + (ks & 7) * 16);
        }
        wg_commit();
        mbar_wait(bars + (KB_ST + (n & 1)) * 8, ((n >> 1) & 1) ^ 1, 82);
        wg_wait<0>();
        acc_fence(d);
        TR(4 * v + 1)
        const uint32_t tag = (sg & 2) ? 0u : tm;
        uint32_t pk[8];
#pragma unroll
        for (int i = 0; i < 8; i++) pk[i] = (pack_bf16(d[2 * i], d[2 * i + 1]) & ~tm) | tag;
        stsm4t(sp + (n & 1) * 8192, pk[0], pk[1], pk[2], pk[3]);
        stsm4t(sp + (n & 1) * 8192 + 4096, pk[4], pk[5], pk[6], pk[7]);
        bar_arrive(KN_ST + (n & 1), 288);
        TR(4 * v + 2)
      }
    }
  } else if (w < 12) {
    reg_dec<56>();
    if (full) {
      const int ly = (w >> 1) & 1, t = pin(tid & 63);
      const uint32_t so = pin((t >> 4) * 8192 + me * 256 + (((t & 15) ^ (me & 7)) << 4));
      int sstar = -1;
      uint32_t sl = sb + K_LN + ly * 64;
      float rr = 0.f;
      int kprev = -1;
      auto records = [&](int sg, uint32_t off) {
        int it = 0;
        while (__any_sync(~0u, (int)lds32(sb + K_LN + 144) <= sg)) { give_up(++it, SPIN_LIMIT, 86); warp_sleep(50); }
        return lds32(sb + K_LN + off);
      };
#pragma unroll 1
      for (int n = ly ? 2 * WD : 0; n < 2 * WSTEP; n++) {
        const int st = n >> 1, v = (n & 1) ? 2 : ly, sg = v ? st - WD : st, tok = sg * 32 + me;
        if (n == 2 * NSEG) bar_sync(KN_INIT, 128);
        if (n == 2 * NSEG + 2) sstar = records(NSEG - 1, 156);
        if (v == 2 ? sg < 0 || (st < NSEG ? st & 1 : 0) != ly : sg >= NSEG - v) continue;
        const bf16* xin = v ? g_rows[tok][0][2] : prm.x0 + tok * DM;
        if (v == 2 && ((records(sg, 148 + (sg >> 5) * 4) >> (sg & 31)) & 1)) xin = g_x2p[sg][0];
        const uint8_t* src = g_part[v] + (sg & 1) * (32 * 8192) + so;
        const uint32_t flip = (sg & 2) ? ~0u : 0u;
        mbar_wait(bars + (KB_GO + v) * 8, sg & 1, 87);
        TR(4 * v)
        uint4 p[8], x;
        int it = 0;
#pragma unroll 1
        do {
#pragma unroll
          for (int k = 0; k < 8; k++) p[k] = ld_rlx128(src + k * 32768);
          x = ld_rlx128(((WEXP & 2) ? prm.x0 : xin) + t * 8);
          give_up(it++, SPIN_LIMIT, 85);
        } while (__builtin_expect(!__all_sync(~0u, (int)and3(and3(and_x(p[0].x, p[1].x, flip), and_x(p[2].x, p[3].x, flip), 1u),
                                                             and_x(p[4].x, p[5].x, flip), and_x(p[6].x, p[7].x, flip))), 0));
        mbar_arrive_z(bars + (KB_OK + v) * 8, t & 31);
#define P8(h, f) (((h(p[0].f) + h(p[1].f)) + (h(p[2].f) + h(p[3].f))) + ((h(p[4].f) + h(p[5].f)) + (h(p[6].f) + h(p[7].f))))
#define X8(f) x.f = add_bf16x2(x.f, pack_bf16(P8(bf_lo, f), P8(bf_hi, f)));
        X8(x) X8(y) X8(z) X8(w)
#undef X8
#undef P8
        TRV(12 + v, it - 1)
        TR(4 * v + 1)
        bf16* dst = g_rows[tok][v][0] + t * 8;
        *(uint4*)dst = x;
        const uint4 wr = ld_rlx128(prm.w_r + t * 8);
        sl ^= 32;
        uint4 y = pair_ln(x, rr, sl, KN_RES + ly, t);
        *(uint4*)(dst + DM) = y;
        x = make_uint4(add_bf16x2(x.x, y.x), add_bf16x2(x.y, y.y), add_bf16x2(x.z, y.z), add_bf16x2(x.w, y.w));
        *(uint4*)(v == (sg < sstar ? 1 : 2) ? prm.out + tok * DM + t * 8 : dst + 2 * DM) = x;
        asm volatile("{ .reg .pred p; setp.eq.u32 p, %2, 0; @p st.relaxed.gpu.global.u64 [%0], %1; }" ::"l"(&g_fl.key[0][0][0] + max(kprev, 0)),
                     "l"((u64)score_bits(rr) << 32 | (uint32_t)~(kprev & (NTOK - 1))), "r"(t | (kprev < 0)) : "memory");
        kprev = v * NTOK + tok;
        rr = (fmaf(bf_lo(y.x), bf_lo(wr.x), bf_hi(y.x) * bf_hi(wr.x)) + fmaf(bf_lo(y.y), bf_lo(wr.y), bf_hi(y.y) * bf_hi(wr.y))) +
             (fmaf(bf_lo(y.z), bf_lo(wr.z), bf_hi(y.z) * bf_hi(wr.z)) + fmaf(bf_lo(y.w), bf_lo(wr.w), bf_hi(y.w) * bf_hi(wr.w)));
        if (v == 0 || st >= NSEG) {
          sl ^= 32;
          y = pair_ln(x, rr, sl, KN_RES + ly, t);
          if (v == 0) *(uint4*)(g_xs[1] + sg * 32768 + (t >> 3) * 4096 + me * 128 + (((t ^ me) & 7) << 4)) = y;
          sts32(sb + K_LN + 128 + ly * 4, score_bits(rr));
          bar_arrive(KN_REL, v == 0 || st == WSTEP - 1 ? 96 : 160);
          kprev = -1;
        }
        TR(4 * v + 2)
      }
    }
  } else if (w < 16) {
    reg_dec<48>();
    const int t = tid - 384, nu = full ? 3 : 4;
    if (full) bar_sync(KN_INIT, 384);
    {
      const int j0 = (full ? me * 3 : 96 + (me - 32) * 4) * 16;
#pragma unroll 1
      for (int i = t; i < nu * 3072; i += 128) {
        const int u = i / 3072, r = i - u * 3072;
        const int q = (r ^ (r >> 3)) & 3, r2 = r - 2048;
        const bf16* src = r < 2048 ? ((q & 2) ? prm.w_up : prm.w_gate) + (size_t)(r >> 2) * FF + j0 + u * 16 + (q & 1) * 8
                                   : prm.w_down + (size_t)(j0 + u * 16 + ((r2 >> 3) & 15)) * DM + (r2 >> 7) * 64 + ((r2 ^ (r2 >> 3)) & 7) * 8;
        cp16(sb + K_W + i * 16, src);
      }
      asm volatile("cp.async.wait_all;" ::: "memory");
    }
    bar_arrive(KN_TAKEN, 160);
#pragma unroll 1
    while (true) {
      bar_sync(KN_CAND, 160);
      const uint4 cand = lds128(sb + K_LN + 160);
      const u64 k = (u64)cand.y << 32 | cand.x;
      const int ev = cand.z, ver = cand.w & 3, tok = key_token(k);
      const bool last = cand.w & 4;
      if (!last) {
        bar_arrive(KN_TAKEN, 160);
        FT(0)
        if (full) ffn_slice<3>(sb, t, g_rows[tok][ver][1], ev); else ffn_slice<4>(sb, t, g_rows[tok][ver][1], ev);
      }
      if ((tok & 31) == me && (ver == 0 || last)) {
        if (t < 64) {
          FT(6)
          uint4 x = ld_rlx128(g_rows[tok][ver][0] + t * 8);
          const uint4 y = ld_rlx128(g_rows[tok][ver][1] + t * 8);
          const float sig = round_bf16(__fdividef(1.f, 1.f + __expf(-key_score(k))));
          int it = 0;
          while (ld_rlx32(g_fl.ffncnt[ev]) < NWORK) { give_up(++it, SPIN_LIMIT, 80); warp_sleep(40); }
          const uint4 u0 = ld_rlx128(&g_fl.upd[ev][t * 8]), u1 = ld_rlx128(&g_fl.upd[ev][t * 8 + 4]);
          auto upd = [&](uint32_t xw, uint32_t yw, uint32_t a, uint32_t b) {
            const uint32_t r = pack_bf16(__uint_as_float(a), __uint_as_float(b));
            return add_bf16x2(xw, add_bf16x2(yw, pack_bf16(bf_lo(r) * sig, bf_hi(r) * sig)));
          };
          x = make_uint4(upd(x.x, y.x, u0.x, u0.y), upd(x.y, y.y, u0.z, u0.w), upd(x.z, y.z, u1.x, u1.y), upd(x.w, y.w, u1.z, u1.w));
          FT(7)
          *(uint4*)((ver ? prm.out + tok * DM : g_x2p[ev][0]) + t * 8) = x;
          if (ver == 0) {
            float e = 0.f;
            *(uint4*)(g_x2p[ev][1] + t * 8) = pair_ln(x, e, sb + K_FS, KN_FF2, t);
            bar_sync(KN_FF2, 64);
            if (t == 0) st_release32(g_fl.patch[ev], 1);
            __syncwarp();
          }
        }
      }
      if (ev == NSEG && !last && full) {
        const int nc = min((int)lds32(sb + K_LN + 156), NSEG + 1 - WD);
#pragma unroll 1
        for (int s0 = (t >> 6) * 4; s0 < nc; s0 += 8) {
          uint4 q[4];
#pragma unroll
          for (int i = 0; i < 4; i++) q[i] = ld_rlx128(g_rows[min(s0 + i, nc - 1) * 32 + me][1][2] + (t & 63) * 8);
#pragma unroll
          for (int i = 0; i < 4; i++) *(uint4*)(prm.out + (min(s0 + i, nc - 1) * 32 + me) * DM + (t & 63) * 8) = q[i];
        }
      }
      FT(8)
      if (last) break;
    }
  } else {
    reg_dec<24>();
    if (w == 16) {
      u64 best = 0, mask = 0;
      int sstar = 0;
      uint32_t ver = 0, ev = 0;
      auto post = [&](uint32_t cmd) {
        bar_sync(KN_TAKEN, 160);
        sts128(sb + K_LN + 160, make_uint4((uint32_t)best, (uint32_t)(best >> 32), ev, ver | cmd));
        bar_arrive(KN_CAND, 160);
      };
      u64 accn = 0, acca = 0;
      uint32_t recs = 0;
      int j = 0;
      uint32_t tq = clk32();
#pragma unroll 1
      for (int st = 0; st < WSTEP; st++) {
        const u64* keys = st < NSEG ? g_fl.key[0][st] : g_fl.key[2][st - WD];
        const bool early = __any_sync(~0u, ld_rlx32(keys + lane) == 0);
        if (early && st < NSEG) quiet_until(tq);
        u64 k = wait_keys(keys, lane, 91);
        if (early) tq = clk32() + QUIET;
        if (st < NSEG) {
          const bool rec = k > best;
          recs &= ~(1u << (st & 31));
          if (rec) {
            best = k; ev = sstar = st;
            recs |= 1u << (st & 31);
            if ((key_token(k) & 31) == me) mask |= 1ull << st;
          }
          if (lane == 0) sts128(sb + K_LN + 144, make_uint4(st + 1, (uint32_t)mask, (uint32_t)(mask >> 32), sstar));
          __syncwarp();
          if (rec) post(0);
        }
#pragma unroll 1
        for (; j <= st - WD - (st < NSEG ? 2 : 0); j++) {
          u64 kn = 1, kc;
          int it = 0;
          do {
            if (j < NSEG - 1) asm volatile("ld.relaxed.gpu.global.u64 %0, [%1];" : "=l"(kn) : "l"(&g_fl.key[1][j][lane]) : "memory");
            asm volatile("ld.relaxed.gpu.global.u64 %0, [%1];" : "=l"(kc) : "l"(&g_fl.key[2][j][lane]) : "memory");
            give_up(it++, SPIN_LIMIT, 92);
          } while (__any_sync(~0u, kn == 0 || kc == 0));
          if ((recs >> (j & 31)) & 1) acca = accn;
          if (kc > acca) acca = kc;
          if (kn > accn) accn = kn;
        }
        if (st >= NSEG) {
          const u64 m = j <= sstar ? accn : acca;
          const uint32_t hi = __reduce_max_sync(~0u, (uint32_t)(m >> 32));
          k = (u64)hi << 32 | __reduce_max_sync(~0u, (uint32_t)(m >> 32) == hi ? (uint32_t)m : 0u);
          if (st == NSEG || k != best) {
            best = k; ev = st;
            ver = (key_token(k) >> 5) < sstar ? 1 : 2;
            post(0);
          }
        }
      }
      HD(6)
      post(4);
      if (me == 0 && lane == 0) st_rlx32(g_ex.ready, 0);
    } else if (!full) {
    } else if (w == 17) {
      uint32_t tq = clk32();
      FOR_UNITS {
        if (ld_rlx32(&g_fl.oflag[v][sg][kb]) < 4) {
          if (v == (st < NSEG ? 0 : 1) && st < WSTEP - 3) quiet_until(tq);
          wait_count(&g_fl.oflag[v][sg][kb], 4, 84);
          if (v == (st < NSEG ? 0 : 1)) tq = clk32() + QUIET;
        }
        mbar_wait(bars + (KB_EMPTY + (n & 1)) * 8, ((n >> 1) & 1) ^ 1, 83);
        TR(v)
        if (st == WSTEP - 1) { HD(v) }
        if (lane == 0) {
          fence_async_glb();
          mbar_expect_tx(bars + (KB_FULL + (n & 1)) * 8, (WEXP & 4) ? 4096 : 32768);
          bulk_g2s(sb + K_O + (n & 1) * 32768, g_O[(v ? sg + DELTA : sg) & (OSLOTS - 1)][v] + kb * 32768, (WEXP & 4) ? 4096 : 32768, bars + (KB_FULL + (n & 1)) * 8);
        }
        __syncwarp();
      }
    } else if (w == 18) {
      FOR_UNITS {
        if (sg > 0) mbar_wait(bars + (KB_OK + v) * 8, (sg - 1) & 1, 90);
        bar_sync(KN_ST + (n & 1), 288);
        fence_async_smem();
        const uint32_t tg = clk32() + GATE_R;
        if (lane == 0) {
          bulk_s2g(g_part[v] + ((sg & 1) * 32 + me) * 8192, sb + K_ST + (n & 1) * 8192, 8192);
          asm volatile("cp.async.bulk.commit_group;" ::: "memory");
          mbar_arrive_z(bars + (KB_EMPTY + (n & 1)) * 8, 0);
          asm volatile("cp.async.bulk.wait_group.read 0;" ::: "memory");
        }
        __syncwarp();
        mbar_arrive_z(bars + (KB_ST + (n & 1)) * 8, lane);
        TR(v)
        if (v == (st < NSEG ? 0 : st < WSTEP - 1 ? 1 : 2) && st > 0) mbar_wait(bars + KB_REL * 8, (st - 1) & 1, 93);
        wait_clock(tg);
        if (st == WSTEP - 1) { HD(2 + v) }
        mbar_arrive_z(bars + (KB_GO + v) * 8, lane);
      }
    } else {
#pragma unroll 1
      for (int st = 0; st < WSTEP; st++) {
        const int sg = st < NSEG ? st : st - WD;
        const bool both = st >= NSEG && st < WSTEP - 1;
        bar_sync(KN_REL, both ? 160 : 96);
        const uint32_t ob = __shfl_sync(~0u, lds32(sb + K_LN + 128), 0), obn = __shfl_sync(~0u, lds32(sb + K_LN + 132), 0);
        mbar_arrive_z(bars + KB_REL * 8, lane);
        if (st == WSTEP - 1) { HD(5) }
        if (lane == 0) {
          if (both) asm volatile("st.relaxed.gpu.global.u64 [%0], %1;" ::"l"(&g_fl.key[1][sg][me]), "l"((u64)obn << 32 | (uint32_t)~(sg * 32 + me)) : "memory");
          st_release_u64(&g_fl.key[st < NSEG ? 0 : 2][sg][me], (u64)ob << 32 | (uint32_t)~(sg * 32 + me));
        }
        __syncwarp();
        TR(0)
      }
    }
  }
}
#undef TRC

typedef CUresult (*EncodeFn)(CUtensorMap*, CUtensorMapDataType, cuuint32_t, void*, const cuuint64_t*, const cuuint64_t*,
                             const cuuint32_t*, const cuuint32_t*, CUtensorMapInterleave, CUtensorMapSwizzle,
                             CUtensorMapL2promotion, CUtensorMapFloatOOBfill);
void make_map(EncodeFn fn, CUtensorMap* m, const void* ptr, int rank, const cuuint64_t* dims, const cuuint64_t* strides, const cuuint32_t* box) {
  const cuuint32_t es[5] = {1, 1, 1, 1, 1};
  fn(m, CU_TENSOR_MAP_DATA_TYPE_BFLOAT16, rank, (void*)ptr, dims, strides, box, es, CU_TENSOR_MAP_INTERLEAVE_NONE,
     CU_TENSOR_MAP_SWIZZLE_128B, CU_TENSOR_MAP_L2_PROMOTION_L2_256B, CU_TENSOR_MAP_FLOAT_OOB_FILL_NONE);
}
struct HostState {
  const void* key[4];
  ChainMaps cm;
  CUtensorMap wo;
};
HostState g_hs;

}

extern "C" void kernel_launch(void* const* d_in, const int* in_sizes, int n_in, void* d_out, int out_size) {
  (void)in_sizes; (void)n_in; (void)out_size;
  HostState& hs = g_hs;
  if (hs.key[0] != d_in[2] || hs.key[1] != d_in[3] || hs.key[2] != d_in[4] || hs.key[3] != d_in[5]) {
    void* fnp = nullptr;
    cudaDriverEntryPointQueryResult qr;
    cudaGetDriverEntryPoint("cuTensorMapEncodeTiled", &fnp, cudaEnableDefault, &qr);
    const cuuint32_t box[2] = {64, 256}, box5[5] = {64, 2, 4, 4, 4};
    const cuuint64_t dw[2] = {HD, DM}, sw[1] = {HD * 2}, dwo[2] = {DM, HD}, swo[1] = {DM * 2};
    const cuuint64_t d5[5] = {DM, 2, 4, 4, HD / 32}, s5[4] = {DM * 2, 8 * DM * 2, 2 * DM * 2, 32 * DM * 2};
    for (int i = 0; i < 3; i++) make_map((EncodeFn)fnp, &hs.cm.w[i], d_in[2 + i], 2, dw, sw, box);
    make_map((EncodeFn)fnp, &hs.cm.wo, d_in[5], 5, d5, s5, box5);
    make_map((EncodeFn)fnp, &hs.wo, d_in[5], 2, dwo, swo, box);
    cudaFuncSetAttribute(worker_kernel, cudaFuncAttributeMaxDynamicSharedMemorySize, K_SMEM);
    cudaFuncSetAttribute(chain_kernel, cudaFuncAttributeMaxDynamicSharedMemorySize, C_SMEM);
    for (int i = 0; i < 4; i++) hs.key[i] = d_in[2 + i];
  }
  cudaStream_t st = cudaStreamPerThread;
  WorkerParams wp;
  wp.wo = hs.wo; wp.x0 = (const bf16*)d_in[0]; wp.w_r = (const bf16*)d_in[8]; wp.w_gate = (const bf16*)d_in[9];
  wp.w_up = (const bf16*)d_in[10]; wp.w_down = (const bf16*)d_in[11]; wp.out = (bf16*)d_out;
  chain_kernel<<<96, 512, C_SMEM, st>>>(hs.cm, (const bf16*)d_in[1], wp.x0);
  cudaLaunchAttribute pdl[1];
  pdl[0].id = cudaLaunchAttributeProgrammaticStreamSerialization;
  pdl[0].val.programmaticStreamSerializationAllowed = 1;
  cudaLaunchConfig_t cfg = {};
  cfg.gridDim = dim3(NWORK); cfg.blockDim = dim3(640); cfg.dynamicSmemBytes = K_SMEM; cfg.stream = st;
  cfg.attrs = pdl; cfg.numAttrs = 1;
  cudaLaunchKernelEx(&cfg, worker_kernel, wp);
}
```

```cpp
#include <cuda_runtime.h>
#include <cuda_bf16.h>
#include <cuda.h>
#include <stdint.h>

namespace {

typedef __nv_bfloat16 bf16;
typedef unsigned long long u64;

constexpr int NTOK = 2048, DM = 512, HD = 4096, NSEG = 64, FF = 1792;
#define DELTA 5
constexpr int NSTEP = NSEG + DELTA;
#define WLAG 1
constexpr int WD = DELTA + WLAG, WSTEP = NSEG + WD;
constexpr int SPIN_LIMIT = 40000;
constexpr int MBAR_LIMIT = 20000;
constexpr int NWORK = 36;
constexpr int OSLOTS = 8;
#define SLP_C 100
#define SLP_K 200
#define WEXP 0

__device__ __align__(1024) uint8_t g_xs[2][NSEG * 32768];
__device__ __align__(1024) uint8_t g_O[OSLOTS][3][32 * 8192];
__device__ __align__(1024) uint8_t g_part[3][2 * 32 * 8192];
__device__ __align__(1024) bf16 g_rows[NTOK][3][3][DM];
__device__ __align__(1024) bf16 g_x2p[NSEG][2][DM];
struct Flags {
  uint32_t pol[96];
  uint32_t stamp[96];
  uint32_t oflag[3][NSEG][8];
  uint32_t ffncnt[WSTEP][8];
  uint32_t patch[NSEG][8];
  u64 key[3][NSEG][32];
  float upd[WSTEP][DM];
};
struct Exchange { uint32_t M[4 * 16384], P[96 * 4096]; Flags fl; uint32_t ready[32]; };
__device__ __align__(65536) Exchange g_ex;
#define g_M g_ex.M
#define g_P g_ex.P
#define g_fl g_ex.fl
#define TR(e)
#define TRV(e, v)
#define TG(i)
#define HD(e)
#define TRDUMP
#define TREXTRA 0

#define STAT(e, v)
#define STATC(n)
#define STATDUMP
__device__ __forceinline__ uint32_t smem_u32(const void* p) { return (uint32_t)__cvta_generic_to_shared(p); }
__device__ __forceinline__ uint32_t pack_bf16(float lo, float hi) {
  uint32_t r;
  asm("cvt.rn.bf16x2.f32 %0, %1, %2;" : "=r"(r) : "f"(hi), "f"(lo));
  return r;
}
__device__ __forceinline__ float bf_lo(uint32_t v) { return __uint_as_float(v << 16); }
__device__ __forceinline__ float bf_hi(uint32_t v) { return __uint_as_float(v & 0xffff0000u); }
__device__ __forceinline__ float ex2_fast(float x) { float y; asm("ex2.approx.ftz.f32 %0, %1;" : "=f"(y) : "f"(x)); return y; }
__device__ __forceinline__ float round_bf16(float x) { return __bfloat162float(__float2bfloat16_rn(x)); }
__device__ __forceinline__ uint32_t clk32() { uint32_t t; asm volatile("mov.u32 %0, %%clock;" : "=r"(t) :: "memory"); return t; }

__device__ __forceinline__ void mma16816(float (&d)[4], uint32_t a0, uint32_t a1, uint32_t a2, uint32_t a3,
                                         uint32_t b0, uint32_t b1) {
  asm("mma.sync.aligned.m16n8k16.row.col.f32.bf16.bf16.f32 {%0,%1,%2,%3}, {%4,%5,%6,%7}, {%8,%9}, {%0,%1,%2,%3};"
      : "+f"(d[0]), "+f"(d[1]), "+f"(d[2]), "+f"(d[3])
      : "r"(a0), "r"(a1), "r"(a2), "r"(a3), "r"(b0), "r"(b1));
}
__device__ __forceinline__ void ldsm4t(uint32_t (&r)[4], uint32_t addr) {
  asm volatile("ldmatrix.sync.aligned.m8n8.x4.trans.shared.b16 {%0,%1,%2,%3}, [%4];"
               : "=r"(r[0]), "=r"(r[1]), "=r"(r[2]), "=r"(r[3]) : "r"(addr) : "memory");
}
__device__ __forceinline__ void stsm4(uint32_t addr, uint32_t a, uint32_t b, uint32_t c, uint32_t d) {
  asm volatile("stmatrix.sync.aligned.m8n8.x4.shared.b16 [%0], {%1,%2,%3,%4};" ::"r"(addr), "r"(a), "r"(b), "r"(c), "r"(d) : "memory");
}
__device__ __forceinline__ void stsm4t(uint32_t addr, uint32_t a, uint32_t b, uint32_t c, uint32_t d) {
  asm volatile("stmatrix.sync.aligned.m8n8.x4.trans.shared.b16 [%0], {%1,%2,%3,%4};" ::"r"(addr), "r"(a), "r"(b), "r"(c), "r"(d) : "memory");
}
__device__ __forceinline__ uint4 lds128(uint32_t a) {
  uint4 v; asm volatile("ld.shared.v4.b32 {%0,%1,%2,%3}, [%4];" : "=r"(v.x), "=r"(v.y), "=r"(v.z), "=r"(v.w) : "r"(a) : "memory"); return v;
}
__device__ __forceinline__ uint32_t lds32(uint32_t a) { uint32_t v; asm volatile("ld.shared.b32 %0, [%1];" : "=r"(v) : "r"(a) : "memory"); return v; }
__device__ __forceinline__ uint32_t lds32_poll(uint32_t a) { uint32_t v; asm volatile("ld.volatile.shared.b32 %0, [%1];" : "=r"(v) : "r"(a) : "memory"); return v; }
__device__ __forceinline__ void sts32(uint32_t a, uint32_t x) { asm volatile("st.shared.b32 [%0], %1;" ::"r"(a), "r"(x) : "memory"); }
__device__ __forceinline__ void sts128(uint32_t a, uint4 v) {
  asm volatile("st.shared.v4.b32 [%0], {%1,%2,%3,%4};" ::"r"(a), "r"(v.x), "r"(v.y), "r"(v.z), "r"(v.w) : "memory");
}
__device__ __forceinline__ void cp16(uint32_t dst, const void* src) {
  asm volatile("cp.async.cg.shared.global [%0], [%1], 16;" ::"r"(dst), "l"(src) : "memory");
}
__device__ __forceinline__ void mbar_init(uint32_t mbar, uint32_t cnt) {
  asm volatile("mbarrier.init.shared.b64 [%0], %1;" ::"r"(mbar), "r"(cnt) : "memory");
}
__device__ __forceinline__ void mbar_expect_tx(uint32_t mbar, uint32_t bytes) {
  asm volatile("mbarrier.arrive.expect_tx.shared.b64 _, [%0], %1;" ::"r"(mbar), "r"(bytes) : "memory");
}
__device__ __forceinline__ void mbar_arrive_z(uint32_t mbar, uint32_t z) {
  asm volatile("{ .reg .pred p; setp.eq.u32 p, %1, 0; @p mbarrier.arrive.shared.b64 _, [%0]; }" ::"r"(mbar), "r"(z) : "memory");
}
__device__ __forceinline__ void mbar_expect_tx_z(uint32_t mbar, uint32_t bytes, uint32_t z) {
  asm volatile("{ .reg .pred p; setp.eq.u32 p, %2, 0; @p mbarrier.arrive.expect_tx.shared.b64 _, [%0], %1; }" ::"r"(mbar), "r"(bytes), "r"(z) : "memory");
}
__device__ __forceinline__ void mbar_arrive_remote_z(uint32_t mbar, uint32_t z) {
  asm volatile("{ .reg .pred p; setp.eq.u32 p, %1, 0; @p mbarrier.arrive.shared::cluster.b64 _, [%0]; }" ::"r"(mbar), "r"(z) : "memory");
}
__device__ __forceinline__ void warp_sleep(uint32_t ns) { __nanosleep(ns); __syncwarp(); }
__device__ __forceinline__ void fail(int) { __trap(); }
__device__ __forceinline__ void give_up(int it, int limit, int code) { if (it > limit) fail(code); }
__device__ __forceinline__ void mbar_wait(uint32_t mbar, uint32_t par, int code) {
  asm volatile("{ .reg .pred p; .reg .b32 n; mov.b32 n, %2;\n"
               "W: mbarrier.try_wait.parity.shared::cta.b64 p, [%0], %1; @p bra D;\n"
               "add.s32 n, n, -1; setp.eq.s32 p, n, 0; @p trap; bra W;\n"
               "D: }" ::"r"(mbar), "r"(par), "n"(MBAR_LIMIT) : "memory");
}
__device__ __forceinline__ void bulk_g2s(uint32_t dst, const void* src, uint32_t bytes, uint32_t mbar) {
  asm volatile("cp.async.bulk.shared::cluster.global.mbarrier::complete_tx::bytes [%0], [%1], %2, [%3];"
               ::"r"(dst), "l"(src), "r"(bytes), "r"(mbar) : "memory");
}
__device__ __forceinline__ void bulk_s2r(uint32_t dst, uint32_t src, uint32_t bytes, uint32_t mbar) {
  asm volatile("cp.async.bulk.shared::cluster.shared::cta.mbarrier::complete_tx::bytes [%0], [%1], %2, [%3];"
               ::"r"(dst), "r"(src), "r"(bytes), "r"(mbar) : "memory");
}
__device__ __forceinline__ void bulk_s2g(void* dst, uint32_t src, uint32_t bytes) {
  asm volatile("cp.async.bulk.global.shared::cta.bulk_group [%0], [%1], %2;" ::"l"(dst), "r"(src), "r"(bytes) : "memory");
}
__device__ __forceinline__ void fence_async_smem() { asm volatile("fence.proxy.async.shared::cta;" ::: "memory"); }
__device__ __forceinline__ void fence_async_glb() { asm volatile("fence.proxy.async.global;" ::: "memory"); }
__device__ __forceinline__ void bar_sync(int id, int n) { asm volatile("bar.sync %0, %1;" ::"r"(id), "r"(n) : "memory"); }
__device__ __forceinline__ void bar_arrive(int id, int n) { asm volatile("bar.arrive %0, %1;" ::"r"(id), "r"(n) : "memory"); }
__device__ __forceinline__ void cluster_sync() { asm volatile("barrier.cluster.arrive.release; barrier.cluster.wait.acquire;" ::: "memory"); }
__device__ __forceinline__ uint32_t mapa_u32(uint32_t a, uint32_t r) {
  uint32_t o;
  asm("mapa.shared::cluster.u32 %0, %1, %2;" : "=r"(o) : "r"(a), "r"(r));
  return o;
}
template <int OFF>
__device__ __forceinline__ void st_async32(uint32_t a, uint32_t x, uint32_t mbar) {
  asm volatile("st.async.weak.shared::cluster.mbarrier::complete_tx::bytes.b32 [%0 + %3], %1, [%2];" ::"r"(a), "r"(x), "r"(mbar), "n"(OFF) : "memory");
}
__device__ __forceinline__ uint4 ld_rlx128(const void* p) {
  uint4 v;
  asm volatile("ld.relaxed.gpu.global.v4.u32 {%0,%1,%2,%3}, [%4];" : "=r"(v.x), "=r"(v.y), "=r"(v.z), "=r"(v.w) : "l"(p) : "memory");
  return v;
}
__device__ __forceinline__ uint2 ld_rlx64(const void* p) {
  uint2 v; asm volatile("ld.relaxed.gpu.global.v2.u32 {%0,%1}, [%2];" : "=r"(v.x), "=r"(v.y) : "l"(p) : "memory"); return v;
}
__device__ __forceinline__ uint32_t ld_rlx32(const void* p) {
  uint32_t v; asm volatile("ld.relaxed.gpu.global.u32 %0, [%1];" : "=r"(v) : "l"(p) : "memory"); return v;
}
__device__ __forceinline__ void st_rlx32(void* p, uint32_t a) { asm volatile("st.relaxed.gpu.global.u32 [%0], %1;" ::"l"(p), "r"(a) : "memory"); }
__device__ __forceinline__ void red_release(uint32_t* p) { asm volatile("red.release.gpu.global.add.u32 [%0], 1;" ::"l"(p) : "memory"); }
__device__ __forceinline__ void st_release32(void* p, uint32_t a) { asm volatile("st.release.gpu.global.u32 [%0], %1;" ::"l"(p), "r"(a) : "memory"); }
__device__ __forceinline__ void st_release_u64(void* p, u64 a) { asm volatile("st.release.gpu.global.u64 [%0], %1;" ::"l"(p), "l"(a) : "memory"); }
__device__ __forceinline__ void wait_count(const uint32_t* p, uint32_t val, int code) {
  int it = 0;
  while (ld_rlx32(p) < val) {
    give_up(++it, SPIN_LIMIT, code);
    warp_sleep(SLP_C);
  }
}
__device__ __forceinline__ u64 wait_keys(const u64* keys, int lane, int code) {
  u64 k;
  int it = 0;
  while (true) {
    asm volatile("ld.relaxed.gpu.global.u64 %0, [%1];" : "=l"(k) : "l"(keys + lane) : "memory");
    if (__all_sync(~0u, k != 0)) break;
    give_up(++it, SPIN_LIMIT, code);
    warp_sleep(SLP_K);
  }
  const uint32_t hi = __reduce_max_sync(~0u, (uint32_t)(k >> 32));
  const uint32_t lo = __reduce_max_sync(~0u, (uint32_t)(k >> 32) == hi ? (uint32_t)k : 0u);
  return (u64)hi << 32 | lo;
}
__device__ __forceinline__ int key_token(u64 k) { return (int)(~(uint32_t)k) & (NTOK - 1); }
__device__ __forceinline__ float key_score(u64 k) {
  const uint32_t ob = (uint32_t)(k >> 32);
  return __uint_as_float((ob & 0x80000000u) ? (ob & 0x7fffffffu) : ~ob);
}

__device__ __forceinline__ uint64_t mk_desc(uint32_t saddr, uint32_t lbo, uint32_t sbo, uint32_t sw) {
  return (uint64_t)((saddr & 0x3FFFF) >> 4) | (uint64_t)(lbo >> 4) << 16 | (uint64_t)(sbo >> 4) << 32 | (uint64_t)sw << 62;
}
template <int N> __device__ __forceinline__ void reg_inc() { asm volatile("setmaxnreg.inc.sync.aligned.u32 %0;" ::"n"(N)); }
template <int N> __device__ __forceinline__ void reg_dec() { asm volatile("setmaxnreg.dec.sync.aligned.u32 %0;" ::"n"(N)); }
__device__ __forceinline__ void wg_fence() { asm volatile("wgmma.fence.sync.aligned;" ::: "memory"); }
__device__ __forceinline__ void wg_commit() { asm volatile("wgmma.commit_group.sync.aligned;" ::: "memory"); }
template <int N> __device__ __forceinline__ void wg_wait() { asm volatile("wgmma.wait_group.sync.aligned %0;" ::"n"(N) : "memory"); }
template <int N> __device__ __forceinline__ void acc_fence(float (&d)[N]) {
#pragma unroll
  for (int i = 0; i < N; i++) asm volatile("" : "+f"(d[i]) :: "memory");
}
#define O4(d, i) "+f"(d[i]), "+f"(d[i + 1]), "+f"(d[i + 2]), "+f"(d[i + 3])
template <int TB, int ACC>
__device__ __forceinline__ void wg_rs24(float (&d)[12], const uint32_t (&a)[4], uint64_t db) {
  asm volatile("wgmma.mma_async.sync.aligned.m64n24k16.f32.bf16.bf16 {%0,%1,%2,%3,%4,%5,%6,%7,%8,%9,%10,%11}, {%12,%13,%14,%15}, %16, %17, 1, 1, %18;"
               : O4(d, 0), O4(d, 4), O4(d, 8) : "r"(a[0]), "r"(a[1]), "r"(a[2]), "r"(a[3]), "l"(db), "n"(ACC), "n"(TB));
}
template <int TB, int ACC>
__device__ __forceinline__ void wg_rs32(float (&d)[16], const uint32_t (&a)[4], uint64_t db) {
  asm volatile("wgmma.mma_async.sync.aligned.m64n32k16.f32.bf16.bf16 {%0,%1,%2,%3,%4,%5,%6,%7,%8,%9,%10,%11,%12,%13,%14,%15}, {%16,%17,%18,%19}, %20, %21, 1, 1, %22;"
               : O4(d, 0), O4(d, 4), O4(d, 8), O4(d, 12) : "r"(a[0]), "r"(a[1]), "r"(a[2]), "r"(a[3]), "l"(db), "n"(ACC), "n"(TB));
}
template <int ACC>
__device__ __forceinline__ void wg_rs64(float (&d)[32], uint32_t a0, uint32_t a1, uint32_t a2, uint32_t a3, uint64_t db) {
  asm volatile("wgmma.mma_async.sync.aligned.m64n64k16.f32.bf16.bf16 {%0,%1,%2,%3,%4,%5,%6,%7,%8,%9,%10,%11,%12,%13,%14,%15,"
               "%16,%17,%18,%19,%20,%21,%22,%23,%24,%25,%26,%27,%28,%29,%30,%31}, {%32,%33,%34,%35}, %36, %37, 1, 1, 0;"
               : O4(d, 0), O4(d, 4), O4(d, 8), O4(d, 12), O4(d, 16), O4(d, 20), O4(d, 24), O4(d, 28)
               : "r"(a0), "r"(a1), "r"(a2), "r"(a3), "l"(db), "n"(ACC));
}
template <int ACC>
__device__ __forceinline__ void wg_ss24(float (&d)[12], uint64_t da, uint64_t db) {
  asm volatile("wgmma.mma_async.sync.aligned.m64n24k16.f32.bf16.bf16 {%0,%1,%2,%3,%4,%5,%6,%7,%8,%9,%10,%11}, %12, %13, %14, 1, 1, 1, 0;"
               : O4(d, 0), O4(d, 4), O4(d, 8) : "l"(da), "l"(db), "n"(ACC));
}
template <int ACC>
__device__ __forceinline__ void wg_rs40(float (&d)[20], const uint32_t (&a)[4], uint64_t db) {
  asm volatile("wgmma.mma_async.sync.aligned.m64n40k16.f32.bf16.bf16 {%0,%1,%2,%3,%4,%5,%6,%7,%8,%9,%10,%11,%12,%13,%14,%15,%16,%17,%18,%19}, {%20,%21,%22,%23}, %24, %25, 1, 1, 1;"
               : O4(d, 0), O4(d, 4), O4(d, 8), O4(d, 12), O4(d, 16) : "r"(a[0]), "r"(a[1]), "r"(a[2]), "r"(a[3]), "l"(db), "n"(ACC));
}

struct Row { uint32_t w[8]; };
__device__ __forceinline__ uint32_t add_bf16x2(uint32_t a, uint32_t b) {
  uint32_t d; asm("add.rn.bf16x2 %0, %1, %2;" : "=r"(d) : "r"(a), "r"(b)); return d;
}
__device__ __forceinline__ Row warp_ln(const Row& r, float& extra) {
  float x[16];
#pragma unroll
  for (int i = 0; i < 8; i++) { x[2 * i] = bf_lo(r.w[i]); x[2 * i + 1] = bf_hi(r.w[i]); }
  float m = (((x[0] + x[1]) + (x[2] + x[3])) + ((x[4] + x[5]) + (x[6] + x[7]))) + (((x[8] + x[9]) + (x[10] + x[11])) + ((x[12] + x[13]) + (x[14] + x[15])));
  m *= (1.f / 16);
  float v0 = 0.f, v1 = 0.f;
#pragma unroll
  for (int i = 0; i < 16; i += 2) { const float d0 = x[i] - m, d1 = x[i + 1] - m; v0 = fmaf(d0, d0, v0); v1 = fmaf(d1, d1, v1); }
  float v = v0 + v1;
#pragma unroll
  for (int o = 1; o <= 16; o <<= 1) {
    const float mo = __shfl_xor_sync(~0u, m, o), vo = __shfl_xor_sync(~0u, v, o);
    extra += __shfl_xor_sync(~0u, extra, o);
    const float d = mo - m;
    v = fmaf(d * d, 8.f * o, v + vo);
    m = 0.5f * (m + mo);
  }
  const float var = fmaf(v, 1.f / DM, 1e-5f);
  float rs = rsqrtf(var);
  rs = rs * fmaf(-0.5f * var * rs, rs, 1.5f);
  Row y;
#pragma unroll
  for (int i = 0; i < 8; i++) y.w[i] = pack_bf16((x[2 * i] - m) * rs, (x[2 * i + 1] - m) * rs);
  return y;
}
__device__ __forceinline__ Row warp_ln(const Row& r) { float e = 0.f; return warp_ln(r, e); }
__device__ __forceinline__ Row load_row(const bf16* p, int lane) {
  Row r;
#pragma unroll
  for (int q = 0; q < 4; q++) { const uint2 v = ld_rlx64(p + lane * 4 + q * 128); r.w[2 * q] = v.x; r.w[2 * q + 1] = v.y; }
  return r;
}
__device__ __forceinline__ void store_row_img(uint8_t* img, int rr, int lane, const Row& r) {
  uint8_t* p = img + (lane >> 4) * 4096 + rr * 128 + ((((lane & 15) >> 1) ^ (rr & 7)) << 4) + (lane & 1) * 8;
#pragma unroll
  for (int q = 0; q < 4; q++) *(uint2*)(p + q * 8192) = make_uint2(r.w[2 * q], r.w[2 * q + 1]);
}

constexpr int C_WO = 0;
constexpr int C_X = 49152;
constexpr int C_M = C_X + 65536;
constexpr int C_Q = C_M + 24576;
constexpr int C_K = C_Q + 10240, C_V = C_K + 10240;
constexpr int C_SA = C_V + 10240, C_SB = C_SA + 8192;
constexpr int C_O = C_SB + 8192;
constexpr int C_OT = C_O + 6144;
constexpr int C_PI = C_OT + 16384;
constexpr int C_BAR = C_PI + 8192;
constexpr int C_SMEM = C_BAR + 384 + 1024 + TREXTRA;
constexpr int C_STG = C_X + 32768;
static_assert(C_STG + 131072 <= C_BAR, "staging");
enum { B_M0 = 0, B_M1, B_M2, B_X, B_O, B_T, B_F, B_XL, B_U, B_P1, B_P2, B_OT, B_XF, B_XA, B_I, B_PI, B_J, B_W, B_WO, B_NUM };
static_assert(B_NUM <= 24, "barriers");
constexpr int C_POL = C_BAR + 192, C_INFO = C_BAR + 208;
enum { NB_ALL = 0, NB_M0, NB_PV, NB_W0, NB_TA, NB_M1, NB_M2, NB_RD, NB_SM, NB_C, NB_GO };
constexpr float SCALE_LOG2E = 0.08838834764831845f * 1.4426950408889634f;
#define N0STEPS 9
#define N2STEPS 12
#define FGATE 1
#define NSSTEPS 0
constexpr int KA = 32 - NSSTEPS - N2STEPS, K3 = KA - N0STEPS;
static_assert(KA % 4 == 0, "the rows of layer 1 are refilled in two parts");
#define BGATE 0
#define W0EARLY 0
#define PVEARLY 1
#define S1GATE 0
#define IGRP 0
#define SHIPLATE 7
#define SHIP 1024
#define GATE_P 2250
#define GATE_W 170
#define EXPF 0
#define GATE_G 170
#define GATE_M 3230
#define HOLE0 22
#define HOLE1 28
#define HOLE2 32
__device__ __forceinline__ uint32_t gtime() { uint32_t t; asm volatile("mov.u32 %0, %%globaltimer_lo;" : "=r"(t) :: "memory"); return t; }
__device__ __forceinline__ void wait_clock(uint32_t t) {
  asm volatile("{ .reg .pred p; .reg .b32 c; .reg .b64 cc;\nL: mov.u64 cc, %%clock64; cvt.u32.u64 c, cc; sub.u32 c, c, %0; setp.lt.s32 p, c, 0; @p bra L; }" ::"r"(t) : "memory");
}
__device__ __forceinline__ void bar_sync_z(int id, int n, uint32_t z) {
  asm volatile("{ .reg .pred p; setp.eq.u32 p, %2, 0; @p bar.sync %0, %1; }" ::"r"(id), "r"(n), "r"(z) : "memory");
}

__device__ __forceinline__ int probe_home(uint32_t* p, int lane) {
  uint32_t best[2] = {~0u, ~0u};
#pragma unroll 1
  for (int rep = 0; rep < 3; rep++) {
#pragma unroll
    for (int pg = 0; pg < 2; pg++) {
      uint32_t t0, t1, v = 0;
      asm volatile("mov.u32 %0, %%clock;" : "=r"(t0) :: "memory");
      asm volatile("{ .reg .pred p; setp.eq.u32 p, %2, 0; @p atom.relaxed.gpu.global.exch.b32 %0, [%1], %3; }" : "+r"(v) : "l"(p + pg * 1024), "r"(lane), "r"(rep) : "memory");
      asm volatile("{ .reg .pred p; setp.ne.u32 p, %1, 0x13572468; mov.u32 %0, 0; @p mov.u32 %0, %%clock; }" : "=r"(t1) : "r"(v) : "memory");
      best[pg] = min(best[pg], t1 - t0);
    }
  }
  return __shfl_sync(~0u, max(-150, min(150, (int)(best[1] - best[0]))), 0);
}
__device__ __forceinline__ uint32_t home_flip(const void* p) { const uint32_t a = (uint32_t)(size_t)p; return ((a >> 16) ^ (a >> 17) ^ (a >> 19)) & 1; }
__device__ __forceinline__ uint32_t ppage(uint32_t lp, uint32_t pol) { return lp ? 3 - pol : pol; }
__device__ __forceinline__ uint32_t and_x(uint32_t a, uint32_t b, uint32_t m) {
  uint32_t d; asm("lop3.b32 %0, %1, %2, %3, 0x42;" : "=r"(d) : "r"(a), "r"(b), "r"(m)); return d;
}
__device__ __forceinline__ uint32_t and3(uint32_t a, uint32_t b, uint32_t c) {
  uint32_t d; asm("lop3.b32 %0, %1, %2, %3, 0x80;" : "=r"(d) : "r"(a), "r"(b), "r"(c)); return d;
}

template <int N> struct IC { static constexpr int value = N; };
template <class F> __device__ __forceinline__ void static_for2(F f) { f(IC<0>()); f(IC<1>()); }
template <class F> __device__ __forceinline__ void static_for3(F f) { f(IC<0>()); f(IC<1>()); f(IC<2>()); }
__device__ __forceinline__ void stage_weights(uint32_t stage, const CUtensorMap* map, int col, int row, uint32_t mbar) {
  mbar_expect_tx(mbar, 131072);
#pragma unroll 1
  for (int i = 0; i < 4; i++)
    asm volatile("cp.async.bulk.tensor.2d.shared::cluster.global.mbarrier::complete_tx::bytes [%0], [%1, {%3, %4}], [%2];"
                 ::"r"(stage + (i & 1) * 65536 + (i >> 1) * 32768), "l"(map), "r"(mbar), "r"(col + (i & 1) * 64), "r"(row + (i >> 1) * 256) : "memory");
}
__device__ __forceinline__ void load_wfrags(uint32_t (&wA)[32][4], uint32_t stage, int w, int lane) {
  const int mi = lane >> 3, r = lane & 7;
  const uint32_t a = stage + (w >> 2) * 65536 + ((mi >> 1) * 8 + r) * 128 + ((((w & 3) * 2 + (mi & 1)) ^ r) << 4);
#pragma unroll
  for (int ks = 0; ks < 32; ks++) ldsm4t(wA[ks], a + ks * 2048);
}
template <int K0, int K1>
__device__ __forceinline__ void tok_seq(float (&d)[16], const uint32_t (&wA)[32][4], uint64_t desc, uint32_t wave) {
#pragma unroll
  for (int k = K0; k < K1; k++) {
    const int ks = k & 31;
    constexpr int HM0 = 1, HM1 = 2, HM2 = 4;
    const int hm = (k == HOLE0 ? HM0 : 0) | (k == HOLE1 ? HM1 : 0) | (k == HOLE2 ? HM2 : 0);
    if (hm) bar_sync_z(NB_RD, 384, ((hm >> wave) & 1) ^ 1);
    if (ks == 0) wg_rs32<0, 0>(d, wA[ks], desc);
    else wg_rs32<0, 1>(d, wA[ks], desc + (ks >> 2) * 256 + (ks & 3) * 2);
  }
}
template <int K0, int K1>
__device__ __forceinline__ void mem_part(float (&d)[12], const uint32_t (&wA)[32][4], uint64_t desc) {
#pragma unroll
  for (int ks = K0; ks < K1; ks++) {
    if (ks == 0) wg_rs24<1, 0>(d, wA[ks], desc);
    else wg_rs24<1, 1>(d, wA[ks], desc + ks * 48);
  }
}
__device__ __forceinline__ void out_tile(float (&d)[12], uint64_t da, uint64_t db) {
#pragma unroll
  for (int i = 0; i < 8; i++) { if (i == 0) wg_ss24<0>(d, da, db); else wg_ss24<1>(d, da + i * 128, db + (i >> 1) * 32 + (i & 1) * 2); }
}
__device__ __forceinline__ void tok_pack(uint32_t (&p)[8], const float (&d)[16]) {
#pragma unroll
  for (int i = 0; i < 8; i++) p[i] = pack_bf16(d[2 * i], d[2 * i + 1]);
}
__device__ __forceinline__ void tok_store(uint32_t dst, const uint32_t (&p)[8]) {
  stsm4(dst, p[0], p[1], p[2], p[3]);
  stsm4(dst + 4096, p[4], p[5], p[6], p[7]);
}
template <class T> __device__ __forceinline__ T keep(T v) { asm volatile("" : "+r"(v)); return v; }
__device__ __forceinline__ uint32_t pin(uint32_t v) { return __shfl_sync(~0u, v, threadIdx.x & 31); }

#define TRC blockIdx.x
#define TRS (C_BAR + 384)
__device__ __forceinline__ void chain_proj(const uint32_t sb, const int w, const int lane_, const uint32_t rank) {
  uint32_t wA[32][4];
  mbar_wait(sb + C_BAR + B_W * 8, 0, 30);
  if (w == 0) { HD(2) }
  load_wfrags(wA, sb + C_STG, w, lane_);
  bar_arrive(NB_ALL, 384);
  const int lane = pin(lane_);
  const uint32_t bars = sb + C_BAR;
  const uint32_t quad = pin(sb + (lane_ >> 4) * 2048 + (lane_ & 15) * 16);
  const uint32_t own = C_Q + rank * 10240;
  const uint64_t dX1 = mk_desc(sb + C_X, 16, 1024, 1), dX2 = dX1 + 2048;
  const uint64_t dM = mk_desc(sb + C_M, 128, 256, 0);
  const uint32_t r1 = rank == 0 ? 1 : 0, r2 = rank == 2 ? 1 : 2;
  const uint32_t xa = pin(sb + own + 8192 + w * 256 + lane_ * 4);
  const uint32_t a1x = pin(mapa_u32(xa, r1)), a2x = pin(mapa_u32(xa, r2));
  const uint32_t b1x = pin(mapa_u32(bars + B_X * 8, r1)), b2x = pin(mapa_u32(bars + B_X * 8, r2));
  const uint32_t wave = rank == 2 ? 0 : rank + 1;
  float a[16];
  wg_fence();
  tok_seq<32, 32 + KA>(a, wA, mk_desc(__shfl_sync(~0u, sb, 0) + C_X, 16, 1024, 1), 3);
  wg_commit();
  wg_wait<0>();
  mbar_arrive_z(bars + B_XA * 8, lane);
#pragma unroll 1
  for (int st = 0;; st++) {
    uint32_t pk[8];
    wg_fence();
    if (NSSTEPS) bar_sync(NB_SM, 416);
    tok_seq<32 + KA, 32 + KA + NSSTEPS>(a, wA, dX1, 3);
    bar_sync(NB_PV, NSSTEPS ? 384 : 416);
    tok_seq<32 + KA + NSSTEPS, 64>(a, wA, dX1, 3);
    wg_commit();
    wg_wait<0>();
    acc_fence(a);
    mbar_arrive_z(bars + B_XF * 8, lane);
    tok_pack(pk, a);
    TR(1)
    bar_sync(NB_W0, 416);
    tok_store(quad + w * 256 + (rank == 0 ? own : C_SA), pk);
    __syncwarp();
    mbar_arrive_z(bars + B_P1 * 8, lane);
    wg_fence();
    tok_seq<0, 32>(a, wA, dX2, wave);
    wg_commit();
    const uint32_t info = lds32(sb + C_INFO + (st & 1) * 4);
    TR(2)
    wg_wait<0>();
    acc_fence(a);
    TR(3)
    tok_pack(pk, a);
    tok_store(quad + w * 256 + (rank == 0 ? C_SA : own), pk);
    if (rank == 2) tok_store(quad + w * 256 + C_SB, pk);
    __syncwarp();
    mbar_arrive_z(bars + B_P2 * 8, lane);
    TR(4)
    wg_fence();
    tok_seq<32, 32 + K3>(a, wA, dX1, wave);
    TR(6)
    {
      float am[12];
      bar_sync(NB_M0, 384);
      mem_part<0, 10>(am, wA, dM);
      TR(7)
      bar_sync(NB_M1, 384);
      mem_part<10, 21>(am, wA, dM);
      bar_sync(NB_M2, 384);
      const uint32_t bad = lds32(sb + C_INFO + 16 + (lane & 3) * 32);
      mem_part<21, 32>(am, wA, dM);
      wg_commit();
      const bool redo = __any_sync(~0u, bad != 0);
      if (__builtin_expect(redo, 0)) {
        wg_wait<0>();
        int it = 0;
        while (__any_sync(~0u, lds32_poll(sb + C_INFO + 20 + (lane & 3) * 32) != st && bad)) give_up(++it, 50 * SPIN_LIMIT, 31);
        wg_fence();
        mem_part<0, 32>(am, wA, dM);
        wg_commit();
      }
      wg_wait<0>();
      acc_fence(am);
      TR(8)
      const uint32_t x00 = pack_bf16(am[0], am[1]), x01 = pack_bf16(am[2], am[3]), x10 = pack_bf16(am[4], am[5]), x11 = pack_bf16(am[6], am[7]);
      const uint32_t y0 = pack_bf16(am[8], am[9]), y1 = pack_bf16(am[10], am[11]), x20 = info ? x10 : y0, x21 = info ? x11 : y1;
      st_async32<0>(a1x, rank == 0 ? x10 : x00, b1x); st_async32<0>(a2x, rank == 2 ? x10 : x20, b2x);
      st_async32<128>(a1x, rank == 0 ? x11 : x01, b1x); st_async32<128>(a2x, rank == 2 ? x11 : x21, b2x);
      sts32(xa, rank == 0 ? x00 : rank == 2 ? x20 : x10); sts32(xa + 128, rank == 0 ? x01 : rank == 2 ? x21 : x11);
      if (__builtin_expect(info, 0)) {
        const uint32_t o = (info & 3) * 2048 - 8192;
        if (rank == 2) { sts32(xa + o, y0); sts32(xa + o + 128, y1); }
        else { st_async32<0>(a2x + o, y0, b2x + (B_T - B_X) * 8); st_async32<128>(a2x + o, y1, b2x + (B_T - B_X) * 8); }
      }
      __syncwarp();
      mbar_arrive_z(bars + B_X * 8, lane);
    }
    TR(9)
    wg_fence();
    tok_seq<32 + K3, 32 + KA>(a, wA, dX1, 3);
    wg_commit();
    TR(0)
    wg_wait<0>();
    if (st == NSTEP - 1) break;
    mbar_arrive_z(bars + B_XA * 8, lane);
  }
  if (NSSTEPS) bar_arrive(NB_SM, 416);
  bar_arrive(NB_PV, NSSTEPS ? 384 : 416);
}

__device__ __forceinline__ void chain_mem(const uint32_t sb, const int w, const int lane_, const uint32_t rank, const int h,
                                          const bf16* __restrict__ mem0) {
  const int lane = pin(lane_);
  const int wave = rank == 2 ? 0 : rank + 1;
  const int c = w - 8, t = c * 32 + lane, b = wave * 32 + h;
  const uint32_t bars = sb + C_BAR;
  const int wi = (lane & 1) * 2 + (lane >> 4), cq = (lane >> 2) & 3;
  mbar_expect_tx_z(bars + B_X * 8, 4096, t); mbar_expect_tx_z(bars + B_O * 8, 4096, t);
  if (NSSTEPS) bar_arrive(NB_SM, 416);
  bar_arrive(NB_PV, NSSTEPS ? 384 : 416); bar_arrive(NB_W0, 416); bar_arrive(NB_RD, 384);
  uint32_t m0[16];
#pragma unroll
  for (int i = 0; i < 16; i++) m0[i] = *(const uint32_t*)(mem0 + (lane >> 2) * DM + (c * 16 + i) * 8 + (lane & 3) * 2);
  uint32_t* pp = g_M + c * 16384 + 14 * 1024 + (blockIdx.x & 31) * 32;
  st_rlx32(pp + lane, 0); st_rlx32(pp + 1024 + lane, 0);
  mbar_wait(bars + B_W * 8, 0, 32);
  {
    uint32_t* p = pp;
    const int vote = probe_home(p, lane);
    sts32(sb + C_POL + c * 4, home_flip(p) ? -vote : vote);
    bar_sync(NB_C, 128);
    const uint4 v = lds128(sb + C_POL);
    const uint32_t side = (int)(v.x + v.y + v.z + v.w) > 0;
    bar_sync(NB_C, 128);
    sts32(sb + C_POL + c * 4, side ^ home_flip(p));
    sts32(sb + C_INFO + 8, side ^ home_flip(g_P + b * 4096));
    if (c == 0) { HD(0) }
    wait_count(g_ex.ready, 96, 35);
    if (c == 0) { HD(1) }
    st_rlx32(&g_fl.pol[b], (side ^ home_flip(g_P + b * 4096)) + 1);
  }
  bar_sync(NB_ALL, 384);
  if (c == 0) { HD(3) }
  mbar_arrive_remote_z(mapa_u32(bars + B_F * 8, (rank + 1 + (t & 1)) % 3), t >> 1);
#pragma unroll
  for (int i = 0; i < 16; i += 4) {
    const uint32_t a = sb + C_M + (c * 8 + i / 2 + (lane >> 4)) * 768 + (lane & 15) * 16;
    stsm4t(a, m0[i], m0[i + 1], m0[i + 2], m0[i + 3]); stsm4t(a + 256, m0[i], m0[i + 1], m0[i + 2], m0[i + 3]); stsm4t(a + 512, m0[i], m0[i + 1], m0[i + 2], m0[i + 3]);
  }
  sts32(sb + C_INFO + 16 + c * 32, 0); sts32(sb + C_INFO + 20 + c * 32, 0);
  fence_async_smem();
  bar_arrive(NB_M0, 384); bar_arrive(NB_M1, 384);
  mbar_wait(bars + B_F * 8, 0, 34);
  bar_arrive(NB_M2, 384);
  mbar_wait(bars + B_WO * 8, 0, 33);
  uint32_t pgbits, polP;
  {
    const int tl = lane / 3, u = ((tl * 3 + rank) * 4 + c) * 3 + (lane - tl * 3);
    uint32_t pol;
    int it = 0;
    do { pol = ld_rlx32(&g_fl.pol[lane < 9 && u < 96 ? u : b]); give_up(it++, SPIN_LIMIT, 40); } while (__any_sync(~0u, pol == 0));
    pgbits = __reduce_or_sync(~0u, lane < 9 ? ppage(h >> 4, (pol - 1) & 1) << (2 * lane) : 0u);
    polP = __shfl_sync(~0u, pol - 1, 9);
  }
  const int mi = lane >> 3;
  const uint32_t l16 = pin(sb + lane * 16);
  const uint32_t r1 = rank == 2 ? 0 : rank + 1, r2 = rank == 0 ? 2 : rank - 1;
  const uint32_t oa = pin(sb + C_O + rank * 2048 + (lane >> 2) * 64 + (((lane & 3) ^ (lane >> 3)) << 4));
  const uint32_t a1 = mapa_u32(oa, r1), b1 = mapa_u32(bars + B_O * 8, r1), a2 = mapa_u32(oa, r2), b2 = mapa_u32(bars + B_O * 8, r2);
  const uint64_t dWo = mk_desc(sb + C_WO, 8192, 1024, 1), dO = mk_desc(sb + C_O, 16, 2048, 2);
  const uint64_t dK = mk_desc(sb + C_K, 128, 2048, 0);
  const uint64_t dV = mk_desc(sb + C_V, 2048, 128, 0), dVm = mk_desc(sb + C_V + 8192, 0, 128, 0);
  const uint32_t qa = pin(sb + C_Q + (c ? c + 1 : mi & 1) * 2048 + (mi >> 1) * 128 + (lane & 7) * 16);
  const uint32_t dg = ((lane >> 2) < 2 * (lane & 3) ? 1 : 0) | ((lane >> 2) < 2 * (lane & 3) + 1 ? 2 : 0);
  const uint32_t msk = pin(c == 0 ? dg | dg << 4 : c == 1 ? dg << 2 | 3 << 4 : c == 2 ? dg << 4 : 0);
  uint8_t* Pw = (uint8_t*)g_P + (rank * 4 + c) * 3 * 16384 + (h & 15) * 256 + ((lane * 4) ^ ((h & 3) << 5));
  const uint32_t pia = pin(sb + C_PI + ((lane >> 4) * 4 + (lane & 3)) * 256 + ((c * 64 + cq * 16) ^ ((lane & 3) << 5)));
  uint8_t* Mw = (uint8_t*)g_M + (b >> 5) * 16384 + ((lane & 2) ? 4096 : 12288) + (b & 31) * 256 + c * 64 + cq * 16 + wi * 4;
  uint32_t nupd = 0;
  bar_arrive(NB_GO, 160);

  { const int st = 71; (void)st; STAT(0, lds32(sb + C_POL + c * 4)) STAT(1, polP) STAT(2, (uint32_t)(size_t)(g_M + c * 16384)) STAT(3, (uint32_t)(size_t)(g_P + b * 4096)) }
#pragma unroll 1
  for (int st = 0;; st++) {
    mbar_wait(bars + B_P1 * 8, st & 1, 38);
    mbar_wait(bars + B_T * 8, st & 1, 42);
    STAT(10, clk32())
    {
      float s[20];
      {
        uint32_t q[8][4];
        if (c == 3) mbar_wait(bars + B_X * 8, st & 1, 41);
#pragma unroll
        for (int i = 0; i < 8; i++) ldsm4t(q[i], qa + i * 256);
        if (c != 3) { mbar_wait(bars + B_X * 8, st & 1, 41); fence_async_smem(); }
        STAT(11, clk32())
        TR(0)
        wg_fence();
#pragma unroll
        for (int i = 0; i < 8; i++) { if (i == 0) wg_rs40<0>(s, q[i], dK); else wg_rs40<1>(s, q[i], dK + i * 16); }
        wg_commit();
        wg_wait<0>();
        if (NSSTEPS) bar_arrive(NB_SM, 416);
        acc_fence(s);
      }
      TR(1)
      const bool w0 = c == 0;
      float z[10] = {s[16], s[17], s[0], s[1], w0 ? s[18] : s[4], w0 ? s[19] : s[5], w0 ? s[2] : s[8], w0 ? s[3] : s[9], w0 ? s[6] : s[12], w0 ? s[7] : s[13]};
      if (msk & 1) z[2] = -INFINITY;
      if (msk & 2) z[3] = -INFINITY;
      if (msk & 4) z[6] = -INFINITY;
      if (msk & 8) z[7] = -INFINITY;
      if (msk & 16) z[8] = -INFINITY;
      if (msk & 32) z[9] = -INFINITY;
      float m0 = fmaxf(fmaxf(z[0], z[1]), fmaxf(z[2], z[3])), m1 = fmaxf(fmaxf(fmaxf(z[4], z[5]), fmaxf(z[6], z[7])), fmaxf(z[8], z[9]));
      m0 = fmaxf(m0, __shfl_xor_sync(~0u, m0, 1)); m1 = fmaxf(m1, __shfl_xor_sync(~0u, m1, 1));
      m0 = fmaxf(m0, __shfl_xor_sync(~0u, m0, 2)); m1 = fmaxf(m1, __shfl_xor_sync(~0u, m1, 2));
      if (!w0) m0 = m1 = fmaxf(m0, m1);
      m0 *= -SCALE_LOG2E; m1 *= -SCALE_LOG2E;
      uint32_t p[5];
#pragma unroll
      for (int k = 0; k < 5; k++) {
        z[2 * k] = ex2_fast(fmaf(z[2 * k], SCALE_LOG2E, k < 2 ? m0 : m1)); z[2 * k + 1] = ex2_fast(fmaf(z[2 * k + 1], SCALE_LOG2E, k < 2 ? m0 : m1));
        p[k] = pack_bf16(z[2 * k], z[2 * k + 1]);
      }
      const uint32_t p2 = w0 ? 0 : p[2], p3 = w0 ? 0 : p[3], p4 = w0 ? 0 : p[4];
      float oA[32], oB[32];
      wg_fence();
      wg_rs64<0>(oA, p[0], p[2], 0, 0, dVm); wg_rs64<1>(oA, p[1], p[3], p2, p[4], dV); wg_rs64<1>(oA, p3, 0, p4, 0, dV + 256);
      wg_commit();
      wg_rs64<0>(oB, p[0], p[2], 0, 0, dVm + 64); wg_rs64<1>(oB, p[1], p[3], p2, p[4], dV + 64); wg_rs64<1>(oB, p3, 0, p4, 0, dV + 320);
      wg_commit();
      float l0 = (z[0] + z[1]) + (z[2] + z[3]), l1 = ((z[4] + z[5]) + (z[6] + z[7])) + (z[8] + z[9]);
      if (!w0) l0 += l1;
      l0 += __shfl_xor_sync(~0u, l0, 1); l1 += __shfl_xor_sync(~0u, l1, 1);
      l0 += __shfl_xor_sync(~0u, l0, 2); l1 += __shfl_xor_sync(~0u, l1, 2);
      float i0, i1;
      asm volatile("rcp.approx.ftz.f32 %0, %2; rcp.approx.ftz.f32 %1, %3;" : "=f"(i0), "=f"(i1) : "f"(l0), "f"(l1));
      asm volatile("st.shared.v2.f32 [%0], {%1,%2};" ::"r"(sb + C_INFO + 24), "f"(i0), "f"(i1) : "memory");
      const uint32_t ta = l16 + C_OT + (st & 1) * 8192 + (c ? c + 1 : 0) * 2048;
      auto leave = [&](const float (&o)[32], auto hc) {
        constexpr int H = decltype(hc)::value;
        uint32_t e[8];
#pragma unroll
        for (int j = 0; j < 8; j++) e[j] = pack_bf16(o[4 * j] * i0, o[4 * j + 1] * i0);
        if (c == 3) {
          static_for2([&](auto bc) {
            constexpr int B = decltype(bc)::value;
            asm volatile("st.async.weak.shared::cluster.mbarrier::complete_tx::bytes.v4.b32 [%0 + %9], {%5,%6,%7,%8}, [%1];\n"
                         "st.async.weak.shared::cluster.mbarrier::complete_tx::bytes.v4.b32 [%2 + %9], {%5,%6,%7,%8}, [%3];\n"
                         "st.shared.v4.b32 [%4 + %9], {%5,%6,%7,%8};"
                         ::"r"(a1), "r"(b1), "r"(a2), "r"(b2), "r"(oa), "r"(e[4 * B]), "r"(e[4 * B + 1]), "r"(e[4 * B + 2]), "r"(e[4 * B + 3]),
                           "n"(H * 1024 + B * 512) : "memory");
          });
        } else {
          stsm4(ta + H * 1024, e[0], e[1], e[2], e[3]); stsm4(ta + H * 1024 + 512, e[4], e[5], e[6], e[7]);
          if (w0) {
#pragma unroll
            for (int j = 0; j < 8; j++) e[j] = pack_bf16(o[4 * j + 2] * i1, o[4 * j + 3] * i1);
            stsm4(ta + 2048 + H * 1024, e[0], e[1], e[2], e[3]); stsm4(ta + 2048 + H * 1024 + 512, e[4], e[5], e[6], e[7]);
          }
        }
      };
      wg_wait<1>();
      acc_fence(oA);
      leave(oA, IC<0>());
      wg_wait<0>();
      if (PVEARLY) bar_arrive(NB_PV, NSSTEPS ? 384 : 416);
      acc_fence(oB);
      leave(oB, IC<1>());
      if (!PVEARLY) bar_arrive(NB_PV, NSSTEPS ? 384 : 416);
      __syncwarp();
      mbar_arrive_z(bars + (c == 3 ? B_O : B_OT) * 8, lane);
      TR(2)
    }
    mbar_wait(bars + B_O * 8, st & 1, 43);
    if (st == NSTEP - 1) break;
    uint32_t info;
    {
      const uint32_t tag = (st & 1) ^ 1;
      float oc0[12], oc1[12], oc2[12];
      fence_async_smem();
      TR(3)
      wg_fence();
      out_tile(oc0, dWo, dO);
      wg_commit();
      out_tile(oc1, dWo + 1024, dO);
      wg_commit();
      asm volatile("" : "+r"(pgbits));
      auto put = [&](const float (&oc)[12], auto tlc) {
        constexpr int TL = decltype(tlc)::value;
        static_for3([&](auto jc) {
          constexpr int j = decltype(jc)::value;
          uint8_t* p = Pw + ((pgbits >> (2 * (TL * 3 + j))) & 3) * 4096;
          asm volatile("st.relaxed.gpu.global.u32 [%0 + %3], %1; st.relaxed.gpu.global.u32 [%0 + %3 + 128], %2;" ::"l"(p),
                       "r"((pack_bf16(oc[4 * j], oc[4 * j + 1]) & ~1u) | tag), "r"((pack_bf16(oc[4 * j + 2], oc[4 * j + 3]) & ~1u) | tag),
                       "n"((TL * 36 + j) * 16384) : "memory");
        });
      };
      wg_wait<1>();
      acc_fence(oc0);
      put(oc0, IC<0>());
      sts32(sb + C_INFO + 24, clk32());
      TR(4)
      out_tile(oc2, dWo + 2048, dO);
      wg_commit();
      wg_wait<1>();
      acc_fence(oc1);
      put(oc1, IC<1>());
      if (W0EARLY) bar_arrive(NB_W0, 416);
      bar_sync(NB_TA, 192);
      TR(5)
      wg_wait<0>();
      if (!W0EARLY) bar_arrive(NB_W0, 416);
      info = lds32(sb + C_INFO + ((st + 1) & 1) * 4);
      acc_fence(oc2);
      if (rank != 2) put(oc2, IC<2>());
      mbar_arrive_remote_z(((t & 1) ? b2 : b1) + (B_F - B_O) * 8, t >> 1);
      mbar_expect_tx_z(bars + ((t & 1) ? B_O : B_X) * 8, 4096, t >> 1);
      TR(6)
    }
    const int sn = (st + 1) & 3;
    uint8_t* mw = Mw + sn * 65536;
    asm volatile("" : "+l"(mw));
    if (__builtin_expect((st < DELTA && b % 3 != 0) || (info && b % 3 == 2), 0)) {
      bar_arrive(NB_RD, 384);
      const int col = b / 3 * 16 + c * 4 + ((lane >> 2) & 3), r0 = (lane & 1) * 4 + (lane >> 4) * 2;
      const bool upd = info && b % 3 == 2;
      if (upd) mbar_wait(bars + B_U * 8, nupd & 1, 39);
      uint32_t hv[2];
#pragma unroll
      for (int i = 0; i < 2; i++) {
        const int r = r0 + i, sg = st + 1 - DELTA;
        const void* p = !upd ? (const void*)(mem0 + r * DM + col) : r == (int)(info >> 4) ? (const void*)(g_x2p[sg][1] + col)
                      : (const void*)(g_xs[1] + sg * 32768 + (col >> 6) * 4096 + ((info & 3) * 8 + r) * 128 + ((((col >> 3) ^ r) & 7) << 4) + (col & 7) * 2);
        asm volatile("ld.relaxed.gpu.global.u16 %0, [%1];" : "=r"(hv[i]) : "l"(p) : "memory");
      }
      st_rlx32(mw, hv[0] | hv[1] << 16);
      STAT(1, 0) STAT(2, 0) STAT(4, 0)
    } else {
      const uint32_t flip = (st & 1) ? ~0u : 0u;
      const bool u16 = lane & 16;
      const uint32_t bs = (lane & 4) ? 0x3f800000u : 0x00003f80u, bs0 = (lane & 8) ? 0u : bs, bs1 = (lane & 8) ? bs : 0u;
      STATC(c_rdy)
      mbar_wait(bars + B_PI * 8, st & 1, 37);
      TR(7)
      uint4 q0 = lds128(pia), q1 = lds128(pia + 2048), q2 = lds128(pia + 4096), q3 = lds128(pia + 6144);
      int it = 0;
#pragma unroll 1
      while (true) {
        float d0[4] = {0.f, 0.f, 0.f, 0.f}, d1[4] = {0.f, 0.f, 0.f, 0.f};
        mma16816(d0, q0.x, q0.y, q0.z, q0.w, bs0, bs1);
        mma16816(d1, q1.x, q1.y, q1.z, q1.w, bs0, bs1);
        mma16816(d0, q2.x, q2.y, q2.z, q2.w, bs0, bs1);
        mma16816(d1, q3.x, q3.y, q3.z, q3.w, bs0, bs1);
        const bool all = __all_sync(~0u, (int)and3(and_x(q0.x, q1.x, flip), and_x(q2.x, q3.x, flip), 1u));
        const float a0 = d0[0] + d1[0], a1 = d0[1] + d1[1], a2 = d0[2] + d1[2], a3 = d0[3] + d1[3];
        asm volatile("{ .reg .pred p; setp.ne.u32 p, %0, 0; @p bar.arrive %1, 384; }" ::"r"((uint32_t)all), "n"((int)NB_RD) : "memory");
        const uint32_t mword = pack_bf16((u16 ? a2 : a0) + __shfl_xor_sync(~0u, u16 ? a0 : a2, 16), (u16 ? a3 : a1) + __shfl_xor_sync(~0u, u16 ? a1 : a3, 16));
        asm volatile("{ .reg .pred p; setp.ne.u32 p, %2, 0; @p st.relaxed.gpu.global.u32 [%0], %1; }" ::"l"(mw), "r"(mword), "r"((uint32_t)all) : "memory");
        if (__builtin_expect(all, 1)) break;
        give_up(++it, SPIN_LIMIT, 44);
        const uint8_t* Pr0 = (const uint8_t*)g_P + b * 16384 + (pia - sb - C_PI) + polP * 4096;
        const uint8_t* Pr1 = Pr0 + (3 - 2 * polP) * 4096;
        q0 = ld_rlx128(Pr0); q1 = ld_rlx128(Pr0 + 2048); q2 = ld_rlx128(Pr1); q3 = ld_rlx128(Pr1 + 2048);
      }
      STATC(c_mst)
      STAT(1, c_rdy - tref) STAT(2, c_mst - tref) STAT(4, it)
      TRV(14, it)
    }
    STAT(0, lds32(sb + C_INFO + 24) - tref) STAT(3, tref)
    nupd += info != 0;
    TR(9)
    {
      int it = 0;
      const uint32_t mchk = pin(keep(l16) + C_M + c * 2048 + lane * 16 + (lane & 28));
      auto missing = [&](int g) { return __any_sync(~0u, max(lds32(mchk + g * 8192), lds32(mchk + g * 8192 + 1024)) == ~0u); };
      auto complete = [&](int g) {
        const uint8_t* src = (const uint8_t*)g_M + sn * 65536 + (lds32(sb + C_POL + sn * 4) ? 4096 : 12288) + g * 16384 + c * 2048 + lane * 16;
        uint4 v0, v1, v2, v3;
#pragma unroll 1
        do {
          v0 = ld_rlx128(src); v1 = ld_rlx128(src + 512); v2 = ld_rlx128(src + 1024); v3 = ld_rlx128(src + 1536);
          give_up(++it, SPIN_LIMIT, 48);
        } while (__any_sync(~0u, max(__vimax3_u32(v0.x, v1.x, v2.x), v3.x) == ~0u));
        const uint32_t d = l16 + C_M + g * 8192 + c * 2048;
        sts128(d, v0); sts128(d + 512, v1); sts128(d + 1024, v2); sts128(d + 1536, v3);
        fence_async_smem();
      };
      mbar_wait(bars + B_M0 * 8, (st + 1) & 1, 45);
      bar_arrive(NB_M0, 384);
      STATC(c_g0)
      TR(10)
      const bool redo = missing(0);
      sts32(sb + C_INFO + 16 + c * 32, redo);
      static_for2([&](auto gc) {
        constexpr int g = 1 + decltype(gc)::value;
        mbar_wait(bars + (B_M0 + g) * 8, (st + 1) & 1, 46);
        TR(10 + g)
        const bool m = missing(g);
        asm volatile("{ .reg .pred p; setp.eq.u32 p, %0, 0; @p bar.arrive %1, 384; }" ::"r"((uint32_t)m), "n"(NB_M1 + g - 1) : "memory");
        if (__builtin_expect(m, 0)) { complete(g); bar_arrive(NB_M1 + g - 1, 384); }
        STAT(6 + g, clk32() - tref)
      });
      if (__builtin_expect(redo, 0)) { complete(0); __syncwarp(); sts32(sb + C_INFO + 20 + c * 32, st + 1); }
      STAT(5, c_g0 - tref)
      STAT(9, clk32() - tref) STAT(6, it + redo * 256)
      TR(13)
      TRV(15, it)
      st_rlx32(Mw + (st & 3) * 65536, ~0u);
    }
  }
}

__device__ __forceinline__ void chain_dma(const uint32_t sb, const int w, const int lane, const uint32_t rank, const int h) {
  const uint32_t bars = sb + C_BAR;
  const int expf_ = EXPF;
  if (w == 12) {
    u64 best = 0;
    uint32_t nx = 0;
    auto load = [&](uint32_t dst, const uint8_t* src, uint32_t bytes) {
      mbar_expect_tx_z(bars + B_XL * 8, bytes, lane >> 1);
      if (lane < 2 && bytes) {
        fence_async_glb();
        bulk_g2s(sb + dst, src, bytes, bars + B_XL * 8);
      }
      __syncwarp();
      mbar_wait(bars + B_XL * 8, nx++ & 1, 52);
    };
    bar_arrive(NSSTEPS ? NB_SM : NB_PV, 416);
    wait_count(g_ex.ready, 96, 59);
    HD(6)
#pragma unroll 1
    for (int st = 0; st < NSTEP; st++) {
      const int sg = st - DELTA;
      const bool more = st + 1 < NSEG && !(expf_ & 4);
      uint32_t info = 0;
      if (sg >= 0) {
        const u64 k = wait_keys(g_fl.key[0][sg], lane, 50);
        if (k > best) { best = k; info = 4 | ((key_token(k) >> 3) & 3) | (key_token(k) & 7) << 4; }
      }
      TR(0)
      mbar_wait(bars + B_XA * 8, st & 1, 58);
      sts32(sb + C_INFO + (st & 1) * 4, info);
      if (st > 0) bar_arrive(NB_TA, 192);
      TR(1)
      load(lane ? C_X : C_X + 32768, lane ? g_xs[0] + (st + 1) * 32768 : g_xs[1] + sg * 32768, lane ? (more ? KA * 1024 : 0) : (sg >= 0 && !(expf_ & 8) ? 32768 : 0));
      bar_arrive(NB_W0, 416);
      TR(2)
      if (__builtin_expect(info, 0)) {
        int it = 0;
        while (ld_rlx32(g_fl.patch[sg]) == 0) { give_up(++it, SPIN_LIMIT, 56); warp_sleep(250); }
        sts32(sb + C_INFO + 40, clk32());
        __syncwarp();
        mbar_arrive_z(bars + B_U * 8, lane);
      }
      mbar_wait(bars + B_XF * 8, st & 1, 53);
      mbar_wait(bars + (B_M0 + BGATE) * 8, st & 1, 54);
      load(C_X + KA * 1024, g_xs[0] + (st + 1) * 32768 + KA * 1024, more && lane == 0 ? 32768 - KA * 1024 : 0);
      TR(3)
      bar_arrive(NSSTEPS ? NB_SM : NB_PV, 416);
    }
  } else if (w == 13) {
    constexpr uint32_t NP = 8192 / SHIP;
    const uint32_t o = (lane >> 1) * SHIP, own = sb + C_Q + rank * 10240, bt = bars + B_T * 8;
    const uint32_t d2 = 1 + (lane & 1);
    const uint32_t src2 = (rank == 0 ? sb + C_SA : rank == 1 ? own : sb + C_SB) + o;
    const uint32_t skip = (lane & 1) ? 4 | (o >> 11) : 8;
#pragma unroll 1
    for (int st = 0; st < NSTEP; st++) {
      mbar_wait(bars + B_P1 * 8, st & 1, 61);
      fence_async_smem();
      mbar_wait(bars + B_F * 8, st & 1, 60);
      if (st > 0) mbar_wait(bars + (S1GATE ? B_PI : B_J) * 8, (st - 1) & 1, 65);
      const uint32_t info = lds32(sb + C_INFO + (st & 1) * 4);
      TR(2)
      if (st < NSEG && rank != 0 && lane < 2 * NP && d2 == 1 && !(expf_ & 1)) bulk_s2r(mapa_u32(own + o, 0), sb + C_SA + o, SHIP, mapa_u32(bt, 0));
      __syncwarp();
      TR(3)
      mbar_wait(bars + B_P2 * 8, st & 1, 62);
      fence_async_smem();
      if (st > 0 && (SHIPLATE >> rank & 1)) mbar_wait(bars + B_I * 8, (st - 1) & 1, 64);
      TR(0)
      if (st >= DELTA && lane < 2 * NP && d2 != rank && (info & 7) != skip && !(expf_ & 2)) bulk_s2r(mapa_u32(own + o, d2), src2, SHIP, mapa_u32(bt, d2));
      __syncwarp();
      TR(1)
    }
  } else if (w == 14) {
    const int s0 = rank == 0 ? 0 : DELTA;
    const uint32_t tbytes = (expf_ & (rank ? 2 : 1)) ? 0 : 16384;
    mbar_expect_tx_z(bars + B_T * 8, s0 == 0 ? tbytes : 0, lane);
#pragma unroll 1
    for (int st = 0; st < NSTEP; st++) {
      const int sg = st - s0;
      const bool act = (unsigned)sg < (unsigned)NSEG;
      mbar_wait(bars + B_OT * 8, st & 1, 70);
      mbar_expect_tx_z(bars + B_T * 8, (unsigned)(sg + 1) < (unsigned)NSEG ? tbytes : 0, lane);
      fence_async_smem();
      const int s1 = rank && st < NSEG - 1 ? st + 1 : st;
      if (s1 != st) mbar_wait(bars + B_X * 8, s1 & 1, 71);
      TR(0)
      if (act && lane == 0 && !(expf_ & (rank ? 32 : 16))) {
        bulk_s2g(g_O[st & (OSLOTS - 1)][rank] + h * 8192, sb + C_OT + (st & 1) * 8192, 8192);
        asm volatile("cp.async.bulk.commit_group;" ::: "memory");
        asm volatile("cp.async.bulk.wait_group 0;" ::: "memory");
        asm volatile("fence.acq_rel.gpu;" ::: "memory");
      }
      __syncwarp();
      if (WLAG && s1 < NSTEP - 1) mbar_wait(bars + (FGATE ? B_M0 + FGATE - 1 : B_I) * 8, (s1 + (FGATE > 0)) & 1, 72);
      if (act && lane == 0) asm volatile("red.relaxed.gpu.global.add.u32 [%0], 1;" ::"l"(&g_fl.oflag[rank][sg][h >> 2]) : "memory");
      __syncwarp();
      TR(1)
    }
  } else {
    mbar_arrive_z(bars + B_M0 * 8, lane); mbar_arrive_z(bars + B_M1 * 8, lane); mbar_arrive_z(bars + B_M2 * 8, lane);
    const uint32_t wave = rank == 2 ? 0 : rank + 1, gate_p = GATE_P + wave * GATE_W, gate_g = GATE_G, gate_m = GATE_M;
    uint32_t nupd = 0, late = 128;
    bar_sync(NB_GO, 160);
#pragma unroll 1
    for (int st = 0; st < NSTEP - 1; st++) {
      mbar_wait(bars + B_X * 8, st & 1, 75);
      if (st < 4) { HD(8 + st) }
      if (st == NSTEP - 2) { HD(12) }
      mbar_wait(bars + B_T * 8, st & 1, 77);
      const uint32_t now = gtime() & ~31u, tag = (st + 1) & 31;
      if (lane == 0) st_rlx32(&g_fl.stamp[blockIdx.x], (now + late) | tag);
      late = 0;
      __syncwarp();
      wait_clock(clk32() + 550);
      uint32_t s0, s1, s2;
      int it = 0;
#pragma unroll 1
      do {
        s0 = ld_rlx32(&g_fl.stamp[lane]) ^ tag; s1 = ld_rlx32(&g_fl.stamp[32 + lane]) ^ tag; s2 = ld_rlx32(&g_fl.stamp[64 + lane]) ^ tag;
        give_up(it++, SPIN_LIMIT, 76);
      } while (__any_sync(~0u, ((s0 | s1 | s2) & 31) != 0));
      const uint32_t tref = now + __reduce_max_sync(~0u, __vimax3_s32((int)(s0 - now), (int)(s1 - now), (int)(s2 - now)));
      const uint32_t g0 = gtime();
      uint32_t g1, c1;
      it = 0;
      do { g1 = gtime(); c1 = clk32(); } while (g1 == g0 && ++it < 64);
      c1 -= (g1 - tref) * 7 / 4;
      sts32(sb + C_INFO + 12, c1);
      TR(0)
      bar_sync(NB_TA, 192);
      const int sn = (st + 1) & 3;
      const uint8_t* src = (const uint8_t*)g_M + sn * 65536 + (lds32(sb + C_POL + sn * 4) ? 4096 : 12288);
      {
        const uint32_t pol = lds32(sb + C_INFO + 8);
        const uint8_t* ps = (const uint8_t*)g_P + (wave * 32 + h) * 16384;
        if (lane == 0) {
          mbar_expect_tx(bars + B_PI * 8, 8192);
          wait_clock(c1 + gate_p);
          bulk_g2s(sb + C_PI, ps + pol * 4096, 4096, bars + B_PI * 8);
          bulk_g2s(sb + C_PI + 4096, ps + (3 - pol) * 4096, 4096, bars + B_PI * 8);
          mbar_arrive_z(bars + B_J * 8, 0);
        }
        __syncwarp();
      }
      c1 += gate_m;
      if (__builtin_expect(lds32(sb + C_INFO + ((st + 1) & 1) * 4), 0)) {
        late = rank == 2 ? 96 : 0;
        mbar_wait(bars + B_U * 8, nupd++ & 1, 78);
        const uint32_t c2 = lds32(sb + C_INFO + 40) + 1200;
        if ((int)(c2 - c1) > 0) c1 = c2;
      }
      mbar_expect_tx_z(bars + (B_M0 + lane) * 8, 8192, lane / 3);
      if (lane == 0) {
#pragma unroll
        for (int g = 0; g < 3; g++) {
          wait_clock(c1 + g * gate_g);
          bulk_g2s(sb + C_M + g * 8192, src + g * 16384, 8192, bars + (B_M0 + g) * 8);
          if (g == IGRP) mbar_arrive_z(bars + B_I * 8, 0);
        }
      }
      __syncwarp();
      TR(3)
    }
  }
}

struct ChainMaps { CUtensorMap w[3], wo; };
__global__ void __cluster_dims__(3, 1, 1) __launch_bounds__(512, 1)
chain_kernel(const __grid_constant__ ChainMaps maps, const bf16* __restrict__ mem0, const bf16* __restrict__ x0) {
  extern __shared__ __align__(1024) uint8_t smem_raw[];
  const uint32_t sb = (smem_u32(smem_raw) + 1023) & ~1023u;
  const int tid = threadIdx.x, lane = tid & 31;
  const int w = __shfl_sync(~0u, tid >> 5, 0);
  uint32_t rank;
  asm volatile("mov.u32 %0, %%cluster_ctarank;" : "=r"(rank));
  const int h = blockIdx.x / 3;
  asm volatile("griddepcontrol.launch_dependents;" ::: "memory");
  TG(0)
  const int row2 = 32 + blockIdx.x * 16 + w, row3 = 1568 + min(w, 4) * 96 + blockIdx.x;
  Row xr[4] = {load_row(x0 + row2 * DM, lane), load_row(x0 + row3 * DM, lane), load_row(x0 + w * DM, lane), load_row(x0 + (w + 16) * DM, lane)};
  if (tid == 0) {
    const uint32_t bars = sb + C_BAR;
    mbar_init(bars + B_M0 * 8, 1); mbar_init(bars + B_M1 * 8, 1); mbar_init(bars + B_M2 * 8, 1);
    mbar_init(bars + B_X * 8, 9); mbar_init(bars + B_O * 8, 2); mbar_init(bars + B_T * 8, 1); mbar_init(bars + B_F * 8, 2);
    mbar_init(bars + B_XL * 8, 2); mbar_init(bars + B_U * 8, 1);
    mbar_init(bars + B_P1 * 8, 8); mbar_init(bars + B_P2 * 8, 8); mbar_init(bars + B_OT * 8, 3); mbar_init(bars + B_XF * 8, 8); mbar_init(bars + B_XA * 8, 8); mbar_init(bars + B_I * 8, 1); mbar_init(bars + B_PI * 8, 1); mbar_init(bars + B_J * 8, 1);
    mbar_init(bars + B_W * 8, 1); mbar_init(bars + B_WO * 8, 1);
    asm volatile("fence.mbarrier_init.release.cluster;" ::: "memory");
    fence_async_smem();
    stage_weights(sb + C_STG, &maps.w[rank], h * 128, 0, bars + B_W * 8);
    const int nt = rank == 2 ? 2 : 3;
    mbar_expect_tx(bars + B_WO * 8, nt * 16384);
    for (int tl = 0; tl < nt; tl++)
      asm volatile("cp.async.bulk.tensor.5d.shared::cluster.global.mbarrier::complete_tx::bytes [%0], [%1, {%3, 0, 0, 0, %4}], [%2];"
                   ::"r"(sb + C_WO + tl * 16384), "l"(&maps.wo), "r"(bars + B_WO * 8), "r"((tl * 3 + rank) * 64), "r"(h * 4) : "memory");
  }
  __syncwarp();
  asm volatile("barrier.cluster.arrive.relaxed.aligned;" ::: "memory");
  {
    const int gt = blockIdx.x * 512 + tid, g1 = gt - 12288, g2 = gt - 12288 - 16384;
    static_assert(12288 + 16384 + sizeof(Flags) / 16 <= 96 * 512, "reset");
    if (g1 < 0) ((uint4*)g_M)[gt / 3072 * 4096 + 256 + gt % 3072] = make_uint4(~0u, ~0u, ~0u, ~0u);
    else if (g2 < 0) ((uint4*)(g_part[1] + 32 * 8192))[g1] = make_uint4(0, 0, 0, 0);
    else if (g2 < (int)(sizeof(Flags) / 16)) ((uint4*)&g_fl)[g2] = make_uint4(0, 0, 0, 0);
    if ((NSTEP - 1) & 1) { ((uint4*)g_P)[gt] = make_uint4(0, 0, 0, 0); ((uint4*)g_P)[gt + 49152] = make_uint4(0, 0, 0, 0); }
#pragma unroll 1
    for (int i = 0; i < 4; i++) {
      if (i != 1 || w < 5) {
        const int row = i == 0 ? row2 : i == 1 ? row3 : (i - 2) * 16 + w;
        store_row_img(i < 2 ? g_xs[0] + (row >> 5) * 32768 : smem_raw + (sb - smem_u32(smem_raw)) + C_X, row & 31, lane, warp_ln(xr[0]));
      }
      xr[0] = xr[1]; xr[1] = xr[2]; xr[2] = xr[3];
    }
  }
  fence_async_smem();
  __syncthreads();
  asm volatile("barrier.cluster.wait.aligned;" ::: "memory");
  if (tid == 448) red_release(g_ex.ready);
  __syncwarp();
  if (w < 8) {
    reg_inc<184>();
    chain_proj(sb, w, lane, rank);
    TG(1)
    TRDUMP
    cluster_sync();
  } else if (w < 12) {
    reg_dec<120>();
    chain_mem(sb, w, lane, rank, h, mem0);
    STATDUMP
    TRDUMP
    cluster_sync();
  } else {
    reg_dec<24>();
    chain_dma(sb, w, lane, rank, h);
    TRDUMP
    cluster_sync();
  }
}
#undef TRC
#undef TRS

constexpr int K_BAR = 0, K_LN = 128, K_FH = 320, K_FS = 512, K_FY = 1536;
constexpr int K_W = 3072;
constexpr int K_O = K_W + 3 * 49152;
constexpr int K_ST = K_O + 65536;
constexpr int K_SMEM = K_ST + 16384;
static_assert(K_SMEM <= 232448, "shared memory");
enum { KB_FULL = 0, KB_EMPTY = 2, KB_OK = 4, KB_GO = 7, KB_ST = 10, KB_REL = 12, KB_W = 13 };
enum { KN_ST = 1, KN_ST1, KN_REL, KN_FFN, KN_INIT, KN_RES, KN_RES1, KN_CAND, KN_TAKEN, KN_FF2 };
#define GATE_R 850
struct WorkerParams {
  CUtensorMap wo;
  const bf16 *x0, *w_r, *w_gate, *w_up, *w_down;
  bf16* out;
};
#define TRC (96 + blockIdx.x)
#define FT(e)
#define QUIET 4900
__device__ __forceinline__ void quiet_until(uint32_t t) {
  int d;
  while ((d = (int)(t - clk32())) > 0) warp_sleep(min(d / 3 + 20, 1000));
}
#define FOR_UNITS _Pragma("unroll 1") for (int st = 0, n = 0; st < WSTEP; st++) \
                  _Pragma("unroll 1") for (int v = st < NSEG ? 0 : st < WSTEP - 1 ? 1 : 2, sg = v ? st - WD : st; v < (st >= WD ? 3 : 1); v++, n++, sg = st - WD)

template <int ACC>
__device__ __forceinline__ void wg_ss8(float (&d)[4], uint64_t da, uint64_t db) {
  asm volatile("wgmma.mma_async.sync.aligned.m64n8k16.f32.bf16.bf16 {%0,%1,%2,%3}, %4, %5, %6, 1, 1, 1, 0;" : O4(d, 0) : "l"(da), "l"(db), "n"(ACC));
}
template <int NU>
__device__ __forceinline__ void ffn_slice(uint32_t sb, int t, const bf16* yrow, int ev) {
  const int lane = t & 31, c = t >> 5;
  FT(1)
  {
    const uint2 r = ld_rlx64(yrow + t * 4);
    asm volatile("st.shared.v2.b32 [%0], {%1,%2};" ::"r"(sb + K_FY + ((t >> 1) & 31) * 32 + (t >> 6) * 16 + (t & 1) * 8), "r"(r.x), "r"(r.y) : "memory");
  }
  fence_async_smem();
  bar_sync(KN_FFN, 128);
  FT(2)
  {
    float g[NU][4];
    const uint64_t da = mk_desc(sb + K_W, 16384, 512, 2), db = mk_desc(sb + K_FY, 32, 0, 0);
    wg_fence();
#pragma unroll
    for (int i = 0; i < 16; i++)
#pragma unroll
      for (int u = 0; u < NU; u++) { if (i == 0) wg_ss8<0>(g[u], da + u * 3072, db); else wg_ss8<1>(g[u], da + u * 3072 + i * 64, db + i * 4); }
    wg_commit();
    wg_wait<0>();
#pragma unroll
    for (int u = 0; u < NU; u++) {
      acc_fence(g[u]);
      if ((lane & 3) == 0) {
        const uint32_t a = sb + K_FS + u * 256 + c * 64 + lane;
        sts32(a, __float_as_uint(c < 2 ? g[u][0] : g[u][1])); sts32(a + 32, __float_as_uint(c < 2 ? g[u][2] : g[u][3]));
      }
    }
  }
  FT(3)
  bar_sync(KN_FFN, 128);
  {
    const uint32_t pa = sb + K_FS + c * 256 + lane * 4;
    const float gt = round_bf16(__uint_as_float(lds32(pa)) + __uint_as_float(lds32(pa + 128)));
    const float up = __shfl_xor_sync(~0u, gt, 16);
    const uint32_t hv = pack_bf16(round_bf16(__fdividef(gt, 1.f + __expf(-gt))) * up, 0.f);
    if (lane < 16) asm volatile("st.shared.b16 [%0], %1;" ::"r"(sb + K_FH + (c * 16 + lane) * 2), "h"((unsigned short)hv) : "memory");
  }
  fence_async_smem();
  bar_sync(KN_FFN, 128);
  FT(4)
#pragma unroll 1
  for (int hf = 0; hf < 2; hf++) {
    float o[4][4];
    const uint64_t da = mk_desc(sb + K_W + 32768 + hf * 8192, 16, 1024, 1), db = mk_desc(sb + K_FH, 16, 0, 0);
    wg_fence();
#pragma unroll
    for (int u = 0; u < NU; u++)
#pragma unroll
      for (int j = 0; j < 4; j++) { if (u == 0) wg_ss8<0>(o[j], da + j * 128, db); else wg_ss8<1>(o[j], da + u * 3072 + j * 128, db + u * 2); }
    wg_commit();
    wg_wait<0>();
    float lo = 0.f, hi = 0.f;
#pragma unroll
    for (int j = 0; j < 4; j++) {
      acc_fence(o[j]);
      const float a = __shfl_sync(~0u, o[j][0], lane & 28), b = __shfl_sync(~0u, o[j][2], lane & 28);
      if ((lane & 3) == j) { lo = a; hi = b; }
    }
    float* p = &g_fl.upd[ev][hf * 256 + (lane & 3) * 64 + c * 16 + (lane >> 2)];
    asm volatile("red.relaxed.gpu.global.add.f32 [%0], %1; red.relaxed.gpu.global.add.f32 [%0 + 32], %2;" ::"l"(p), "f"(lo), "f"(hi) : "memory");
  }
  FT(5)
  bar_sync(KN_FFN, 128);
  if (t == 96) red_release(g_fl.ffncnt[ev]);
  __syncwarp();
}
__device__ __forceinline__ uint4 pair_ln(uint4 r, float& e, uint32_t sl, int bar, int t) {
  const float x[8] = {bf_lo(r.x), bf_hi(r.x), bf_lo(r.y), bf_hi(r.y), bf_lo(r.z), bf_hi(r.z), bf_lo(r.w), bf_hi(r.w)};
  const float s = ((x[0] + x[1]) + (x[2] + x[3])) + ((x[4] + x[5]) + (x[6] + x[7]));
  const float q = (fmaf(x[0], x[0], x[1] * x[1]) + fmaf(x[2], x[2], x[3] * x[3])) + (fmaf(x[4], x[4], x[5] * x[5]) + fmaf(x[6], x[6], x[7] * x[7]));
  const bool u16 = t & 16, u8 = t & 8;
  const float a = (u16 ? q : s) + __shfl_xor_sync(~0u, u16 ? s : q, 16), b = e + __shfl_xor_sync(~0u, e, 16);
  float v = (u8 ? b : a) + __shfl_xor_sync(~0u, u8 ? a : b, 8);
  v += __shfl_xor_sync(~0u, v, 4); v += __shfl_xor_sync(~0u, v, 2); v += __shfl_xor_sync(~0u, v, 1);
  sts32(sl + (t >> 3) * 4, __float_as_uint(v));
  bar_sync(bar, 64);
  const uint4 s0 = lds128(sl), s1 = lds128(sl + 16);
  const float m = (__uint_as_float(s0.x) + __uint_as_float(s1.x)) * (1.f / DM), m2 = (__uint_as_float(s0.z) + __uint_as_float(s1.z)) * (1.f / DM);
  e = __uint_as_float(s0.y) + __uint_as_float(s1.y);
  float rs;
  asm("rsqrt.approx.ftz.f32 %0, %1;" : "=f"(rs) : "f"(fmaxf(fmaf(-m, m, m2), 0.f) + 1e-5f));
  return make_uint4(pack_bf16((x[0] - m) * rs, (x[1] - m) * rs), pack_bf16((x[2] - m) * rs, (x[3] - m) * rs),
                    pack_bf16((x[4] - m) * rs, (x[5] - m) * rs), pack_bf16((x[6] - m) * rs, (x[7] - m) * rs));
}
__device__ __forceinline__ uint32_t score_bits(float r) {
  const uint32_t b = pack_bf16(0.f, r);
  return (b & 0x80000000u) ? ~b : (b | 0x80000000u);
}

__global__ void __launch_bounds__(640, 1) worker_kernel(const __grid_constant__ WorkerParams prm) {
  extern __shared__ __align__(1024) uint8_t smem_raw[];
  const uint32_t sb = smem_u32(smem_raw);
  if (sb & 1023) __trap();
  const int tid = threadIdx.x, lane = tid & 31;
  const int w = __shfl_sync(~0u, tid >> 5, 0);
  const int me = blockIdx.x, kb = me >> 2, cb = me & 3;
  const bool full = me < 32;
  const uint32_t bars = sb + K_BAR;
  TG(0)
  if (tid == 0) {
    for (int i = 0; i < 2; i++) { mbar_init(bars + (KB_FULL + i) * 8, 1); mbar_init(bars + (KB_EMPTY + i) * 8, 1); }
    for (int i = 0; i < 10; i++) mbar_init(bars + (KB_OK + i) * 8, i < 3 ? 2 : 1);
    sts32(sb + K_LN + 144, 0);
    asm volatile("fence.mbarrier_init.release.cluster;" ::: "memory");
    fence_async_smem();
  }
  __syncwarp();
  if (w == 0) {
    wait_count(g_ex.ready, 96, 94);
    if (lane == 0 && full) stage_weights(sb + K_W, &prm.wo, cb * 128, kb * 512, bars + KB_W * 8);
  }
  __syncthreads();
  if (w < 8) {
    reg_inc<176>();
    if (full) {
      uint32_t wA[32][4];
      mbar_wait(bars + KB_W * 8, 0, 79);
      load_wfrags(wA, sb + K_W, w, lane);
      bar_arrive(KN_INIT, 384);
      const uint32_t sp = pin(sb + K_ST + ((lane >> 4) * 8 + (lane & 7)) * 256 + (((2 * w + ((lane >> 3) & 1)) ^ (lane & 7)) << 4));
      const uint32_t tm = pin(lane < 4 ? 0x00010001u : 0u);
      FOR_UNITS {
        float d[16];
        mbar_wait(bars + (KB_FULL + (n & 1)) * 8, (n >> 1) & 1, 81);
        TR(4 * v)
        const uint64_t db = mk_desc(sb + K_O + (n & 1) * 32768, 128, 2048, 0);
        wg_fence();
#pragma unroll
        for (int ks = 0; ks < 32; ks++) {
          if (ks == 0) wg_rs32<0, 0>(d, wA[ks], db);
          else wg_rs32<0, 1>(d, wA[ks], db + (ks >> 3) * 512 + (ks & 7) * 16);
        }
        wg_commit();
        mbar_wait(bars + (KB_ST + (n & 1)) * 8, ((n >> 1) & 1) ^ 1, 82);
        wg_wait<0>();
        acc_fence(d);
        TR(4 * v + 1)
        const uint32_t tag = (sg & 2) ? 0u : tm;
        uint32_t pk[8];
#pragma unroll
        for (int i = 0; i < 8; i++) pk[i] = (pack_bf16(d[2 * i], d[2 * i + 1]) & ~tm) | tag;
        stsm4t(sp + (n & 1) * 8192, pk[0], pk[1], pk[2], pk[3]);
        stsm4t(sp + (n & 1) * 8192 + 4096, pk[4], pk[5], pk[6], pk[7]);
        bar_arrive(KN_ST + (n & 1), 288);
        TR(4 * v + 2)
      }
    }
  } else if (w < 12) {
    reg_dec<56>();
    if (full) {
      const int ly = (w >> 1) & 1, t = pin(tid & 63);
      const uint32_t so = pin((t >> 4) * 8192 + me * 256 + (((t & 15) ^ (me & 7)) << 4));
      int sstar = -1;
      uint32_t sl = sb + K_LN + ly * 64;
      float rr = 0.f;
      int kprev = -1;
      auto records = [&](int sg, uint32_t off) {
        int it = 0;
        while (__any_sync(~0u, (int)lds32_poll(sb + K_LN + 144) <= sg)) { give_up(++it, SPIN_LIMIT, 86); warp_sleep(50); }
        return lds32_poll(sb + K_LN + off);
      };
#pragma unroll 1
      for (int n = ly ? 2 * WD : 0; n < 2 * WSTEP; n++) {
        const int st = n >> 1, v = (n & 1) ? 2 : ly, sg = v ? st - WD : st, tok = sg * 32 + me;
        if (n == 2 * NSEG) bar_sync(KN_INIT, 128);
        if (n == 2 * NSEG + 2) sstar = records(NSEG - 1, 156);
        if (v == 2 ? sg < 0 || (st < NSEG ? st & 1 : 0) != ly : sg >= NSEG - v) continue;
        const bf16* xin = v ? g_rows[tok][0][2] : prm.x0 + tok * DM;
        if (v == 2 && ((records(sg, 148 + (sg >> 5) * 4) >> (sg & 31)) & 1)) xin = g_x2p[sg][0];
        const uint8_t* src = g_part[v] + (sg & 1) * (32 * 8192) + so;
        const uint32_t flip = (sg & 2) ? ~0u : 0u;
        mbar_wait(bars + (KB_GO + v) * 8, sg & 1, 87);
        TR(4 * v)
        uint4 p[8], x;
        int it = 0;
#pragma unroll 1
        do {
#pragma unroll
          for (int k = 0; k < 8; k++) p[k] = ld_rlx128(src + k * 32768);
          x = ld_rlx128(((WEXP & 2) ? prm.x0 : xin) + t * 8);
          give_up(it++, SPIN_LIMIT, 85);
        } while (__builtin_expect(!__all_sync(~0u, (int)and3(and3(and_x(p[0].x, p[1].x, flip), and_x(p[2].x, p[3].x, flip), 1u),
                                                             and_x(p[4].x, p[5].x, flip), and_x(p[6].x, p[7].x, flip))), 0));
        mbar_arrive_z(bars + (KB_OK + v) * 8, t & 31);
#define P8(h, f) (((h(p[0].f) + h(p[1].f)) + (h(p[2].f) + h(p[3].f))) + ((h(p[4].f) + h(p[5].f)) + (h(p[6].f) + h(p[7].f))))
#define X8(f) x.f = add_bf16x2(x.f, pack_bf16(P8(bf_lo, f), P8(bf_hi, f)));
        X8(x) X8(y) X8(z) X8(w)
#undef X8
#undef P8
        TRV(12 + v, it - 1)
        TR(4 * v + 1)
        bf16* dst = g_rows[tok][v][0] + t * 8;
        *(uint4*)dst = x;
        const uint4 wr = ld_rlx128(prm.w_r + t * 8);
        sl ^= 32;
        uint4 y = pair_ln(x, rr, sl, KN_RES + ly, t);
        *(uint4*)(dst + DM) = y;
        x = make_uint4(add_bf16x2(x.x, y.x), add_bf16x2(x.y, y.y), add_bf16x2(x.z, y.z), add_bf16x2(x.w, y.w));
        *(uint4*)(v == (sg < sstar ? 1 : 2) ? prm.out + tok * DM + t * 8 : dst + 2 * DM) = x;
        asm volatile("{ .reg .pred p; setp.eq.u32 p, %2, 0; @p st.relaxed.gpu.global.u64 [%0], %1; }" ::"l"(&g_fl.key[0][0][0] + max(kprev, 0)),
                     "l"((u64)score_bits(rr) << 32 | (uint32_t)~(kprev & (NTOK - 1))), "r"(t | (kprev < 0)) : "memory");
        kprev = v * NTOK + tok;
        rr = (fmaf(bf_lo(y.x), bf_lo(wr.x), bf_hi(y.x) * bf_hi(wr.x)) + fmaf(bf_lo(y.y), bf_lo(wr.y), bf_hi(y.y) * bf_hi(wr.y))) +
             (fmaf(bf_lo(y.z), bf_lo(wr.z), bf_hi(y.z) * bf_hi(wr.z)) + fmaf(bf_lo(y.w), bf_lo(wr.w), bf_hi(y.w) * bf_hi(wr.w)));
        if (v == 0 || st >= NSEG) {
          sl ^= 32;
          y = pair_ln(x, rr, sl, KN_RES + ly, t);
          if (v == 0) *(uint4*)(g_xs[1] + sg * 32768 + (t >> 3) * 4096 + me * 128 + (((t ^ me) & 7) << 4)) = y;
          sts32(sb + K_LN + 128 + ly * 4, score_bits(rr));
          bar_arrive(KN_REL, v == 0 || st == WSTEP - 1 ? 96 : 160);
          kprev = -1;
        }
        TR(4 * v + 2)
      }
    }
  } else if (w < 16) {
    reg_dec<48>();
    const int t = tid - 384, nu = full ? 3 : 4;
    if (full) bar_sync(KN_INIT, 384);
    {
      const int j0 = (full ? me * 3 : 96 + (me - 32) * 4) * 16;
#pragma unroll 1
      for (int i = t; i < nu * 3072; i += 128) {
        const int u = i / 3072, r = i - u * 3072;
        const int q = (r ^ (r >> 3)) & 3, r2 = r - 2048;
        const bf16* src = r < 2048 ? ((q & 2) ? prm.w_up : prm.w_gate) + (size_t)(r >> 2) * FF + j0 + u * 16 + (q & 1) * 8
                                   : prm.w_down + (size_t)(j0 + u * 16 + ((r2 >> 3) & 15)) * DM + (r2 >> 7) * 64 + ((r2 ^ (r2 >> 3)) & 7) * 8;
        cp16(sb + K_W + i * 16, src);
      }
      asm volatile("cp.async.wait_all;" ::: "memory");
    }
    bar_arrive(KN_TAKEN, 160);
#pragma unroll 1
    while (true) {
      bar_sync(KN_CAND, 160);
      const uint4 cand = lds128(sb + K_LN + 160);
      const u64 k = (u64)cand.y << 32 | cand.x;
      const int ev = cand.z, ver = cand.w & 3, tok = key_token(k);
      const bool last = cand.w & 4;
      if (!last) {
        bar_arrive(KN_TAKEN, 160);
        FT(0)
        if (full) ffn_slice<3>(sb, t, g_rows[tok][ver][1], ev); else ffn_slice<4>(sb, t, g_rows[tok][ver][1], ev);
      }
      if ((tok & 31) == me && (ver == 0 || last)) {
        if (t < 64) {
          FT(6)
          uint4 x = ld_rlx128(g_rows[tok][ver][0] + t * 8);
          const uint4 y = ld_rlx128(g_rows[tok][ver][1] + t * 8);
          const float sig = round_bf16(__fdividef(1.f, 1.f + __expf(-key_score(k))));
          int it = 0;
          while (ld_rlx32(g_fl.ffncnt[ev]) < NWORK) { give_up(++it, SPIN_LIMIT, 80); warp_sleep(40); }
          const uint4 u0 = ld_rlx128(&g_fl.upd[ev][t * 8]), u1 = ld_rlx128(&g_fl.upd[ev][t * 8 + 4]);
          auto upd = [&](uint32_t xw, uint32_t yw, uint32_t a, uint32_t b) {
            const uint32_t r = pack_bf16(__uint_as_float(a), __uint_as_float(b));
            return add_bf16x2(xw, add_bf16x2(yw, pack_bf16(bf_lo(r) * sig, bf_hi(r) * sig)));
          };
          x = make_uint4(upd(x.x, y.x, u0.x, u0.y), upd(x.y, y.y, u0.z, u0.w), upd(x.z, y.z, u1.x, u1.y), upd(x.w, y.w, u1.z, u1.w));
          FT(7)
          *(uint4*)((ver ? prm.out + tok * DM : g_x2p[ev][0]) + t * 8) = x;
          if (ver == 0) {
            float e = 0.f;
            *(uint4*)(g_x2p[ev][1] + t * 8) = pair_ln(x, e, sb + K_FS, KN_FF2, t);
            bar_sync(KN_FF2, 64);
            if (t == 0) st_release32(g_fl.patch[ev], 1);
            __syncwarp();
          }
        }
      }
      if (ev == NSEG && !last && full) {
        const int nc = min((int)lds32(sb + K_LN + 156), NSEG + 1 - WD);
#pragma unroll 1
        for (int s0 = (t >> 6) * 4; s0 < nc; s0 += 8) {
          uint4 q[4];
#pragma unroll
          for (int i = 0; i < 4; i++) q[i] = ld_rlx128(g_rows[min(s0 + i, nc - 1) * 32 + me][1][2] + (t & 63) * 8);
#pragma unroll
          for (int i = 0; i < 4; i++) *(uint4*)(prm.out + (min(s0 + i, nc - 1) * 32 + me) * DM + (t & 63) * 8) = q[i];
        }
      }
      FT(8)
      if (last) break;
    }
  } else {
    reg_dec<24>();
    if (w == 16) {
      u64 best = 0, mask = 0;
      int sstar = 0;
      uint32_t ver = 0, ev = 0;
      auto post = [&](uint32_t cmd) {
        bar_sync(KN_TAKEN, 160);
        sts128(sb + K_LN + 160, make_uint4((uint32_t)best, (uint32_t)(best >> 32), ev, ver | cmd));
        bar_arrive(KN_CAND, 160);
      };
      u64 accn = 0, acca = 0;
      uint32_t recs = 0;
      int j = 0;
      uint32_t tq = clk32();
#pragma unroll 1
      for (int st = 0; st < WSTEP; st++) {
        const u64* keys = st < NSEG ? g_fl.key[0][st] : g_fl.key[2][st - WD];
        const bool early = __any_sync(~0u, ld_rlx32(keys + lane) == 0);
        if (early && st < NSEG) quiet_until(tq);
        u64 k = wait_keys(keys, lane, 91);
        if (early) tq = clk32() + QUIET;
        if (st < NSEG) {
          const bool rec = k > best;
          recs &= ~(1u << (st & 31));
          if (rec) {
            best = k; ev = sstar = st;
            recs |= 1u << (st & 31);
            if ((key_token(k) & 31) == me) mask |= 1ull << st;
          }
          if (lane == 0) sts128(sb + K_LN + 144, make_uint4(st + 1, (uint32_t)mask, (uint32_t)(mask >> 32), sstar));
          __syncwarp();
          if (rec) post(0);
        }
#pragma unroll 1
        for (; j <= st - WD - (st < NSEG ? 2 : 0); j++) {
          u64 kn = 1, kc;
          int it = 0;
          do {
            if (j < NSEG - 1) asm volatile("ld.relaxed.gpu.global.u64 %0, [%1];" : "=l"(kn) : "l"(&g_fl.key[1][j][lane]) : "memory");
            asm volatile("ld.relaxed.gpu.global.u64 %0, [%1];" : "=l"(kc) : "l"(&g_fl.key[2][j][lane]) : "memory");
            give_up(it++, SPIN_LIMIT, 92);
          } while (__any_sync(~0u, kn == 0 || kc == 0));
          if ((recs >> (j & 31)) & 1) acca = accn;
          if (kc > acca) acca = kc;
          if (kn > accn) accn = kn;
        }
        if (st >= NSEG) {
          const u64 m = j <= sstar ? accn : acca;
          const uint32_t hi = __reduce_max_sync(~0u, (uint32_t)(m >> 32));
          k = (u64)hi << 32 | __reduce_max_sync(~0u, (uint32_t)(m >> 32) == hi ? (uint32_t)m : 0u);
          if (st == NSEG || k != best) {
            best = k; ev = st;
            ver = (key_token(k) >> 5) < sstar ? 1 : 2;
            post(0);
          }
        }
      }
      HD(6)
      post(4);
      if (me == 0 && lane == 0) st_rlx32(g_ex.ready, 0);
    } else if (!full) {
    } else if (w == 17) {
      uint32_t tq = clk32();
      FOR_UNITS {
        if (ld_rlx32(&g_fl.oflag[v][sg][kb]) < 4) {
          if (v == (st < NSEG ? 0 : 1) && st < WSTEP - 3) quiet_until(tq);
          wait_count(&g_fl.oflag[v][sg][kb], 4, 84);
          if (v == (st < NSEG ? 0 : 1)) tq = clk32() + QUIET;
        }
        mbar_wait(bars + (KB_EMPTY + (n & 1)) * 8, ((n >> 1) & 1) ^ 1, 83);
        TR(v)
        if (st == WSTEP - 1) { HD(v) }
        if (lane == 0) {
          fence_async_glb();
          mbar_expect_tx(bars + (KB_FULL + (n & 1)) * 8, (WEXP & 4) ? 4096 : 32768);
          bulk_g2s(sb + K_O + (n & 1) * 32768, g_O[(v ? sg + DELTA : sg) & (OSLOTS - 1)][v] + kb * 32768, (WEXP & 4) ? 4096 : 32768, bars + (KB_FULL + (n & 1)) * 8);
        }
        __syncwarp();
      }
    } else if (w == 18) {
      FOR_UNITS {
        if (sg > 0) mbar_wait(bars + (KB_OK + v) * 8, (sg - 1) & 1, 90);
        bar_sync(KN_ST + (n & 1), 288);
        fence_async_smem();
        const uint32_t tg = clk32() + GATE_R;
        if (lane == 0) {
          bulk_s2g(g_part[v] + ((sg & 1) * 32 + me) * 8192, sb + K_ST + (n & 1) * 8192, 8192);
          asm volatile("cp.async.bulk.commit_group;" ::: "memory");
          mbar_arrive_z(bars + (KB_EMPTY + (n & 1)) * 8, 0);
          asm volatile("cp.async.bulk.wait_group.read 0;" ::: "memory");
        }
        __syncwarp();
        mbar_arrive_z(bars + (KB_ST + (n & 1)) * 8, lane);
        TR(v)
        if (v == (st < NSEG ? 0 : st < WSTEP - 1 ? 1 : 2) && st > 0) mbar_wait(bars + KB_REL * 8, (st - 1) & 1, 93);
        wait_clock(tg);
        if (st == WSTEP - 1) { HD(2 + v) }
        mbar_arrive_z(bars + (KB_GO + v) * 8, lane);
      }
    } else {
#pragma unroll 1
      for (int st = 0; st < WSTEP; st++) {
        const int sg = st < NSEG ? st : st - WD;
        const bool both = st >= NSEG && st < WSTEP - 1;
        bar_sync(KN_REL, both ? 160 : 96);
        const uint32_t ob = __shfl_sync(~0u, lds32(sb + K_LN + 128), 0), obn = __shfl_sync(~0u, lds32(sb + K_LN + 132), 0);
        mbar_arrive_z(bars + KB_REL * 8, lane);
        if (st == WSTEP - 1) { HD(5) }
        if (lane == 0) {
          if (both) asm volatile("st.relaxed.gpu.global.u64 [%0], %1;" ::"l"(&g_fl.key[1][sg][me]), "l"((u64)obn << 32 | (uint32_t)~(sg * 32 + me)) : "memory");
          st_release_u64(&g_fl.key[st < NSEG ? 0 : 2][sg][me], (u64)ob << 32 | (uint32_t)~(sg * 32 + me));
        }
        __syncwarp();
        TR(0)
      }
    }
  }
}
#undef TRC

typedef CUresult (*EncodeFn)(CUtensorMap*, CUtensorMapDataType, cuuint32_t, void*, const cuuint64_t*, const cuuint64_t*,
                             const cuuint32_t*, const cuuint32_t*, CUtensorMapInterleave, CUtensorMapSwizzle,
                             CUtensorMapL2promotion, CUtensorMapFloatOOBfill);
void make_map(EncodeFn fn, CUtensorMap* m, const void* ptr, int rank, const cuuint64_t* dims, const cuuint64_t* strides, const cuuint32_t* box) {
  const cuuint32_t es[5] = {1, 1, 1, 1, 1};
  fn(m, CU_TENSOR_MAP_DATA_TYPE_BFLOAT16, rank, (void*)ptr, dims, strides, box, es, CU_TENSOR_MAP_INTERLEAVE_NONE,
     CU_TENSOR_MAP_SWIZZLE_128B, CU_TENSOR_MAP_L2_PROMOTION_L2_256B, CU_TENSOR_MAP_FLOAT_OOB_FILL_NONE);
}
struct HostState {
  const void* key[4];
  ChainMaps cm;
  CUtensorMap wo;
};
HostState g_hs;

}

extern "C" void kernel_launch(void* const* d_in, const int* in_sizes, int n_in, void* d_out, int out_size) {
  (void)in_sizes; (void)n_in; (void)out_size;
  HostState& hs = g_hs;
  if (hs.key[0] != d_in[2] || hs.key[1] != d_in[3] || hs.key[2] != d_in[4] || hs.key[3] != d_in[5]) {
    void* fnp = nullptr;
    cudaDriverEntryPointQueryResult qr;
    cudaGetDriverEntryPoint("cuTensorMapEncodeTiled", &fnp, cudaEnableDefault, &qr);
    const cuuint32_t box[2] = {64, 256}, box5[5] = {64, 2, 4, 4, 4};
    const cuuint64_t dw[2] = {HD, DM}, sw[1] = {HD * 2}, dwo[2] = {DM, HD}, swo[1] = {DM * 2};
    const cuuint64_t d5[5] = {DM, 2, 4, 4, HD / 32}, s5[4] = {DM * 2, 8 * DM * 2, 2 * DM * 2, 32 * DM * 2};
    for (int i = 0; i < 3; i++) make_map((EncodeFn)fnp, &hs.cm.w[i], d_in[2 + i], 2, dw, sw, box);
    make_map((EncodeFn)fnp, &hs.cm.wo, d_in[5], 5, d5, s5, box5);
    make_map((EncodeFn)fnp, &hs.wo, d_in[5], 2, dwo, swo, box);
    cudaFuncSetAttribute(worker_kernel, cudaFuncAttributeMaxDynamicSharedMemorySize, K_SMEM);
    cudaFuncSetAttribute(chain_kernel, cudaFuncAttributeMaxDynamicSharedMemorySize, C_SMEM);
    for (int i = 0; i < 4; i++) hs.key[i] = d_in[2 + i];
  }
  cudaStream_t st = cudaStreamPerThread;
  WorkerParams wp;
  wp.wo = hs.wo; wp.x0 = (const bf16*)d_in[0]; wp.w_r = (const bf16*)d_in[8]; wp.w_gate = (const bf16*)d_in[9];
  wp.w_up = (const bf16*)d_in[10]; wp.w_down = (const bf16*)d_in[11]; wp.out = (bf16*)d_out;
  chain_kernel<<<96, 512, C_SMEM, st>>>(hs.cm, (const bf16*)d_in[1], wp.x0);
  cudaLaunchAttribute pdl[1];
  pdl[0].id = cudaLaunchAttributeProgrammaticStreamSerialization;
  pdl[0].val.programmaticStreamSerializationAllowed = 1;
  cudaLaunchConfig_t cfg = {};
  cfg.gridDim = dim3(NWORK); cfg.blockDim = dim3(640); cfg.dynamicSmemBytes = K_SMEM; cfg.stream = st;
  cfg.attrs = pdl; cfg.numAttrs = 1;
  cudaLaunchKernelEx(&cfg, worker_kernel, wp);
}
```

```cpp
#include <cuda_runtime.h>
#include <cuda_bf16.h>
#include <cuda.h>
#include <stdint.h>

namespace {

typedef __nv_bfloat16 bf16;
typedef unsigned long long u64;

constexpr int NTOK = 2048, DM = 512, HD = 4096, NSEG = 64, FF = 1792;
#define DELTA 5
constexpr int NSTEP = NSEG + DELTA;
#define WLAG 1
constexpr int WD = DELTA + WLAG, WSTEP = NSEG + WD;
constexpr int SPIN_LIMIT = 40000;
constexpr int MBAR_LIMIT = 20000;
constexpr int NWORK = 36;
constexpr int OSLOTS = 8;
#define SLP_C 100
#define SLP_K 200
#define WEXP 0

__device__ __align__(1024) uint8_t g_xs[2][NSEG * 32768];
__device__ __align__(1024) uint8_t g_O[OSLOTS][3][32 * 8192];
__device__ __align__(1024) uint8_t g_part[3][2 * 32 * 8192];
__device__ __align__(1024) bf16 g_rows[NTOK][3][3][DM];
__device__ __align__(1024) bf16 g_x2p[NSEG][2][DM];
struct Flags {
  uint32_t pol[96];
  uint32_t stamp[96];
  uint32_t oflag[3][NSEG][8];
  uint32_t ffncnt[WSTEP][8];
  u64 key[3][NSEG][32];
  float upd[WSTEP][DM];
};
struct Exchange { uint32_t M[4 * 16384], P[96 * 4096]; Flags fl; uint32_t ready[32]; };
__device__ __align__(65536) Exchange g_ex;
#define g_M g_ex.M
#define g_P g_ex.P
#define g_fl g_ex.fl
#define TR(e)
#define TRV(e, v)
#define TG(i)
#define HD(e)
#define TRDUMP
#define TREXTRA 0

#define STAT(e, v)
#define STATC(n)
#define STATDUMP
__device__ __forceinline__ uint32_t smem_u32(const void* p) { return (uint32_t)__cvta_generic_to_shared(p); }
__device__ __forceinline__ uint32_t pack_bf16(float lo, float hi) {
  uint32_t r;
  asm("cvt.rn.bf16x2.f32 %0, %1, %2;" : "=r"(r) : "f"(hi), "f"(lo));
  return r;
}
__device__ __forceinline__ float bf_lo(uint32_t v) { return __uint_as_float(v << 16); }
__device__ __forceinline__ float bf_hi(uint32_t v) { return __uint_as_float(v & 0xffff0000u); }
__device__ __forceinline__ float ex2_fast(float x) { float y; asm("ex2.approx.ftz.f32 %0, %1;" : "=f"(y) : "f"(x)); return y; }
__device__ __forceinline__ float round_bf16(float x) { return __bfloat162float(__float2bfloat16_rn(x)); }
__device__ __forceinline__ uint32_t clk32() { uint32_t t; asm volatile("mov.u32 %0, %%clock;" : "=r"(t) :: "memory"); return t; }

__device__ __forceinline__ void mma16816(float (&d)[4], uint32_t a0, uint32_t a1, uint32_t a2, uint32_t a3,
                                         uint32_t b0, uint32_t b1) {
  asm("mma.sync.aligned.m16n8k16.row.col.f32.bf16.bf16.f32 {%0,%1,%2,%3}, {%4,%5,%6,%7}, {%8,%9}, {%0,%1,%2,%3};"
      : "+f"(d[0]), "+f"(d[1]), "+f"(d[2]), "+f"(d[3])
      : "r"(a0), "r"(a1), "r"(a2), "r"(a3), "r"(b0), "r"(b1));
}
__device__ __forceinline__ void ldsm4t(uint32_t (&r)[4], uint32_t addr) {
  asm volatile("ldmatrix.sync.aligned.m8n8.x4.trans.shared.b16 {%0,%1,%2,%3}, [%4];"
               : "=r"(r[0]), "=r"(r[1]), "=r"(r[2]), "=r"(r[3]) : "r"(addr) : "memory");
}
__device__ __forceinline__ void stsm4(uint32_t addr, uint32_t a, uint32_t b, uint32_t c, uint32_t d) {
  asm volatile("stmatrix.sync.aligned.m8n8.x4.shared.b16 [%0], {%1,%2,%3,%4};" ::"r"(addr), "r"(a), "r"(b), "r"(c), "r"(d) : "memory");
}
__device__ __forceinline__ void stsm4t(uint32_t addr, uint32_t a, uint32_t b, uint32_t c, uint32_t d) {
  asm volatile("stmatrix.sync.aligned.m8n8.x4.trans.shared.b16 [%0], {%1,%2,%3,%4};" ::"r"(addr), "r"(a), "r"(b), "r"(c), "r"(d) : "memory");
}
__device__ __forceinline__ uint4 lds128(uint32_t a) {
  uint4 v; asm volatile("ld.shared.v4.b32 {%0,%1,%2,%3}, [%4];" : "=r"(v.x), "=r"(v.y), "=r"(v.z), "=r"(v.w) : "r"(a) : "memory"); return v;
}
__device__ __forceinline__ uint32_t lds32(uint32_t a) { uint32_t v; asm volatile("ld.shared.b32 %0, [%1];" : "=r"(v) : "r"(a) : "memory"); return v; }
__device__ __forceinline__ uint32_t lds32_poll(uint32_t a) { uint32_t v; asm volatile("ld.volatile.shared.b32 %0, [%1];" : "=r"(v) : "r"(a) : "memory"); return v; }
__device__ __forceinline__ void sts32(uint32_t a, uint32_t x) { asm volatile("st.shared.b32 [%0], %1;" ::"r"(a), "r"(x) : "memory"); }
__device__ __forceinline__ void sts128(uint32_t a, uint4 v) {
  asm volatile("st.shared.v4.b32 [%0], {%1,%2,%3,%4};" ::"r"(a), "r"(v.x), "r"(v.y), "r"(v.z), "r"(v.w) : "memory");
}
__device__ __forceinline__ void cp16(uint32_t dst, const void* src) {
  asm volatile("cp.async.cg.shared.global [%0], [%1], 16;" ::"r"(dst), "l"(src) : "memory");
}
__device__ __forceinline__ void mbar_init(uint32_t mbar, uint32_t cnt) {
  asm volatile("mbarrier.init.shared.b64 [%0], %1;" ::"r"(mbar), "r"(cnt) : "memory");
}
__device__ __forceinline__ void mbar_expect_tx(uint32_t mbar, uint32_t bytes) {
  asm volatile("mbarrier.arrive.expect_tx.shared.b64 _, [%0], %1;" ::"r"(mbar), "r"(bytes) : "memory");
}
__device__ __forceinline__ void mbar_arrive_z(uint32_t mbar, uint32_t z) {
  asm volatile("{ .reg .pred p; setp.eq.u32 p, %1, 0; @p mbarrier.arrive.shared.b64 _, [%0]; }" ::"r"(mbar), "r"(z) : "memory");
}
__device__ __forceinline__ void mbar_expect_tx_z(uint32_t mbar, uint32_t bytes, uint32_t z) {
  asm volatile("{ .reg .pred p; setp.eq.u32 p, %2, 0; @p mbarrier.arrive.expect_tx.shared.b64 _, [%0], %1; }" ::"r"(mbar), "r"(bytes), "r"(z) : "memory");
}
__device__ __forceinline__ void mbar_arrive_remote_z(uint32_t mbar, uint32_t z) {
  asm volatile("{ .reg .pred p; setp.eq.u32 p, %1, 0; @p mbarrier.arrive.shared::cluster.b64 _, [%0]; }" ::"r"(mbar), "r"(z) : "memory");
}
__device__ __forceinline__ void warp_sleep(uint32_t ns) { __nanosleep(ns); __syncwarp(); }
__device__ __forceinline__ void fail(int) { __trap(); }
__device__ __forceinline__ void give_up(int it, int limit, int code) { if (it > limit) fail(code); }
__device__ __forceinline__ void mbar_wait(uint32_t mbar, uint32_t par, int code) {
  asm volatile("{ .reg .pred p; .reg .b32 n; mov.b32 n, %2;\n"
               "W: mbarrier.try_wait.parity.shared::cta.b64 p, [%0], %1; @p bra D;\n"
               "add.s32 n, n, -1; setp.eq.s32 p, n, 0; @p trap; bra W;\n"
               "D: }" ::"r"(mbar), "r"(par), "n"(MBAR_LIMIT) : "memory");
}
__device__ __forceinline__ void bulk_g2s(uint32_t dst, const void* src, uint32_t bytes, uint32_t mbar) {
  asm volatile("cp.async.bulk.shared::cluster.global.mbarrier::complete_tx::bytes [%0], [%1], %2, [%3];"
               ::"r"(dst), "l"(src), "r"(bytes), "r"(mbar) : "memory");
}
__device__ __forceinline__ void bulk_s2r(uint32_t dst, uint32_t src, uint32_t bytes, uint32_t mbar) {
  asm volatile("cp.async.bulk.shared::cluster.shared::cta.mbarrier::complete_tx::bytes [%0], [%1], %2, [%3];"
               ::"r"(dst), "r"(src), "r"(bytes), "r"(mbar) : "memory");
}
__device__ __forceinline__ void bulk_s2g(void* dst, uint32_t src, uint32_t bytes) {
  asm volatile("cp.async.bulk.global.shared::cta.bulk_group [%0], [%1], %2;" ::"l"(dst), "r"(src), "r"(bytes) : "memory");
}
__device__ __forceinline__ void fence_async_smem() { asm volatile("fence.proxy.async.shared::cta;" ::: "memory"); }
__device__ __forceinline__ void fence_async_glb() { asm volatile("fence.proxy.async.global;" ::: "memory"); }
__device__ __forceinline__ void bar_sync(int id, int n) { asm volatile("bar.sync %0, %1;" ::"r"(id), "r"(n) : "memory"); }
__device__ __forceinline__ void bar_arrive(int id, int n) { asm volatile("bar.arrive %0, %1;" ::"r"(id), "r"(n) : "memory"); }
__device__ __forceinline__ void cluster_sync() { asm volatile("barrier.cluster.arrive.release; barrier.cluster.wait.acquire;" ::: "memory"); }
__device__ __forceinline__ uint32_t mapa_u32(uint32_t a, uint32_t r) {
  uint32_t o;
  asm("mapa.shared::cluster.u32 %0, %1, %2;" : "=r"(o) : "r"(a), "r"(r));
  return o;
}
template <int OFF>
__device__ __forceinline__ void st_async32(uint32_t a, uint32_t x, uint32_t mbar) {
  asm volatile("st.async.weak.shared::cluster.mbarrier::complete_tx::bytes.b32 [%0 + %3], %1, [%2];" ::"r"(a), "r"(x), "r"(mbar), "n"(OFF) : "memory");
}
__device__ __forceinline__ uint4 ld_rlx128(const void* p) {
  uint4 v;
  asm volatile("ld.relaxed.gpu.global.v4.u32 {%0,%1,%2,%3}, [%4];" : "=r"(v.x), "=r"(v.y), "=r"(v.z), "=r"(v.w) : "l"(p) : "memory");
  return v;
}
__device__ __forceinline__ uint2 ld_rlx64(const void* p) {
  uint2 v; asm volatile("ld.relaxed.gpu.global.v2.u32 {%0,%1}, [%2];" : "=r"(v.x), "=r"(v.y) : "l"(p) : "memory"); return v;
}
__device__ __forceinline__ uint32_t ld_rlx32(const void* p) {
  uint32_t v; asm volatile("ld.relaxed.gpu.global.u32 %0, [%1];" : "=r"(v) : "l"(p) : "memory"); return v;
}
__device__ __forceinline__ void st_rlx32(void* p, uint32_t a) { asm volatile("st.relaxed.gpu.global.u32 [%0], %1;" ::"l"(p), "r"(a) : "memory"); }
__device__ __forceinline__ void red_release(uint32_t* p) { asm volatile("red.release.gpu.global.add.u32 [%0], 1;" ::"l"(p) : "memory"); }
__device__ __forceinline__ void st_release_u64(void* p, u64 a) { asm volatile("st.release.gpu.global.u64 [%0], %1;" ::"l"(p), "l"(a) : "memory"); }
__device__ __forceinline__ void wait_count(const uint32_t* p, uint32_t val, int code) {
  int it = 0;
  while (ld_rlx32(p) < val) {
    give_up(++it, SPIN_LIMIT, code);
    warp_sleep(SLP_C);
  }
}
__device__ __forceinline__ u64 wait_keys(const u64* keys, int lane, int code) {
  u64 k;
  int it = 0;
  while (true) {
    asm volatile("ld.relaxed.gpu.global.u64 %0, [%1];" : "=l"(k) : "l"(keys + lane) : "memory");
    if (__all_sync(~0u, k != 0)) break;
    give_up(++it, SPIN_LIMIT, code);
    warp_sleep(SLP_K);
  }
  const uint32_t hi = __reduce_max_sync(~0u, (uint32_t)(k >> 32));
  const uint32_t lo = __reduce_max_sync(~0u, (uint32_t)(k >> 32) == hi ? (uint32_t)k : 0u);
  return (u64)hi << 32 | lo;
}
__device__ __forceinline__ int key_token(u64 k) { return (int)(~(uint32_t)k) & (NTOK - 1); }
__device__ __forceinline__ float key_score(u64 k) {
  const uint32_t ob = (uint32_t)(k >> 32);
  return __uint_as_float((ob & 0x80000000u) ? (ob & 0x7fffffffu) : ~ob);
}

__device__ __forceinline__ uint64_t mk_desc(uint32_t saddr, uint32_t lbo, uint32_t sbo, uint32_t sw) {
  return (uint64_t)((saddr & 0x3FFFF) >> 4) | (uint64_t)(lbo >> 4) << 16 | (uint64_t)(sbo >> 4) << 32 | (uint64_t)sw << 62;
}
template <int N> __device__ __forceinline__ void reg_inc() { asm volatile("setmaxnreg.inc.sync.aligned.u32 %0;" ::"n"(N)); }
template <int N> __device__ __forceinline__ void reg_dec() { asm volatile("setmaxnreg.dec.sync.aligned.u32 %0;" ::"n"(N)); }
__device__ __forceinline__ void wg_fence() { asm volatile("wgmma.fence.sync.aligned;" ::: "memory"); }
__device__ __forceinline__ void wg_commit() { asm volatile("wgmma.commit_group.sync.aligned;" ::: "memory"); }
template <int N> __device__ __forceinline__ void wg_wait() { asm volatile("wgmma.wait_group.sync.aligned %0;" ::"n"(N) : "memory"); }
template <int N> __device__ __forceinline__ void acc_fence(float (&d)[N]) {
#pragma unroll
  for (int i = 0; i < N; i++) asm volatile("" : "+f"(d[i]) :: "memory");
}
#define O4(d, i) "+f"(d[i]), "+f"(d[i + 1]), "+f"(d[i + 2]), "+f"(d[i + 3])
template <int TB, int ACC>
__device__ __forceinline__ void wg_rs24(float (&d)[12], const uint32_t (&a)[4], uint64_t db) {
  asm volatile("wgmma.mma_async.sync.aligned.m64n24k16.f32.bf16.bf16 {%0,%1,%2,%3,%4,%5,%6,%7,%8,%9,%10,%11}, {%12,%13,%14,%15}, %16, %17, 1, 1, %18;"
               : O4(d, 0), O4(d, 4), O4(d, 8) : "r"(a[0]), "r"(a[1]), "r"(a[2]), "r"(a[3]), "l"(db), "n"(ACC), "n"(TB));
}
template <int TB, int ACC>
__device__ __forceinline__ void wg_rs32(float (&d)[16], const uint32_t (&a)[4], uint64_t db) {
  asm volatile("wgmma.mma_async.sync.aligned.m64n32k16.f32.bf16.bf16 {%0,%1,%2,%3,%4,%5,%6,%7,%8,%9,%10,%11,%12,%13,%14,%15}, {%16,%17,%18,%19}, %20, %21, 1, 1, %22;"
               : O4(d, 0), O4(d, 4), O4(d, 8), O4(d, 12) : "r"(a[0]), "r"(a[1]), "r"(a[2]), "r"(a[3]), "l"(db), "n"(ACC), "n"(TB));
}
template <int ACC>
__device__ __forceinline__ void wg_rs64(float (&d)[32], uint32_t a0, uint32_t a1, uint32_t a2, uint32_t a3, uint64_t db) {
  asm volatile("wgmma.mma_async.sync.aligned.m64n64k16.f32.bf16.bf16 {%0,%1,%2,%3,%4,%5,%6,%7,%8,%9,%10,%11,%12,%13,%14,%15,"
               "%16,%17,%18,%19,%20,%21,%22,%23,%24,%25,%26,%27,%28,%29,%30,%31}, {%32,%33,%34,%35}, %36, %37, 1, 1, 0;"
               : O4(d, 0), O4(d, 4), O4(d, 8), O4(d, 12), O4(d, 16), O4(d, 20), O4(d, 24), O4(d, 28)
               : "r"(a0), "r"(a1), "r"(a2), "r"(a3), "l"(db), "n"(ACC));
}
template <int ACC>
__device__ __forceinline__ void wg_ss24(float (&d)[12], uint64_t da, uint64_t db) {
  asm volatile("wgmma.mma_async.sync.aligned.m64n24k16.f32.bf16.bf16 {%0,%1,%2,%3,%4,%5,%6,%7,%8,%9,%10,%11}, %12, %13, %14, 1, 1, 1, 0;"
               : O4(d, 0), O4(d, 4), O4(d, 8) : "l"(da), "l"(db), "n"(ACC));
}
template <int ACC>
__device__ __forceinline__ void wg_rs40(float (&d)[20], const uint32_t (&a)[4], uint64_t db) {
  asm volatile("wgmma.mma_async.sync.aligned.m64n40k16.f32.bf16.bf16 {%0,%1,%2,%3,%4,%5,%6,%7,%8,%9,%10,%11,%12,%13,%14,%15,%16,%17,%18,%19}, {%20,%21,%22,%23}, %24, %25, 1, 1, 1;"
               : O4(d, 0), O4(d, 4), O4(d, 8), O4(d, 12), O4(d, 16) : "r"(a[0]), "r"(a[1]), "r"(a[2]), "r"(a[3]), "l"(db), "n"(ACC));
}

struct Row { uint32_t w[8]; };
__device__ __forceinline__ uint32_t add_bf16x2(uint32_t a, uint32_t b) {
  uint32_t d; asm("add.rn.bf16x2 %0, %1, %2;" : "=r"(d) : "r"(a), "r"(b)); return d;
}
__device__ __forceinline__ Row warp_ln(const Row& r, float& extra) {
  float x[16];
#pragma unroll
  for (int i = 0; i < 8; i++) { x[2 * i] = bf_lo(r.w[i]); x[2 * i + 1] = bf_hi(r.w[i]); }
  float m = (((x[0] + x[1]) + (x[2] + x[3])) + ((x[4] + x[5]) + (x[6] + x[7]))) + (((x[8] + x[9]) + (x[10] + x[11])) + ((x[12] + x[13]) + (x[14] + x[15])));
  m *= (1.f / 16);
  float v0 = 0.f, v1 = 0.f;
#pragma unroll
  for (int i = 0; i < 16; i += 2) { const float d0 = x[i] - m, d1 = x[i + 1] - m; v0 = fmaf(d0, d0, v0); v1 = fmaf(d1, d1, v1); }
  float v = v0 + v1;
#pragma unroll
  for (int o = 1; o <= 16; o <<= 1) {
    const float mo = __shfl_xor_sync(~0u, m, o), vo = __shfl_xor_sync(~0u, v, o);
    extra += __shfl_xor_sync(~0u, extra, o);
    const float d = mo - m;
    v = fmaf(d * d, 8.f * o, v + vo);
    m = 0.5f * (m + mo);
  }
  const float var = fmaf(v, 1.f / DM, 1e-5f);
  float rs = rsqrtf(var);
  rs = rs * fmaf(-0.5f * var * rs, rs, 1.5f);
  Row y;
#pragma unroll
  for (int i = 0; i < 8; i++) y.w[i] = pack_bf16((x[2 * i] - m) * rs, (x[2 * i + 1] - m) * rs);
  return y;
}
__device__ __forceinline__ Row warp_ln(const Row& r) { float e = 0.f; return warp_ln(r, e); }
__device__ __forceinline__ Row load_row(const bf16* p, int lane) {
  Row r;
#pragma unroll
  for (int q = 0; q < 4; q++) { const uint2 v = ld_rlx64(p + lane * 4 + q * 128); r.w[2 * q] = v.x; r.w[2 * q + 1] = v.y; }
  return r;
}
__device__ __forceinline__ void store_row_img(uint8_t* img, int rr, int lane, const Row& r) {
  uint8_t* p = img + (lane >> 4) * 4096 + rr * 128 + ((((lane & 15) >> 1) ^ (rr & 7)) << 4) + (lane & 1) * 8;
#pragma unroll
  for (int q = 0; q < 4; q++) *(uint2*)(p + q * 8192) = make_uint2(r.w[2 * q], r.w[2 * q + 1]);
}

constexpr int C_WO = 0;
constexpr int C_X = 49152;
constexpr int C_M = C_X + 65536;
constexpr int C_Q = C_M + 24576;
constexpr int C_K = C_Q + 10240, C_V = C_K + 10240;
constexpr int C_SA = C_V + 10240, C_SB = C_SA + 8192;
constexpr int C_O = C_SB + 8192;
constexpr int C_OT = C_O + 6144;
constexpr int C_PI = C_OT + 16384;
constexpr int C_BAR = C_PI + 8192;
constexpr int C_SMEM = C_BAR + 384 + 1024 + TREXTRA;
constexpr int C_STG = C_X + 32768;
static_assert(C_STG + 131072 <= C_BAR, "staging");
enum { B_M0 = 0, B_M1, B_M2, B_X, B_O, B_T, B_F, B_XL, B_U, B_P1, B_P2, B_OT, B_XF, B_XA, B_I, B_PI, B_J, B_W, B_WO, B_NUM };
static_assert(B_NUM <= 24, "barriers");
constexpr int C_POL = C_BAR + 192, C_INFO = C_BAR + 208;
enum { NB_ALL = 0, NB_M0, NB_PV, NB_W0, NB_TA, NB_M1, NB_M2, NB_RD, NB_SM, NB_C, NB_GO };
constexpr float SCALE_LOG2E = 0.08838834764831845f * 1.4426950408889634f;
#define N0STEPS 9
#define N2STEPS 12
#define FGATE 1
#define NSSTEPS 0
constexpr int KA = 32 - NSSTEPS - N2STEPS, K3 = KA - N0STEPS;
static_assert(KA % 4 == 0, "the rows of layer 1 are refilled in two parts");
#define BGATE 0
#define W0EARLY 0
#define PVEARLY 1
#define S1GATE 0
#define UPOLL 120
#define UGATE 1200
#define IGRP 0
#define SHIPLATE 7
#define SHIP 1024
#define GATE_P 2300
#define GATE_W 170
#define EXPF 0
#define GATE_G 170
#define GATE_M 3280
#define HOLE0 22
#define HOLE1 28
#define HOLE2 32
__device__ __forceinline__ uint32_t gtime() { uint32_t t; asm volatile("mov.u32 %0, %%globaltimer_lo;" : "=r"(t) :: "memory"); return t; }
__device__ __forceinline__ void wait_clock(uint32_t t) {
  asm volatile("{ .reg .pred p; .reg .b32 c; .reg .b64 cc;\nL: mov.u64 cc, %%clock64; cvt.u32.u64 c, cc; sub.u32 c, c, %0; setp.lt.s32 p, c, 0; @p bra L; }" ::"r"(t) : "memory");
}
__device__ __forceinline__ void bar_sync_z(int id, int n, uint32_t z) {
  asm volatile("{ .reg .pred p; setp.eq.u32 p, %2, 0; @p bar.sync %0, %1; }" ::"r"(id), "r"(n), "r"(z) : "memory");
}

__device__ __forceinline__ int probe_home(uint32_t* p, int lane) {
  uint32_t best[2] = {~0u, ~0u};
#pragma unroll 1
  for (int rep = 0; rep < 3; rep++) {
#pragma unroll
    for (int pg = 0; pg < 2; pg++) {
      uint32_t t0, t1, v = 0;
      asm volatile("mov.u32 %0, %%clock;" : "=r"(t0) :: "memory");
      asm volatile("{ .reg .pred p; setp.eq.u32 p, %2, 0; @p atom.relaxed.gpu.global.exch.b32 %0, [%1], %3; }" : "+r"(v) : "l"(p + pg * 1024), "r"(lane), "r"(rep) : "memory");
      asm volatile("{ .reg .pred p; setp.ne.u32 p, %1, 0x13572468; mov.u32 %0, 0; @p mov.u32 %0, %%clock; }" : "=r"(t1) : "r"(v) : "memory");
      best[pg] = min(best[pg], t1 - t0);
    }
  }
  return __shfl_sync(~0u, max(-150, min(150, (int)(best[1] - best[0]))), 0);
}
__device__ __forceinline__ uint32_t home_flip(const void* p) { const uint32_t a = (uint32_t)(size_t)p; return ((a >> 16) ^ (a >> 17) ^ (a >> 19)) & 1; }
__device__ __forceinline__ uint32_t ppage(uint32_t lp, uint32_t pol) { return lp ? 3 - pol : pol; }
__device__ __forceinline__ uint32_t and_x(uint32_t a, uint32_t b, uint32_t m) {
  uint32_t d; asm("lop3.b32 %0, %1, %2, %3, 0x42;" : "=r"(d) : "r"(a), "r"(b), "r"(m)); return d;
}
__device__ __forceinline__ uint32_t and3(uint32_t a, uint32_t b, uint32_t c) {
  uint32_t d; asm("lop3.b32 %0, %1, %2, %3, 0x80;" : "=r"(d) : "r"(a), "r"(b), "r"(c)); return d;
}

template <int N> struct IC { static constexpr int value = N; };
template <class F> __device__ __forceinline__ void static_for2(F f) { f(IC<0>()); f(IC<1>()); }
template <class F> __device__ __forceinline__ void static_for3(F f) { f(IC<0>()); f(IC<1>()); f(IC<2>()); }
__device__ __forceinline__ void stage_weights(uint32_t stage, const CUtensorMap* map, int col, int row, uint32_t mbar) {
  mbar_expect_tx(mbar, 131072);
#pragma unroll 1
  for (int i = 0; i < 4; i++)
    asm volatile("cp.async.bulk.tensor.2d.shared::cluster.global.mbarrier::complete_tx::bytes [%0], [%1, {%3, %4}], [%2];"
                 ::"r"(stage + (i & 1) * 65536 + (i >> 1) * 32768), "l"(map), "r"(mbar), "r"(col + (i & 1) * 64), "r"(row + (i >> 1) * 256) : "memory");
}
__device__ __forceinline__ void load_wfrags(uint32_t (&wA)[32][4], uint32_t stage, int w, int lane) {
  const int mi = lane >> 3, r = lane & 7;
  const uint32_t a = stage + (w >> 2) * 65536 + ((mi >> 1) * 8 + r) * 128 + ((((w & 3) * 2 + (mi & 1)) ^ r) << 4);
#pragma unroll
  for (int ks = 0; ks < 32; ks++) ldsm4t(wA[ks], a + ks * 2048);
}
template <int K0, int K1>
__device__ __forceinline__ void tok_seq(float (&d)[16], const uint32_t (&wA)[32][4], uint64_t desc, uint32_t wave) {
#pragma unroll
  for (int k = K0; k < K1; k++) {
    const int ks = k & 31;
    constexpr int HM0 = 1, HM1 = 2, HM2 = 4;
    const int hm = (k == HOLE0 ? HM0 : 0) | (k == HOLE1 ? HM1 : 0) | (k == HOLE2 ? HM2 : 0);
    if (hm) bar_sync_z(NB_RD, 384, ((hm >> wave) & 1) ^ 1);
    if (ks == 0) wg_rs32<0, 0>(d, wA[ks], desc);
    else wg_rs32<0, 1>(d, wA[ks], desc + (ks >> 2) * 256 + (ks & 3) * 2);
  }
}
template <int K0, int K1>
__device__ __forceinline__ void mem_part(float (&d)[12], const uint32_t (&wA)[32][4], uint64_t desc) {
#pragma unroll
  for (int ks = K0; ks < K1; ks++) {
    if (ks == 0) wg_rs24<1, 0>(d, wA[ks], desc);
    else wg_rs24<1, 1>(d, wA[ks], desc + ks * 48);
  }
}
__device__ __forceinline__ void out_tile(float (&d)[12], uint64_t da, uint64_t db) {
#pragma unroll
  for (int i = 0; i < 8; i++) { if (i == 0) wg_ss24<0>(d, da, db); else wg_ss24<1>(d, da + i * 128, db + (i >> 1) * 32 + (i & 1) * 2); }
}
__device__ __forceinline__ void tok_pack(uint32_t (&p)[8], const float (&d)[16]) {
#pragma unroll
  for (int i = 0; i < 8; i++) p[i] = pack_bf16(d[2 * i], d[2 * i + 1]);
}
__device__ __forceinline__ void tok_store(uint32_t dst, const uint32_t (&p)[8]) {
  stsm4(dst, p[0], p[1], p[2], p[3]);
  stsm4(dst + 4096, p[4], p[5], p[6], p[7]);
}
template <class T> __device__ __forceinline__ T keep(T v) { asm volatile("" : "+r"(v)); return v; }
__device__ __forceinline__ uint32_t pin(uint32_t v) { return __shfl_sync(~0u, v, threadIdx.x & 31); }

#define TRC blockIdx.x
#define TRS (C_BAR + 384)
__device__ __forceinline__ void chain_proj(const uint32_t sb, const int w, const int lane_, const uint32_t rank) {
  uint32_t wA[32][4];
  mbar_wait(sb + C_BAR + B_W * 8, 0, 30);
  if (w == 0) { HD(2) }
  load_wfrags(wA, sb + C_STG, w, lane_);
  bar_arrive(NB_ALL, 384);
  const int lane = pin(lane_);
  const uint32_t bars = sb + C_BAR;
  const uint32_t quad = pin(sb + (lane_ >> 4) * 2048 + (lane_ & 15) * 16);
  const uint32_t own = C_Q + rank * 10240;
  const uint64_t dX1 = mk_desc(sb + C_X, 16, 1024, 1), dX2 = dX1 + 2048;
  const uint64_t dM = mk_desc(sb + C_M, 128, 256, 0);
  const uint32_t r1 = rank == 0 ? 1 : 0, r2 = rank == 2 ? 1 : 2;
  const uint32_t xa = pin(sb + own + 8192 + w * 256 + lane_ * 4);
  const uint32_t a1x = pin(mapa_u32(xa, r1)), a2x = pin(mapa_u32(xa, r2));
  const uint32_t b1x = pin(mapa_u32(bars + B_X * 8, r1)), b2x = pin(mapa_u32(bars + B_X * 8, r2));
  const uint32_t wave = rank == 2 ? 0 : rank + 1;
  float a[16];
  wg_fence();
  tok_seq<32, 32 + KA>(a, wA, mk_desc(__shfl_sync(~0u, sb, 0) + C_X, 16, 1024, 1), 3);
  wg_commit();
  wg_wait<0>();
  mbar_arrive_z(bars + B_XA * 8, lane);
#pragma unroll 1
  for (int st = 0;; st++) {
    uint32_t pk[8];
    wg_fence();
    if (NSSTEPS) bar_sync(NB_SM, 416);
    tok_seq<32 + KA, 32 + KA + NSSTEPS>(a, wA, dX1, 3);
    bar_sync(NB_PV, NSSTEPS ? 384 : 416);
    tok_seq<32 + KA + NSSTEPS, 64>(a, wA, dX1, 3);
    wg_commit();
    wg_wait<0>();
    acc_fence(a);
    mbar_arrive_z(bars + B_XF * 8, lane);
    tok_pack(pk, a);
    TR(1)
    bar_sync(NB_W0, 416);
    tok_store(quad + w * 256 + (rank == 0 ? own : C_SA), pk);
    __syncwarp();
    mbar_arrive_z(bars + B_P1 * 8, lane);
    wg_fence();
    tok_seq<0, 32>(a, wA, dX2, wave);
    wg_commit();
    const uint32_t info = lds32(sb + C_INFO + (st & 1) * 4);
    TR(2)
    wg_wait<0>();
    acc_fence(a);
    TR(3)
    tok_pack(pk, a);
    tok_store(quad + w * 256 + (rank == 0 ? C_SA : own), pk);
    if (rank == 2) tok_store(quad + w * 256 + C_SB, pk);
    __syncwarp();
    mbar_arrive_z(bars + B_P2 * 8, lane);
    TR(4)
    wg_fence();
    tok_seq<32, 32 + K3>(a, wA, dX1, wave);
    TR(6)
    {
      float am[12];
      bar_sync(NB_M0, 384);
      mem_part<0, 10>(am, wA, dM);
      TR(7)
      bar_sync(NB_M1, 384);
      mem_part<10, 21>(am, wA, dM);
      bar_sync(NB_M2, 384);
      const uint32_t bad = lds32(sb + C_INFO + 16 + (lane & 3) * 32);
      mem_part<21, 32>(am, wA, dM);
      wg_commit();
      const bool redo = __any_sync(~0u, bad != 0);
      if (__builtin_expect(redo, 0)) {
        wg_wait<0>();
        int it = 0;
        while (__any_sync(~0u, lds32_poll(sb + C_INFO + 20 + (lane & 3) * 32) != st && bad)) give_up(++it, 50 * SPIN_LIMIT, 31);
        wg_fence();
        mem_part<0, 32>(am, wA, dM);
        wg_commit();
      }
      wg_wait<0>();
      acc_fence(am);
      TR(8)
      const uint32_t x00 = pack_bf16(am[0], am[1]), x01 = pack_bf16(am[2], am[3]), x10 = pack_bf16(am[4], am[5]), x11 = pack_bf16(am[6], am[7]);
      const uint32_t y0 = pack_bf16(am[8], am[9]), y1 = pack_bf16(am[10], am[11]), x20 = info ? x10 : y0, x21 = info ? x11 : y1;
      st_async32<0>(a1x, rank == 0 ? x10 : x00, b1x); st_async32<0>(a2x, rank == 2 ? x10 : x20, b2x);
      st_async32<128>(a1x, rank == 0 ? x11 : x01, b1x); st_async32<128>(a2x, rank == 2 ? x11 : x21, b2x);
      sts32(xa, rank == 0 ? x00 : rank == 2 ? x20 : x10); sts32(xa + 128, rank == 0 ? x01 : rank == 2 ? x21 : x11);
      if (__builtin_expect(info, 0)) {
        const uint32_t o = (info & 3) * 2048 - 8192;
        if (rank == 2) { sts32(xa + o, y0); sts32(xa + o + 128, y1); }
        else { st_async32<0>(a2x + o, y0, b2x + (B_T - B_X) * 8); st_async32<128>(a2x + o, y1, b2x + (B_T - B_X) * 8); }
      }
      __syncwarp();
      mbar_arrive_z(bars + B_X * 8, lane);
    }
    TR(9)
    wg_fence();
    tok_seq<32 + K3, 32 + KA>(a, wA, dX1, 3);
    wg_commit();
    TR(0)
    wg_wait<0>();
    if (st == NSTEP - 1) break;
    mbar_arrive_z(bars + B_XA * 8, lane);
  }
  if (NSSTEPS) bar_arrive(NB_SM, 416);
  bar_arrive(NB_PV, NSSTEPS ? 384 : 416);
}

__device__ __forceinline__ void chain_mem(const uint32_t sb, const int w, const int lane_, const uint32_t rank, const int h,
                                          const bf16* __restrict__ mem0) {
  const int lane = pin(lane_);
  const int wave = rank == 2 ? 0 : rank + 1;
  const int c = w - 8, t = c * 32 + lane, b = wave * 32 + h;
  const uint32_t bars = sb + C_BAR;
  const int wi = (lane & 1) * 2 + (lane >> 4), cq = (lane >> 2) & 3;
  mbar_expect_tx_z(bars + B_X * 8, 4096, t); mbar_expect_tx_z(bars + B_O * 8, 4096, t);
  if (NSSTEPS) bar_arrive(NB_SM, 416);
  bar_arrive(NB_PV, NSSTEPS ? 384 : 416); bar_arrive(NB_W0, 416); bar_arrive(NB_RD, 384);
  uint32_t m0[16];
#pragma unroll
  for (int i = 0; i < 16; i++) m0[i] = *(const uint32_t*)(mem0 + (lane >> 2) * DM + (c * 16 + i) * 8 + (lane & 3) * 2);
  uint32_t* pp = g_M + c * 16384 + 14 * 1024 + (blockIdx.x & 31) * 32;
  st_rlx32(pp + lane, 0); st_rlx32(pp + 1024 + lane, 0);
  mbar_wait(bars + B_W * 8, 0, 32);
  {
    uint32_t* p = pp;
    const int vote = probe_home(p, lane);
    sts32(sb + C_POL + c * 4, home_flip(p) ? -vote : vote);
    bar_sync(NB_C, 128);
    const uint4 v = lds128(sb + C_POL);
    const uint32_t side = (int)(v.x + v.y + v.z + v.w) > 0;
    bar_sync(NB_C, 128);
    sts32(sb + C_POL + c * 4, side ^ home_flip(p));
    sts32(sb + C_INFO + 8, side ^ home_flip(g_P + b * 4096));
    if (c == 0) { HD(0) }
    wait_count(g_ex.ready, 96, 35);
    if (c == 0) { HD(1) }
    st_rlx32(&g_fl.pol[b], (side ^ home_flip(g_P + b * 4096)) + 1);
  }
  bar_sync(NB_ALL, 384);
  if (c == 0) { HD(3) }
  mbar_arrive_remote_z(mapa_u32(bars + B_F * 8, (rank + 1 + (t & 1)) % 3), t >> 1);
#pragma unroll
  for (int i = 0; i < 16; i += 4) {
    const uint32_t a = sb + C_M + (c * 8 + i / 2 + (lane >> 4)) * 768 + (lane & 15) * 16;
    stsm4t(a, m0[i], m0[i + 1], m0[i + 2], m0[i + 3]); stsm4t(a + 256, m0[i], m0[i + 1], m0[i + 2], m0[i + 3]); stsm4t(a + 512, m0[i], m0[i + 1], m0[i + 2], m0[i + 3]);
  }
  sts32(sb + C_INFO + 16 + c * 32, 0); sts32(sb + C_INFO + 20 + c * 32, 0);
  fence_async_smem();
  bar_arrive(NB_M0, 384); bar_arrive(NB_M1, 384);
  mbar_wait(bars + B_F * 8, 0, 34);
  bar_arrive(NB_M2, 384);
  mbar_wait(bars + B_WO * 8, 0, 33);
  uint32_t pgbits, polP;
  {
    const int tl = lane / 3, u = ((tl * 3 + rank) * 4 + c) * 3 + (lane - tl * 3);
    uint32_t pol;
    int it = 0;
    do { pol = ld_rlx32(&g_fl.pol[lane < 9 && u < 96 ? u : b]); give_up(it++, SPIN_LIMIT, 40); } while (__any_sync(~0u, pol == 0));
    pgbits = __reduce_or_sync(~0u, lane < 9 ? ppage(h >> 4, (pol - 1) & 1) << (2 * lane) : 0u);
    polP = __shfl_sync(~0u, pol - 1, 9);
  }
  const int mi = lane >> 3;
  const uint32_t l16 = pin(sb + lane * 16);
  const uint32_t r1 = rank == 2 ? 0 : rank + 1, r2 = rank == 0 ? 2 : rank - 1;
  const uint32_t oa = pin(sb + C_O + rank * 2048 + (lane >> 2) * 64 + (((lane & 3) ^ (lane >> 3)) << 4));
  const uint32_t a1 = mapa_u32(oa, r1), b1 = mapa_u32(bars + B_O * 8, r1), a2 = mapa_u32(oa, r2), b2 = mapa_u32(bars + B_O * 8, r2);
  const uint64_t dWo = mk_desc(sb + C_WO, 8192, 1024, 1), dO = mk_desc(sb + C_O, 16, 2048, 2);
  const uint64_t dK = mk_desc(sb + C_K, 128, 2048, 0);
  const uint64_t dV = mk_desc(sb + C_V, 2048, 128, 0), dVm = mk_desc(sb + C_V + 8192, 0, 128, 0);
  const uint32_t qa = pin(sb + C_Q + (c ? c + 1 : mi & 1) * 2048 + (mi >> 1) * 128 + (lane & 7) * 16);
  const uint32_t dg = ((lane >> 2) < 2 * (lane & 3) ? 1 : 0) | ((lane >> 2) < 2 * (lane & 3) + 1 ? 2 : 0);
  const uint32_t msk = pin(c == 0 ? dg | dg << 4 : c == 1 ? dg << 2 | 3 << 4 : c == 2 ? dg << 4 : 0);
  uint8_t* Pw = (uint8_t*)g_P + (rank * 4 + c) * 3 * 16384 + (h & 15) * 256 + ((lane * 4) ^ ((h & 3) << 5));
  const uint32_t pia = pin(sb + C_PI + ((lane >> 4) * 4 + (lane & 3)) * 256 + ((c * 64 + cq * 16) ^ ((lane & 3) << 5)));
  uint8_t* Mw = (uint8_t*)g_M + (b >> 5) * 16384 + ((lane & 2) ? 4096 : 12288) + (b & 31) * 256 + c * 64 + cq * 16 + wi * 4;
  uint32_t nupd = 0;
  bar_arrive(NB_GO, 160);

  { const int st = 71; (void)st; STAT(0, lds32(sb + C_POL + c * 4)) STAT(1, polP) STAT(2, (uint32_t)(size_t)(g_M + c * 16384)) STAT(3, (uint32_t)(size_t)(g_P + b * 4096)) }
#pragma unroll 1
  for (int st = 0;; st++) {
    mbar_wait(bars + B_P1 * 8, st & 1, 38);
    mbar_wait(bars + B_T * 8, st & 1, 42);
    STAT(10, clk32())
    {
      float s[20];
      {
        uint32_t q[8][4];
        if (c == 3) mbar_wait(bars + B_X * 8, st & 1, 41);
#pragma unroll
        for (int i = 0; i < 8; i++) ldsm4t(q[i], qa + i * 256);
        if (c != 3) { mbar_wait(bars + B_X * 8, st & 1, 41); fence_async_smem(); }
        STAT(11, clk32())
        TR(0)
        wg_fence();
#pragma unroll
        for (int i = 0; i < 8; i++) { if (i == 0) wg_rs40<0>(s, q[i], dK); else wg_rs40<1>(s, q[i], dK + i * 16); }
        wg_commit();
        wg_wait<0>();
        if (NSSTEPS) bar_arrive(NB_SM, 416);
        acc_fence(s);
      }
      TR(1)
      const bool w0 = c == 0;
      float z[10] = {s[16], s[17], s[0], s[1], w0 ? s[18] : s[4], w0 ? s[19] : s[5], w0 ? s[2] : s[8], w0 ? s[3] : s[9], w0 ? s[6] : s[12], w0 ? s[7] : s[13]};
      if (msk & 1) z[2] = -INFINITY;
      if (msk & 2) z[3] = -INFINITY;
      if (msk & 4) z[6] = -INFINITY;
      if (msk & 8) z[7] = -INFINITY;
      if (msk & 16) z[8] = -INFINITY;
      if (msk & 32) z[9] = -INFINITY;
      float m0 = fmaxf(fmaxf(z[0], z[1]), fmaxf(z[2], z[3])), m1 = fmaxf(fmaxf(fmaxf(z[4], z[5]), fmaxf(z[6], z[7])), fmaxf(z[8], z[9]));
      m0 = fmaxf(m0, __shfl_xor_sync(~0u, m0, 1)); m1 = fmaxf(m1, __shfl_xor_sync(~0u, m1, 1));
      m0 = fmaxf(m0, __shfl_xor_sync(~0u, m0, 2)); m1 = fmaxf(m1, __shfl_xor_sync(~0u, m1, 2));
      if (!w0) m0 = m1 = fmaxf(m0, m1);
      m0 *= -SCALE_LOG2E; m1 *= -SCALE_LOG2E;
      uint32_t p[5];
#pragma unroll
      for (int k = 0; k < 5; k++) {
        z[2 * k] = ex2_fast(fmaf(z[2 * k], SCALE_LOG2E, k < 2 ? m0 : m1)); z[2 * k + 1] = ex2_fast(fmaf(z[2 * k + 1], SCALE_LOG2E, k < 2 ? m0 : m1));
        p[k] = pack_bf16(z[2 * k], z[2 * k + 1]);
      }
      const uint32_t p2 = w0 ? 0 : p[2], p3 = w0 ? 0 : p[3], p4 = w0 ? 0 : p[4];
      float oA[32], oB[32];
      wg_fence();
      wg_rs64<0>(oA, p[0], p[2], 0, 0, dVm); wg_rs64<1>(oA, p[1], p[3], p2, p[4], dV); wg_rs64<1>(oA, p3, 0, p4, 0, dV + 256);
      wg_commit();
      wg_rs64<0>(oB, p[0], p[2], 0, 0, dVm + 64); wg_rs64<1>(oB, p[1], p[3], p2, p[4], dV + 64); wg_rs64<1>(oB, p3, 0, p4, 0, dV + 320);
      wg_commit();
      float l0 = (z[0] + z[1]) + (z[2] + z[3]), l1 = ((z[4] + z[5]) + (z[6] + z[7])) + (z[8] + z[9]);
      if (!w0) l0 += l1;
      l0 += __shfl_xor_sync(~0u, l0, 1); l1 += __shfl_xor_sync(~0u, l1, 1);
      l0 += __shfl_xor_sync(~0u, l0, 2); l1 += __shfl_xor_sync(~0u, l1, 2);
      float i0, i1;
      asm volatile("rcp.approx.ftz.f32 %0, %2; rcp.approx.ftz.f32 %1, %3;" : "=f"(i0), "=f"(i1) : "f"(l0), "f"(l1));
      asm volatile("st.shared.v2.f32 [%0], {%1,%2};" ::"r"(sb + C_INFO + 24), "f"(i0), "f"(i1) : "memory");
      const uint32_t ta = l16 + C_OT + (st & 1) * 8192 + (c ? c + 1 : 0) * 2048;
      auto leave = [&](const float (&o)[32], auto hc) {
        constexpr int H = decltype(hc)::value;
        uint32_t e[8];
#pragma unroll
        for (int j = 0; j < 8; j++) e[j] = pack_bf16(o[4 * j] * i0, o[4 * j + 1] * i0);
        if (c == 3) {
          static_for2([&](auto bc) {
            constexpr int B = decltype(bc)::value;
            asm volatile("st.async.weak.shared::cluster.mbarrier::complete_tx::bytes.v4.b32 [%0 + %9], {%5,%6,%7,%8}, [%1];\n"
                         "st.async.weak.shared::cluster.mbarrier::complete_tx::bytes.v4.b32 [%2 + %9], {%5,%6,%7,%8}, [%3];\n"
                         "st.shared.v4.b32 [%4 + %9], {%5,%6,%7,%8};"
                         ::"r"(a1), "r"(b1), "r"(a2), "r"(b2), "r"(oa), "r"(e[4 * B]), "r"(e[4 * B + 1]), "r"(e[4 * B + 2]), "r"(e[4 * B + 3]),
                           "n"(H * 1024 + B * 512) : "memory");
          });
        } else {
          stsm4(ta + H * 1024, e[0], e[1], e[2], e[3]); stsm4(ta + H * 1024 + 512, e[4], e[5], e[6], e[7]);
          if (w0) {
#pragma unroll
            for (int j = 0; j < 8; j++) e[j] = pack_bf16(o[4 * j + 2] * i1, o[4 * j + 3] * i1);
            stsm4(ta + 2048 + H * 1024, e[0], e[1], e[2], e[3]); stsm4(ta + 2048 + H * 1024 + 512, e[4], e[5], e[6], e[7]);
          }
        }
      };
      wg_wait<1>();
      acc_fence(oA);
      leave(oA, IC<0>());
      wg_wait<0>();
      if (PVEARLY) bar_arrive(NB_PV, NSSTEPS ? 384 : 416);
      acc_fence(oB);
      leave(oB, IC<1>());
      if (!PVEARLY) bar_arrive(NB_PV, NSSTEPS ? 384 : 416);
      __syncwarp();
      mbar_arrive_z(bars + (c == 3 ? B_O : B_OT) * 8, lane);
      TR(2)
    }
    mbar_wait(bars + B_O * 8, st & 1, 43);
    if (st == NSTEP - 1) break;
    uint32_t info;
    {
      const uint32_t tag = (st & 1) ^ 1;
      float oc0[12], oc1[12], oc2[12];
      fence_async_smem();
      TR(3)
      wg_fence();
      out_tile(oc0, dWo, dO);
      wg_commit();
      out_tile(oc1, dWo + 1024, dO);
      wg_commit();
      asm volatile("" : "+r"(pgbits));
      auto put = [&](const float (&oc)[12], auto tlc) {
        constexpr int TL = decltype(tlc)::value;
        static_for3([&](auto jc) {
          constexpr int j = decltype(jc)::value;
          uint8_t* p = Pw + ((pgbits >> (2 * (TL * 3 + j))) & 3) * 4096;
          asm volatile("st.relaxed.gpu.global.u32 [%0 + %3], %1; st.relaxed.gpu.global.u32 [%0 + %3 + 128], %2;" ::"l"(p),
                       "r"((pack_bf16(oc[4 * j], oc[4 * j + 1]) & ~1u) | tag), "r"((pack_bf16(oc[4 * j + 2], oc[4 * j + 3]) & ~1u) | tag),
                       "n"((TL * 36 + j) * 16384) : "memory");
        });
      };
      wg_wait<1>();
      acc_fence(oc0);
      put(oc0, IC<0>());
      sts32(sb + C_INFO + 24, clk32());
      TR(4)
      out_tile(oc2, dWo + 2048, dO);
      wg_commit();
      wg_wait<1>();
      acc_fence(oc1);
      put(oc1, IC<1>());
      if (W0EARLY) bar_arrive(NB_W0, 416);
      bar_sync(NB_TA, 192);
      TR(5)
      wg_wait<0>();
      if (!W0EARLY) bar_arrive(NB_W0, 416);
      info = lds32(sb + C_INFO + ((st + 1) & 1) * 4);
      acc_fence(oc2);
      if (rank != 2) put(oc2, IC<2>());
      mbar_arrive_remote_z(((t & 1) ? b2 : b1) + (B_F - B_O) * 8, t >> 1);
      mbar_expect_tx_z(bars + ((t & 1) ? B_O : B_X) * 8, 4096, t >> 1);
      TR(6)
    }
    const int sn = (st + 1) & 3;
    uint8_t* mw = Mw + sn * 65536;
    asm volatile("" : "+l"(mw));
    if (__builtin_expect((st < DELTA && b % 3 != 0) || (info && b % 3 == 2), 0)) {
      bar_arrive(NB_RD, 384);
      const int col = b / 3 * 16 + c * 4 + ((lane >> 2) & 3), r0 = (lane & 1) * 4 + (lane >> 4) * 2;
      const bool upd = info && b % 3 == 2;
      if (upd) mbar_wait(bars + B_U * 8, nupd & 1, 39);
      uint32_t hv[2];
#pragma unroll
      for (int i = 0; i < 2; i++) {
        const int r = r0 + i, sg = st + 1 - DELTA;
        const void* p = !upd ? (const void*)(mem0 + r * DM + col) : r == (int)(info >> 4) ? (const void*)(g_x2p[sg][1] + col)
                      : (const void*)(g_xs[1] + sg * 32768 + (col >> 6) * 4096 + ((info & 3) * 8 + r) * 128 + ((((col >> 3) ^ r) & 7) << 4) + (col & 7) * 2);
        asm volatile("ld.relaxed.gpu.global.u16 %0, [%1];" : "=r"(hv[i]) : "l"(p) : "memory");
      }
      st_rlx32(mw, hv[0] | hv[1] << 16);
      STAT(1, 0) STAT(2, 0) STAT(4, 0)
    } else {
      const uint32_t flip = (st & 1) ? ~0u : 0u;
      const bool u16 = lane & 16;
      const uint32_t bs = (lane & 4) ? 0x3f800000u : 0x00003f80u, bs0 = (lane & 8) ? 0u : bs, bs1 = (lane & 8) ? bs : 0u;
      STATC(c_rdy)
      mbar_wait(bars + B_PI * 8, st & 1, 37);
      TR(7)
      uint4 q0 = lds128(pia), q1 = lds128(pia + 2048), q2 = lds128(pia + 4096), q3 = lds128(pia + 6144);
      int it = 0;
#pragma unroll 1
      while (true) {
        float d0[4] = {0.f, 0.f, 0.f, 0.f}, d1[4] = {0.f, 0.f, 0.f, 0.f};
        mma16816(d0, q0.x, q0.y, q0.z, q0.w, bs0, bs1);
        mma16816(d1, q1.x, q1.y, q1.z, q1.w, bs0, bs1);
        mma16816(d0, q2.x, q2.y, q2.z, q2.w, bs0, bs1);
        mma16816(d1, q3.x, q3.y, q3.z, q3.w, bs0, bs1);
        const bool all = __all_sync(~0u, (int)and3(and_x(q0.x, q1.x, flip), and_x(q2.x, q3.x, flip), 1u));
        const float a0 = d0[0] + d1[0], a1 = d0[1] + d1[1], a2 = d0[2] + d1[2], a3 = d0[3] + d1[3];
        asm volatile("{ .reg .pred p; setp.ne.u32 p, %0, 0; @p bar.arrive %1, 384; }" ::"r"((uint32_t)all), "n"((int)NB_RD) : "memory");
        const uint32_t mword = pack_bf16((u16 ? a2 : a0) + __shfl_xor_sync(~0u, u16 ? a0 : a2, 16), (u16 ? a3 : a1) + __shfl_xor_sync(~0u, u16 ? a1 : a3, 16));
        asm volatile("{ .reg .pred p; setp.ne.u32 p, %2, 0; @p st.relaxed.gpu.global.u32 [%0], %1; }" ::"l"(mw), "r"(mword), "r"((uint32_t)all) : "memory");
        if (__builtin_expect(all, 1)) break;
        give_up(++it, SPIN_LIMIT, 44);
        const uint8_t* Pr0 = (const uint8_t*)g_P + b * 16384 + (pia - sb - C_PI) + polP * 4096;
        const uint8_t* Pr1 = Pr0 + (3 - 2 * polP) * 4096;
        q0 = ld_rlx128(Pr0); q1 = ld_rlx128(Pr0 + 2048); q2 = ld_rlx128(Pr1); q3 = ld_rlx128(Pr1 + 2048);
      }
      STATC(c_mst)
      STAT(1, c_rdy - tref) STAT(2, c_mst - tref) STAT(4, it)
      TRV(14, it)
    }
    STAT(0, lds32(sb + C_INFO + 24) - tref) STAT(3, tref)
    nupd += info != 0;
    TR(9)
    {
      int it = 0;
      const uint32_t mchk = pin(keep(l16) + C_M + c * 2048 + lane * 16 + (lane & 28));
      auto missing = [&](int g) { return __any_sync(~0u, max(lds32(mchk + g * 8192), lds32(mchk + g * 8192 + 1024)) == ~0u); };
      auto complete = [&](int g) {
        const uint8_t* src = (const uint8_t*)g_M + sn * 65536 + (lds32(sb + C_POL + sn * 4) ? 4096 : 12288) + g * 16384 + c * 2048 + lane * 16;
        uint4 v0, v1, v2, v3;
#pragma unroll 1
        do {
          v0 = ld_rlx128(src); v1 = ld_rlx128(src + 512); v2 = ld_rlx128(src + 1024); v3 = ld_rlx128(src + 1536);
          give_up(++it, SPIN_LIMIT, 48);
        } while (__any_sync(~0u, max(__vimax3_u32(v0.x, v1.x, v2.x), v3.x) == ~0u));
        const uint32_t d = l16 + C_M + g * 8192 + c * 2048;
        sts128(d, v0); sts128(d + 512, v1); sts128(d + 1024, v2); sts128(d + 1536, v3);
        fence_async_smem();
      };
      mbar_wait(bars + B_M0 * 8, (st + 1) & 1, 45);
      bar_arrive(NB_M0, 384);
      STATC(c_g0)
      TR(10)
      const bool redo = missing(0);
      sts32(sb + C_INFO + 16 + c * 32, redo);
      static_for2([&](auto gc) {
        constexpr int g = 1 + decltype(gc)::value;
        mbar_wait(bars + (B_M0 + g) * 8, (st + 1) & 1, 46);
        TR(10 + g)
        const bool m = missing(g);
        asm volatile("{ .reg .pred p; setp.eq.u32 p, %0, 0; @p bar.arrive %1, 384; }" ::"r"((uint32_t)m), "n"(NB_M1 + g - 1) : "memory");
        if (__builtin_expect(m, 0)) { complete(g); bar_arrive(NB_M1 + g - 1, 384); }
        STAT(6 + g, clk32() - tref)
      });
      if (__builtin_expect(redo, 0)) { complete(0); __syncwarp(); sts32(sb + C_INFO + 20 + c * 32, st + 1); }
      STAT(5, c_g0 - tref)
      STAT(9, clk32() - tref) STAT(6, it + redo * 256)
      TR(13)
      TRV(15, it)
      st_rlx32(Mw + (st & 3) * 65536, ~0u);
    }
  }
}

__device__ __forceinline__ void chain_dma(const uint32_t sb, const int w, const int lane, const uint32_t rank, const int h) {
  const uint32_t bars = sb + C_BAR;
  const int expf_ = EXPF;
  if (w == 12) {
    u64 best = 0;
    uint32_t nx = 0;
    auto load = [&](uint32_t dst, const uint8_t* src, uint32_t bytes) {
      mbar_expect_tx_z(bars + B_XL * 8, bytes, lane >> 1);
      if (lane < 2 && bytes) {
        fence_async_glb();
        bulk_g2s(sb + dst, src, bytes, bars + B_XL * 8);
      }
      __syncwarp();
      mbar_wait(bars + B_XL * 8, nx++ & 1, 52);
    };
    bar_arrive(NSSTEPS ? NB_SM : NB_PV, 416);
    wait_count(g_ex.ready, 96, 59);
    HD(6)
#pragma unroll 1
    for (int st = 0; st < NSTEP; st++) {
      const int sg = st - DELTA;
      const bool more = st + 1 < NSEG && !(expf_ & 4);
      uint32_t info = 0;
      if (sg >= 0) {
        const u64 k = wait_keys(g_fl.key[0][sg], lane, 50);
        if (k > best) { best = k; info = 4 | ((key_token(k) >> 3) & 3) | (key_token(k) & 7) << 4; }
      }
      TR(0)
      mbar_wait(bars + B_XA * 8, st & 1, 58);
      sts32(sb + C_INFO + (st & 1) * 4, info);
      if (st > 0) bar_arrive(NB_TA, 192);
      TR(1)
      load(lane ? C_X : C_X + 32768, lane ? g_xs[0] + (st + 1) * 32768 : g_xs[1] + sg * 32768, lane ? (more ? KA * 1024 : 0) : (sg >= 0 && !(expf_ & 8) ? 32768 : 0));
      bar_arrive(NB_W0, 416);
      TR(2)
      if (__builtin_expect(info, 0)) {
        int it = 0;
        while (__any_sync(~0u, max(ld_rlx32(g_x2p[sg][1] + lane * 16), ld_rlx32(g_x2p[sg][1] + lane * 16 + 8)) == ~0u)) { give_up(++it, SPIN_LIMIT, 56); warp_sleep(UPOLL); }
        sts32(sb + C_INFO + 40, clk32());
        __syncwarp();
        mbar_arrive_z(bars + B_U * 8, lane);
      }
      mbar_wait(bars + B_XF * 8, st & 1, 53);
      mbar_wait(bars + (B_M0 + BGATE) * 8, st & 1, 54);
      load(C_X + KA * 1024, g_xs[0] + (st + 1) * 32768 + KA * 1024, more && lane == 0 ? 32768 - KA * 1024 : 0);
      TR(3)
      bar_arrive(NSSTEPS ? NB_SM : NB_PV, 416);
    }
  } else if (w == 13) {
    constexpr uint32_t NP = 8192 / SHIP;
    const uint32_t o = (lane >> 1) * SHIP, own = sb + C_Q + rank * 10240, bt = bars + B_T * 8;
    const uint32_t d2 = 1 + (lane & 1);
    const uint32_t src2 = (rank == 0 ? sb + C_SA : rank == 1 ? own : sb + C_SB) + o;
    const uint32_t skip = (lane & 1) ? 4 | (o >> 11) : 8;
#pragma unroll 1
    for (int st = 0; st < NSTEP; st++) {
      mbar_wait(bars + B_P1 * 8, st & 1, 61);
      fence_async_smem();
      mbar_wait(bars + B_F * 8, st & 1, 60);
      if (st > 0) mbar_wait(bars + (S1GATE ? B_PI : B_J) * 8, (st - 1) & 1, 65);
      const uint32_t info = lds32(sb + C_INFO + (st & 1) * 4);
      TR(2)
      if (st < NSEG && rank != 0 && lane < 2 * NP && d2 == 1 && !(expf_ & 1)) bulk_s2r(mapa_u32(own + o, 0), sb + C_SA + o, SHIP, mapa_u32(bt, 0));
      __syncwarp();
      TR(3)
      mbar_wait(bars + B_P2 * 8, st & 1, 62);
      fence_async_smem();
      if (st > 0 && (SHIPLATE >> rank & 1)) mbar_wait(bars + B_I * 8, (st - 1) & 1, 64);
      TR(0)
      if (st >= DELTA && lane < 2 * NP && d2 != rank && (info & 7) != skip && !(expf_ & 2)) bulk_s2r(mapa_u32(own + o, d2), src2, SHIP, mapa_u32(bt, d2));
      __syncwarp();
      TR(1)
    }
  } else if (w == 14) {
    const int s0 = rank == 0 ? 0 : DELTA;
    const uint32_t tbytes = (expf_ & (rank ? 2 : 1)) ? 0 : 16384;
    mbar_expect_tx_z(bars + B_T * 8, s0 == 0 ? tbytes : 0, lane);
#pragma unroll 1
    for (int st = 0; st < NSTEP; st++) {
      const int sg = st - s0;
      const bool act = (unsigned)sg < (unsigned)NSEG;
      mbar_wait(bars + B_OT * 8, st & 1, 70);
      mbar_expect_tx_z(bars + B_T * 8, (unsigned)(sg + 1) < (unsigned)NSEG ? tbytes : 0, lane);
      fence_async_smem();
      const int s1 = rank && st < NSEG - 1 ? st + 1 : st;
      if (s1 != st) mbar_wait(bars + B_X * 8, s1 & 1, 71);
      TR(0)
      if (act && lane == 0 && !(expf_ & (rank ? 32 : 16))) {
        bulk_s2g(g_O[st & (OSLOTS - 1)][rank] + h * 8192, sb + C_OT + (st & 1) * 8192, 8192);
        asm volatile("cp.async.bulk.commit_group;" ::: "memory");
        asm volatile("cp.async.bulk.wait_group 0;" ::: "memory");
        asm volatile("fence.acq_rel.gpu;" ::: "memory");
      }
      __syncwarp();
      if (WLAG && s1 < NSTEP - 1) mbar_wait(bars + (FGATE ? B_M0 + FGATE - 1 : B_I) * 8, (s1 + (FGATE > 0)) & 1, 72);
      if (act && lane == 0) asm volatile("red.relaxed.gpu.global.add.u32 [%0], 1;" ::"l"(&g_fl.oflag[rank][sg][h >> 2]) : "memory");
      __syncwarp();
      TR(1)
    }
  } else {
    mbar_arrive_z(bars + B_M0 * 8, lane); mbar_arrive_z(bars + B_M1 * 8, lane); mbar_arrive_z(bars + B_M2 * 8, lane);
    const uint32_t wave = rank == 2 ? 0 : rank + 1, gate_p = GATE_P + wave * GATE_W, gate_g = GATE_G, gate_m = GATE_M;
    uint32_t nupd = 0, late = 128;
    bar_sync(NB_GO, 160);
#pragma unroll 1
    for (int st = 0; st < NSTEP - 1; st++) {
      mbar_wait(bars + B_X * 8, st & 1, 75);
      if (st < 4) { HD(8 + st) }
      if (st == NSTEP - 2) { HD(12) }
      mbar_wait(bars + B_T * 8, st & 1, 77);
      const uint32_t now = gtime() & ~31u, tag = (st + 1) & 31;
      if (lane == 0) st_rlx32(&g_fl.stamp[blockIdx.x], (now + late) | tag);
      late = 0;
      __syncwarp();
      wait_clock(clk32() + 550);
      uint32_t s0, s1, s2;
      int it = 0;
#pragma unroll 1
      do {
        s0 = ld_rlx32(&g_fl.stamp[lane]) ^ tag; s1 = ld_rlx32(&g_fl.stamp[32 + lane]) ^ tag; s2 = ld_rlx32(&g_fl.stamp[64 + lane]) ^ tag;
        give_up(it++, SPIN_LIMIT, 76);
      } while (__any_sync(~0u, ((s0 | s1 | s2) & 31) != 0));
      const uint32_t tref = now + __reduce_max_sync(~0u, __vimax3_s32((int)(s0 - now), (int)(s1 - now), (int)(s2 - now)));
      const uint32_t g0 = gtime();
      uint32_t g1, c1;
      it = 0;
      do { g1 = gtime(); c1 = clk32(); } while (g1 == g0 && ++it < 64);
      c1 -= (g1 - tref) * 7 / 4;
      sts32(sb + C_INFO + 12, c1);
      TR(0)
      bar_sync(NB_TA, 192);
      const int sn = (st + 1) & 3;
      const uint8_t* src = (const uint8_t*)g_M + sn * 65536 + (lds32(sb + C_POL + sn * 4) ? 4096 : 12288);
      {
        const uint32_t pol = lds32(sb + C_INFO + 8);
        const uint8_t* ps = (const uint8_t*)g_P + (wave * 32 + h) * 16384;
        if (lane == 0) {
          mbar_expect_tx(bars + B_PI * 8, 8192);
          wait_clock(c1 + gate_p);
          bulk_g2s(sb + C_PI, ps + pol * 4096, 4096, bars + B_PI * 8);
          bulk_g2s(sb + C_PI + 4096, ps + (3 - pol) * 4096, 4096, bars + B_PI * 8);
          mbar_arrive_z(bars + B_J * 8, 0);
        }
        __syncwarp();
      }
      c1 += gate_m;
      if (__builtin_expect(lds32(sb + C_INFO + ((st + 1) & 1) * 4), 0)) {
        late = rank == 2 ? 96 : 0;
        mbar_wait(bars + B_U * 8, nupd++ & 1, 78);
        const uint32_t c2 = lds32(sb + C_INFO + 40) + UGATE;
        if ((int)(c2 - c1) > 0) c1 = c2;
      }
      mbar_expect_tx_z(bars + (B_M0 + lane) * 8, 8192, lane / 3);
      if (lane == 0) {
#pragma unroll
        for (int g = 0; g < 3; g++) {
          wait_clock(c1 + g * gate_g);
          bulk_g2s(sb + C_M + g * 8192, src + g * 16384, 8192, bars + (B_M0 + g) * 8);
          if (g == IGRP) mbar_arrive_z(bars + B_I * 8, 0);
        }
      }
      __syncwarp();
      TR(3)
    }
  }
}

struct ChainMaps { CUtensorMap w[3], wo; };
__global__ void __cluster_dims__(3, 1, 1) __launch_bounds__(512, 1)
chain_kernel(const __grid_constant__ ChainMaps maps, const bf16* __restrict__ mem0, const bf16* __restrict__ x0) {
  extern __shared__ __align__(1024) uint8_t smem_raw[];
  const uint32_t sb = (smem_u32(smem_raw) + 1023) & ~1023u;
  const int tid = threadIdx.x, lane = tid & 31;
  const int w = __shfl_sync(~0u, tid >> 5, 0);
  uint32_t rank;
  asm volatile("mov.u32 %0, %%cluster_ctarank;" : "=r"(rank));
  const int h = blockIdx.x / 3;
  asm volatile("griddepcontrol.launch_dependents;" ::: "memory");
  TG(0)
  const int row2 = 32 + blockIdx.x * 16 + w, row3 = 1568 + min(w, 4) * 96 + blockIdx.x;
  Row xr[4] = {load_row(x0 + row2 * DM, lane), load_row(x0 + row3 * DM, lane), load_row(x0 + w * DM, lane), load_row(x0 + (w + 16) * DM, lane)};
  if (tid == 0) {
    const uint32_t bars = sb + C_BAR;
    mbar_init(bars + B_M0 * 8, 1); mbar_init(bars + B_M1 * 8, 1); mbar_init(bars + B_M2 * 8, 1);
    mbar_init(bars + B_X * 8, 9); mbar_init(bars + B_O * 8, 2); mbar_init(bars + B_T * 8, 1); mbar_init(bars + B_F * 8, 2);
    mbar_init(bars + B_XL * 8, 2); mbar_init(bars + B_U * 8, 1);
    mbar_init(bars + B_P1 * 8, 8); mbar_init(bars + B_P2 * 8, 8); mbar_init(bars + B_OT * 8, 3); mbar_init(bars + B_XF * 8, 8); mbar_init(bars + B_XA * 8, 8); mbar_init(bars + B_I * 8, 1); mbar_init(bars + B_PI * 8, 1); mbar_init(bars + B_J * 8, 1);
    mbar_init(bars + B_W * 8, 1); mbar_init(bars + B_WO * 8, 1);
    asm volatile("fence.mbarrier_init.release.cluster;" ::: "memory");
    fence_async_smem();
    stage_weights(sb + C_STG, &maps.w[rank], h * 128, 0, bars + B_W * 8);
    const int nt = rank == 2 ? 2 : 3;
    mbar_expect_tx(bars + B_WO * 8, nt * 16384);
    for (int tl = 0; tl < nt; tl++)
      asm volatile("cp.async.bulk.tensor.5d.shared::cluster.global.mbarrier::complete_tx::bytes [%0], [%1, {%3, 0, 0, 0, %4}], [%2];"
                   ::"r"(sb + C_WO + tl * 16384), "l"(&maps.wo), "r"(bars + B_WO * 8), "r"((tl * 3 + rank) * 64), "r"(h * 4) : "memory");
  }
  __syncwarp();
  asm volatile("barrier.cluster.arrive.relaxed.aligned;" ::: "memory");
  {
    const int gt = blockIdx.x * 512 + tid, g1 = gt - 12288, g2 = gt - 12288 - 16384, g3 = gt - 45056;
    static_assert(12288 + 16384 + sizeof(Flags) / 16 <= 45056, "reset");
    if (g1 < 0) ((uint4*)g_M)[gt / 3072 * 4096 + 256 + gt % 3072] = make_uint4(~0u, ~0u, ~0u, ~0u);
    else if (g2 < 0) ((uint4*)(g_part[1] + 32 * 8192))[g1] = make_uint4(0, 0, 0, 0);
    else if (g2 < (int)(sizeof(Flags) / 16)) ((uint4*)&g_fl)[g2] = make_uint4(0, 0, 0, 0);
    else if (g3 >= 0) ((uint4*)g_x2p[g3 >> 6][1])[g3 & 63] = make_uint4(~0u, ~0u, ~0u, ~0u);
    if ((NSTEP - 1) & 1) { ((uint4*)g_P)[gt] = make_uint4(0, 0, 0, 0); ((uint4*)g_P)[gt + 49152] = make_uint4(0, 0, 0, 0); }
#pragma unroll 1
    for (int i = 0; i < 4; i++) {
      if (i != 1 || w < 5) {
        const int row = i == 0 ? row2 : i == 1 ? row3 : (i - 2) * 16 + w;
        store_row_img(i < 2 ? g_xs[0] + (row >> 5) * 32768 : smem_raw + (sb - smem_u32(smem_raw)) + C_X, row & 31, lane, warp_ln(xr[0]));
      }
      xr[0] = xr[1]; xr[1] = xr[2]; xr[2] = xr[3];
    }
  }
  fence_async_smem();
  __syncthreads();
  asm volatile("barrier.cluster.wait.aligned;" ::: "memory");
  if (tid == 448) red_release(g_ex.ready);
  __syncwarp();
  if (w < 8) {
    reg_inc<184>();
    chain_proj(sb, w, lane, rank);
    TG(1)
    TRDUMP
    cluster_sync();
  } else if (w < 12) {
    reg_dec<120>();
    chain_mem(sb, w, lane, rank, h, mem0);
    STATDUMP
    TRDUMP
    cluster_sync();
  } else {
    reg_dec<24>();
    chain_dma(sb, w, lane, rank, h);
    TRDUMP
    cluster_sync();
  }
}
#undef TRC
#undef TRS

constexpr int K_BAR = 0, K_LN = 128, K_FH = 320, K_FS = 512, K_FY = 1536;
constexpr int K_W = 3072;
constexpr int K_O = K_W + 3 * 49152;
constexpr int K_ST = K_O + 65536;
constexpr int K_SMEM = K_ST + 16384;
static_assert(K_SMEM <= 232448, "shared memory");
enum { KB_FULL = 0, KB_EMPTY = 2, KB_OK = 4, KB_GO = 7, KB_ST = 10, KB_REL = 12, KB_W = 13 };
enum { KN_ST = 1, KN_ST1, KN_REL, KN_FFN, KN_INIT, KN_RES, KN_RES1, KN_CAND, KN_TAKEN, KN_FF2 };
#define GATE_R 850
struct WorkerParams {
  CUtensorMap wo;
  const bf16 *x0, *w_r, *w_gate, *w_up, *w_down;
  bf16* out;
};
#define TRC (96 + blockIdx.x)
#define FT(e)
#define QUIET 4700
__device__ __forceinline__ void quiet_until(uint32_t t) {
  int d;
  while ((d = (int)(t - clk32())) > 0) warp_sleep(min(d / 3 + 20, 1000));
}
#define FOR_UNITS _Pragma("unroll 1") for (int st = 0, n = 0; st < WSTEP; st++) \
                  _Pragma("unroll 1") for (int v = st < NSEG ? 0 : st < WSTEP - 1 ? 1 : 2, sg = v ? st - WD : st; v < (st >= WD ? 3 : 1); v++, n++, sg = st - WD)

template <int ACC>
__device__ __forceinline__ void wg_ss8(float (&d)[4], uint64_t da, uint64_t db) {
  asm volatile("wgmma.mma_async.sync.aligned.m64n8k16.f32.bf16.bf16 {%0,%1,%2,%3}, %4, %5, %6, 1, 1, 1, 0;" : O4(d, 0) : "l"(da), "l"(db), "n"(ACC));
}
template <int NU>
__device__ __forceinline__ void ffn_slice(uint32_t sb, int t, const bf16* yrow, int ev) {
  const int lane = t & 31, c = t >> 5;
  FT(1)
  {
    const uint2 r = ld_rlx64(yrow + t * 4);
    asm volatile("st.shared.v2.b32 [%0], {%1,%2};" ::"r"(sb + K_FY + ((t >> 1) & 31) * 32 + (t >> 6) * 16 + (t & 1) * 8), "r"(r.x), "r"(r.y) : "memory");
  }
  fence_async_smem();
  bar_sync(KN_FFN, 128);
  FT(2)
  {
    float g[NU][4];
    const uint64_t da = mk_desc(sb + K_W, 16384, 512, 2), db = mk_desc(sb + K_FY, 32, 0, 0);
    wg_fence();
#pragma unroll
    for (int i = 0; i < 16; i++)
#pragma unroll
      for (int u = 0; u < NU; u++) { if (i == 0) wg_ss8<0>(g[u], da + u * 3072, db); else wg_ss8<1>(g[u], da + u * 3072 + i * 64, db + i * 4); }
    wg_commit();
    wg_wait<0>();
#pragma unroll
    for (int u = 0; u < NU; u++) {
      acc_fence(g[u]);
      if ((lane & 3) == 0) {
        const uint32_t a = sb + K_FS + u * 256 + c * 64 + lane;
        sts32(a, __float_as_uint(c < 2 ? g[u][0] : g[u][1])); sts32(a + 32, __float_as_uint(c < 2 ? g[u][2] : g[u][3]));
      }
    }
  }
  FT(3)
  bar_sync(KN_FFN, 128);
  {
    const uint32_t pa = sb + K_FS + c * 256 + lane * 4;
    const float gt = round_bf16(__uint_as_float(lds32(pa)) + __uint_as_float(lds32(pa + 128)));
    const float up = __shfl_xor_sync(~0u, gt, 16);
    const uint32_t hv = pack_bf16(round_bf16(__fdividef(gt, 1.f + __expf(-gt))) * up, 0.f);
    if (lane < 16) asm volatile("st.shared.b16 [%0], %1;" ::"r"(sb + K_FH + (c * 16 + lane) * 2), "h"((unsigned short)hv) : "memory");
  }
  fence_async_smem();
  bar_sync(KN_FFN, 128);
  FT(4)
  float old[4];
#pragma unroll
  for (int hf = 0; hf < 2; hf++) {
    float o[4][4];
    const uint64_t da = mk_desc(sb + K_W + 32768 + hf * 8192, 16, 1024, 1), db = mk_desc(sb + K_FH, 16, 0, 0);
    wg_fence();
#pragma unroll
    for (int u = 0; u < NU; u++)
#pragma unroll
      for (int j = 0; j < 4; j++) { if (u == 0) wg_ss8<0>(o[j], da + j * 128, db); else wg_ss8<1>(o[j], da + u * 3072 + j * 128, db + u * 2); }
    wg_commit();
    wg_wait<0>();
    float lo = 0.f, hi = 0.f;
#pragma unroll
    for (int j = 0; j < 4; j++) {
      acc_fence(o[j]);
      const float a = __shfl_sync(~0u, o[j][0], lane & 28), b = __shfl_sync(~0u, o[j][2], lane & 28);
      if ((lane & 3) == j) { lo = a; hi = b; }
    }
    float* p = &g_fl.upd[ev][hf * 256 + (lane & 3) * 64 + c * 16 + (lane >> 2)];
    asm volatile("atom.relaxed.gpu.global.add.f32 %0, [%2], %3; atom.relaxed.gpu.global.add.f32 %1, [%2 + 32], %4;"
                 : "=f"(old[2 * hf]), "=f"(old[2 * hf + 1]) : "l"(p), "f"(lo), "f"(hi) : "memory");
  }
  sts32(sb + K_FY + t * 4, __float_as_uint((old[0] + old[1]) + (old[2] + old[3])));
  FT(5)
  bar_sync(KN_FFN, 128);
  if (t == 96) asm volatile("red.relaxed.gpu.global.add.u32 [%0], 1;" ::"l"(g_fl.ffncnt[ev]) : "memory");
  __syncwarp();
}
__device__ __forceinline__ uint4 pair_ln(uint4 r, float& e, uint32_t sl, int bar, int t) {
  const float x[8] = {bf_lo(r.x), bf_hi(r.x), bf_lo(r.y), bf_hi(r.y), bf_lo(r.z), bf_hi(r.z), bf_lo(r.w), bf_hi(r.w)};
  const float s = ((x[0] + x[1]) + (x[2] + x[3])) + ((x[4] + x[5]) + (x[6] + x[7]));
  const float q = (fmaf(x[0], x[0], x[1] * x[1]) + fmaf(x[2], x[2], x[3] * x[3])) + (fmaf(x[4], x[4], x[5] * x[5]) + fmaf(x[6], x[6], x[7] * x[7]));
  const bool u16 = t & 16, u8 = t & 8;
  const float a = (u16 ? q : s) + __shfl_xor_sync(~0u, u16 ? s : q, 16), b = e + __shfl_xor_sync(~0u, e, 16);
  float v = (u8 ? b : a) + __shfl_xor_sync(~0u, u8 ? a : b, 8);
  v += __shfl_xor_sync(~0u, v, 4); v += __shfl_xor_sync(~0u, v, 2); v += __shfl_xor_sync(~0u, v, 1);
  sts32(sl + (t >> 3) * 4, __float_as_uint(v));
  bar_sync(bar, 64);
  const uint4 s0 = lds128(sl), s1 = lds128(sl + 16);
  const float m = (__uint_as_float(s0.x) + __uint_as_float(s1.x)) * (1.f / DM), m2 = (__uint_as_float(s0.z) + __uint_as_float(s1.z)) * (1.f / DM);
  e = __uint_as_float(s0.y) + __uint_as_float(s1.y);
  float rs;
  asm("rsqrt.approx.ftz.f32 %0, %1;" : "=f"(rs) : "f"(fmaxf(fmaf(-m, m, m2), 0.f) + 1e-5f));
  return make_uint4(pack_bf16((x[0] - m) * rs, (x[1] - m) * rs), pack_bf16((x[2] - m) * rs, (x[3] - m) * rs),
                    pack_bf16((x[4] - m) * rs, (x[5] - m) * rs), pack_bf16((x[6] - m) * rs, (x[7] - m) * rs));
}
__device__ __forceinline__ uint32_t score_bits(float r) {
  const uint32_t b = pack_bf16(0.f, r);
  return (b & 0x80000000u) ? ~b : (b | 0x80000000u);
}

__global__ void __launch_bounds__(640, 1) worker_kernel(const __grid_constant__ WorkerParams prm) {
  extern __shared__ __align__(1024) uint8_t smem_raw[];
  const uint32_t sb = smem_u32(smem_raw);
  if (sb & 1023) __trap();
  const int tid = threadIdx.x, lane = tid & 31;
  const int w = __shfl_sync(~0u, tid >> 5, 0);
  const int me = blockIdx.x, kb = me >> 2, cb = me & 3;
  const bool full = me < 32;
  const uint32_t bars = sb + K_BAR;
  TG(0)
  if (tid == 0) {
    for (int i = 0; i < 2; i++) { mbar_init(bars + (KB_FULL + i) * 8, 1); mbar_init(bars + (KB_EMPTY + i) * 8, 1); }
    for (int i = 0; i < 10; i++) mbar_init(bars + (KB_OK + i) * 8, i < 3 ? 2 : 1);
    sts32(sb + K_LN + 144, 0);
    asm volatile("fence.mbarrier_init.release.cluster;" ::: "memory");
    fence_async_smem();
  }
  __syncwarp();
  if (w == 0) {
    wait_count(g_ex.ready, 96, 94);
    if (lane == 0 && full) stage_weights(sb + K_W, &prm.wo, cb * 128, kb * 512, bars + KB_W * 8);
  }
  __syncthreads();
  if (w < 8) {
    reg_inc<176>();
    if (full) {
      uint32_t wA[32][4];
      mbar_wait(bars + KB_W * 8, 0, 79);
      load_wfrags(wA, sb + K_W, w, lane);
      bar_arrive(KN_INIT, 384);
      const uint32_t sp = pin(sb + K_ST + ((lane >> 4) * 8 + (lane & 7)) * 256 + (((2 * w + ((lane >> 3) & 1)) ^ (lane & 7)) << 4));
      const uint32_t tm = pin(lane < 4 ? 0x00010001u : 0u);
      FOR_UNITS {
        float d[16];
        mbar_wait(bars + (KB_FULL + (n & 1)) * 8, (n >> 1) & 1, 81);
        TR(4 * v)
        const uint64_t db = mk_desc(sb + K_O + (n & 1) * 32768, 128, 2048, 0);
        wg_fence();
#pragma unroll
        for (int ks = 0; ks < 32; ks++) {
          if (ks == 0) wg_rs32<0, 0>(d, wA[ks], db);
          else wg_rs32<0, 1>(d, wA[ks], db + (ks >> 3) * 512 + (ks & 7) * 16);
        }
        wg_commit();
        mbar_wait(bars + (KB_ST + (n & 1)) * 8, ((n >> 1) & 1) ^ 1, 82);
        wg_wait<0>();
        acc_fence(d);
        TR(4 * v + 1)
        const uint32_t tag = (sg & 2) ? 0u : tm;
        uint32_t pk[8];
#pragma unroll
        for (int i = 0; i < 8; i++) pk[i] = (pack_bf16(d[2 * i], d[2 * i + 1]) & ~tm) | tag;
        stsm4t(sp + (n & 1) * 8192, pk[0], pk[1], pk[2], pk[3]);
        stsm4t(sp + (n & 1) * 8192 + 4096, pk[4], pk[5], pk[6], pk[7]);
        bar_arrive(KN_ST + (n & 1), 288);
        TR(4 * v + 2)
      }
    }
  } else if (w < 12) {
    reg_dec<56>();
    if (full) {
      const int ly = (w >> 1) & 1, t = pin(tid & 63);
      const uint32_t so = pin((t >> 4) * 8192 + me * 256 + (((t & 15) ^ (me & 7)) << 4));
      int sstar = -1;
      uint32_t sl = sb + K_LN + ly * 64;
      float rr = 0.f;
      int kprev = -1;
      auto records = [&](int sg, uint32_t off) {
        int it = 0;
        while (__any_sync(~0u, (int)lds32_poll(sb + K_LN + 144) <= sg)) { give_up(++it, SPIN_LIMIT, 86); warp_sleep(50); }
        return lds32_poll(sb + K_LN + off);
      };
#pragma unroll 1
      for (int n = ly ? 2 * WD : 0; n < 2 * WSTEP; n++) {
        const int st = n >> 1, v = (n & 1) ? 2 : ly, sg = v ? st - WD : st, tok = sg * 32 + me;
        if (n == 2 * NSEG) bar_sync(KN_INIT, 128);
        if (n == 2 * NSEG + 2) sstar = records(NSEG - 1, 156);
        if (v == 2 ? sg < 0 || (st < NSEG ? st & 1 : 0) != ly : sg >= NSEG - v) continue;
        const bf16* xin = v ? g_rows[tok][0][2] : prm.x0 + tok * DM;
        if (v == 2 && ((records(sg, 148 + (sg >> 5) * 4) >> (sg & 31)) & 1)) xin = g_x2p[sg][0];
        const uint8_t* src = g_part[v] + (sg & 1) * (32 * 8192) + so;
        const uint32_t flip = (sg & 2) ? ~0u : 0u;
        mbar_wait(bars + (KB_GO + v) * 8, sg & 1, 87);
        TR(4 * v)
        uint4 p[8], x;
        int it = 0;
#pragma unroll 1
        do {
#pragma unroll
          for (int k = 0; k < 8; k++) p[k] = ld_rlx128(src + k * 32768);
          x = ld_rlx128(((WEXP & 2) ? prm.x0 : xin) + t * 8);
          give_up(it++, SPIN_LIMIT, 85);
        } while (__builtin_expect(!__all_sync(~0u, (int)and3(and3(and_x(p[0].x, p[1].x, flip), and_x(p[2].x, p[3].x, flip), 1u),
                                                             and_x(p[4].x, p[5].x, flip), and_x(p[6].x, p[7].x, flip))), 0));
        mbar_arrive_z(bars + (KB_OK + v) * 8, t & 31);
#define P8(h, f) (((h(p[0].f) + h(p[1].f)) + (h(p[2].f) + h(p[3].f))) + ((h(p[4].f) + h(p[5].f)) + (h(p[6].f) + h(p[7].f))))
#define X8(f) x.f = add_bf16x2(x.f, pack_bf16(P8(bf_lo, f), P8(bf_hi, f)));
        X8(x) X8(y) X8(z) X8(w)
#undef X8
#undef P8
        TRV(12 + v, it - 1)
        TR(4 * v + 1)
        bf16* dst = g_rows[tok][v][0] + t * 8;
        *(uint4*)dst = x;
        const uint4 wr = ld_rlx128(prm.w_r + t * 8);
        sl ^= 32;
        uint4 y = pair_ln(x, rr, sl, KN_RES + ly, t);
        *(uint4*)(dst + DM) = y;
        x = make_uint4(add_bf16x2(x.x, y.x), add_bf16x2(x.y, y.y), add_bf16x2(x.z, y.z), add_bf16x2(x.w, y.w));
        *(uint4*)(v == (sg < sstar ? 1 : 2) ? prm.out + tok * DM + t * 8 : dst + 2 * DM) = x;
        asm volatile("{ .reg .pred p; setp.eq.u32 p, %2, 0; @p st.relaxed.gpu.global.u64 [%0], %1; }" ::"l"(&g_fl.key[0][0][0] + max(kprev, 0)),
                     "l"((u64)score_bits(rr) << 32 | (uint32_t)~(kprev & (NTOK - 1))), "r"(t | (kprev < 0)) : "memory");
        kprev = v * NTOK + tok;
        rr = (fmaf(bf_lo(y.x), bf_lo(wr.x), bf_hi(y.x) * bf_hi(wr.x)) + fmaf(bf_lo(y.y), bf_lo(wr.y), bf_hi(y.y) * bf_hi(wr.y))) +
             (fmaf(bf_lo(y.z), bf_lo(wr.z), bf_hi(y.z) * bf_hi(wr.z)) + fmaf(bf_lo(y.w), bf_lo(wr.w), bf_hi(y.w) * bf_hi(wr.w)));
        if (v == 0 || st >= NSEG) {
          sl ^= 32;
          y = pair_ln(x, rr, sl, KN_RES + ly, t);
          if (v == 0) *(uint4*)(g_xs[1] + sg * 32768 + (t >> 3) * 4096 + me * 128 + (((t ^ me) & 7) << 4)) = y;
          sts32(sb + K_LN + 128 + ly * 4, score_bits(rr));
          bar_arrive(KN_REL, v == 0 || st == WSTEP - 1 ? 96 : 160);
          kprev = -1;
        }
        TR(4 * v + 2)
      }
    }
  } else if (w < 16) {
    reg_dec<48>();
    const int t = tid - 384, nu = full ? 3 : 4;
    if (full) bar_sync(KN_INIT, 384);
    {
      const int j0 = (full ? me * 3 : 96 + (me - 32) * 4) * 16;
#pragma unroll 1
      for (int i = t; i < nu * 3072; i += 128) {
        const int u = i / 3072, r = i - u * 3072;
        const int q = (r ^ (r >> 3)) & 3, r2 = r - 2048;
        const bf16* src = r < 2048 ? ((q & 2) ? prm.w_up : prm.w_gate) + (size_t)(r >> 2) * FF + j0 + u * 16 + (q & 1) * 8
                                   : prm.w_down + (size_t)(j0 + u * 16 + ((r2 >> 3) & 15)) * DM + (r2 >> 7) * 64 + ((r2 ^ (r2 >> 3)) & 7) * 8;
        cp16(sb + K_W + i * 16, src);
      }
      asm volatile("cp.async.wait_all;" ::: "memory");
    }
    bar_arrive(KN_TAKEN, 160);
#pragma unroll 1
    while (true) {
      bar_sync(KN_CAND, 160);
      const uint4 cand = lds128(sb + K_LN + 160);
      const u64 k = (u64)cand.y << 32 | cand.x;
      const int ev = cand.z, ver = cand.w & 3, tok = key_token(k);
      const bool last = cand.w & 4;
      if (!last) {
        bar_arrive(KN_TAKEN, 160);
        FT(0)
        if (full) ffn_slice<3>(sb, t, g_rows[tok][ver][1], ev); else ffn_slice<4>(sb, t, g_rows[tok][ver][1], ev);
      }
      if ((tok & 31) == me && (ver == 0 || last)) {
        if (t < 64) {
          FT(6)
          uint4 x = ld_rlx128(g_rows[tok][ver][0] + t * 8);
          const uint4 y = ld_rlx128(g_rows[tok][ver][1] + t * 8);
          const float sig = round_bf16(__fdividef(1.f, 1.f + __expf(-key_score(k))));
          int it = 0;
          while (ld_rlx32(g_fl.ffncnt[ev]) < NWORK) { give_up(++it, SPIN_LIMIT, 80); warp_sleep(40); }
          uint4 u0, u1;
          asm volatile("atom.relaxed.gpu.global.add.v4.f32 {%0,%1,%2,%3}, [%8], {%9,%9,%9,%9}; atom.relaxed.gpu.global.add.v4.f32 {%4,%5,%6,%7}, [%8 + 16], {%9,%9,%9,%9};"
                       : "=r"(u0.x), "=r"(u0.y), "=r"(u0.z), "=r"(u0.w), "=r"(u1.x), "=r"(u1.y), "=r"(u1.z), "=r"(u1.w) : "l"(&g_fl.upd[ev][t * 8]), "r"(0) : "memory");
          auto upd = [&](uint32_t xw, uint32_t yw, uint32_t a, uint32_t b) {
            const uint32_t r = pack_bf16(__uint_as_float(a), __uint_as_float(b));
            return add_bf16x2(xw, add_bf16x2(yw, pack_bf16(bf_lo(r) * sig, bf_hi(r) * sig)));
          };
          x = make_uint4(upd(x.x, y.x, u0.x, u0.y), upd(x.y, y.y, u0.z, u0.w), upd(x.z, y.z, u1.x, u1.y), upd(x.w, y.w, u1.z, u1.w));
          FT(7)
          *(uint4*)((ver ? prm.out + tok * DM : g_x2p[ev][0]) + t * 8) = x;
          if (ver == 0) {
            float e = 0.f;
            *(uint4*)(g_x2p[ev][1] + t * 8) = pair_ln(x, e, sb + K_FS, KN_FF2, t);
          }
        }
      }
      if (ev == NSEG && !last && full) {
        const int nc = min((int)lds32(sb + K_LN + 156), NSEG + 1 - WD);
#pragma unroll 1
        for (int s0 = (t >> 6) * 4; s0 < nc; s0 += 8) {
          uint4 q[4];
#pragma unroll
          for (int i = 0; i < 4; i++) q[i] = ld_rlx128(g_rows[min(s0 + i, nc - 1) * 32 + me][1][2] + (t & 63) * 8);
#pragma unroll
          for (int i = 0; i < 4; i++) *(uint4*)(prm.out + (min(s0 + i, nc - 1) * 32 + me) * DM + (t & 63) * 8) = q[i];
        }
      }
      FT(8)
      if (last) break;
    }
  } else {
    reg_dec<24>();
    if (w == 16) {
      u64 best = 0, mask = 0;
      int sstar = 0;
      uint32_t ver = 0, ev = 0;
      auto post = [&](uint32_t cmd) {
        bar_sync(KN_TAKEN, 160);
        sts128(sb + K_LN + 160, make_uint4((uint32_t)best, (uint32_t)(best >> 32), ev, ver | cmd));
        bar_arrive(KN_CAND, 160);
      };
      u64 accn = 0, acca = 0;
      uint32_t recs = 0;
      int j = 0;
      uint32_t tq = clk32();
#pragma unroll 1
      for (int st = 0; st < WSTEP; st++) {
        const u64* keys = st < NSEG ? g_fl.key[0][st] : g_fl.key[2][st - WD];
        const bool early = __any_sync(~0u, ld_rlx32(keys + lane) == 0);
        if (early && st < NSEG) quiet_until(tq);
        u64 k = wait_keys(keys, lane, 91);
        if (early) tq = clk32() + QUIET;
        if (st < NSEG) {
          const bool rec = k > best;
          recs &= ~(1u << (st & 31));
          if (rec) {
            best = k; ev = sstar = st;
            recs |= 1u << (st & 31);
            if ((key_token(k) & 31) == me) mask |= 1ull << st;
          }
          if (lane == 0) sts128(sb + K_LN + 144, make_uint4(st + 1, (uint32_t)mask, (uint32_t)(mask >> 32), sstar));
          __syncwarp();
          if (rec) post(0);
        }
#pragma unroll 1
        for (; j <= st - WD - (st < NSEG ? 2 : 0); j++) {
          u64 kn = 1, kc;
          int it = 0;
          do {
            if (j < NSEG - 1) asm volatile("ld.relaxed.gpu.global.u64 %0, [%1];" : "=l"(kn) : "l"(&g_fl.key[1][j][lane]) : "memory");
            asm volatile("ld.relaxed.gpu.global.u64 %0, [%1];" : "=l"(kc) : "l"(&g_fl.key[2][j][lane]) : "memory");
            give_up(it++, SPIN_LIMIT, 92);
          } while (__any_sync(~0u, kn == 0 || kc == 0));
          if ((recs >> (j & 31)) & 1) acca = accn;
          if (kc > acca) acca = kc;
          if (kn > accn) accn = kn;
        }
        if (st >= NSEG) {
          const u64 m = j <= sstar ? accn : acca;
          const uint32_t hi = __reduce_max_sync(~0u, (uint32_t)(m >> 32));
          k = (u64)hi << 32 | __reduce_max_sync(~0u, (uint32_t)(m >> 32) == hi ? (uint32_t)m : 0u);
          if (st == NSEG || k != best) {
            best = k; ev = st;
            ver = (key_token(k) >> 5) < sstar ? 1 : 2;
            post(0);
          }
        }
      }
      HD(6)
      post(4);
      if (me == 0 && lane == 0) st_rlx32(g_ex.ready, 0);
    } else if (!full) {
    } else if (w == 17) {
      uint32_t tq = clk32();
      FOR_UNITS {
        if (ld_rlx32(&g_fl.oflag[v][sg][kb]) < 4) {
          if (v == (st < NSEG ? 0 : 1) && st < WSTEP - 3) quiet_until(tq);
          wait_count(&g_fl.oflag[v][sg][kb], 4, 84);
          if (v == (st < NSEG ? 0 : 1)) tq = clk32() + QUIET;
        }
        mbar_wait(bars + (KB_EMPTY + (n & 1)) * 8, ((n >> 1) & 1) ^ 1, 83);
        TR(v)
        if (st == WSTEP - 1) { HD(v) }
        if (lane == 0) {
          fence_async_glb();
          mbar_expect_tx(bars + (KB_FULL + (n & 1)) * 8, (WEXP & 4) ? 4096 : 32768);
          bulk_g2s(sb + K_O + (n & 1) * 32768, g_O[(v ? sg + DELTA : sg) & (OSLOTS - 1)][v] + kb * 32768, (WEXP & 4) ? 4096 : 32768, bars + (KB_FULL + (n & 1)) * 8);
        }
        __syncwarp();
      }
    } else if (w == 18) {
      FOR_UNITS {
        if (sg > 0) mbar_wait(bars + (KB_OK + v) * 8, (sg - 1) & 1, 90);
        bar_sync(KN_ST + (n & 1), 288);
        fence_async_smem();
        const uint32_t tg = clk32() + GATE_R;
        if (lane == 0) {
          bulk_s2g(g_part[v] + ((sg & 1) * 32 + me) * 8192, sb + K_ST + (n & 1) * 8192, 8192);
          asm volatile("cp.async.bulk.commit_group;" ::: "memory");
          mbar_arrive_z(bars + (KB_EMPTY + (n & 1)) * 8, 0);
          asm volatile("cp.async.bulk.wait_group.read 0;" ::: "memory");
        }
        __syncwarp();
        mbar_arrive_z(bars + (KB_ST + (n & 1)) * 8, lane);
        TR(v)
        if (v == (st < NSEG ? 0 : st < WSTEP - 1 ? 1 : 2) && st > 0) mbar_wait(bars + KB_REL * 8, (st - 1) & 1, 93);
        wait_clock(tg);
        if (st == WSTEP - 1) { HD(2 + v) }
        mbar_arrive_z(bars + (KB_GO + v) * 8, lane);
      }
    } else {
#pragma unroll 1
      for (int st = 0; st < WSTEP; st++) {
        const int sg = st < NSEG ? st : st - WD;
        const bool both = st >= NSEG && st < WSTEP - 1;
        bar_sync(KN_REL, both ? 160 : 96);
        const uint32_t ob = __shfl_sync(~0u, lds32(sb + K_LN + 128), 0), obn = __shfl_sync(~0u, lds32(sb + K_LN + 132), 0);
        mbar_arrive_z(bars + KB_REL * 8, lane);
        if (st == WSTEP - 1) { HD(5) }
        if (lane == 0) {
          if (both) asm volatile("st.relaxed.gpu.global.u64 [%0], %1;" ::"l"(&g_fl.key[1][sg][me]), "l"((u64)obn << 32 | (uint32_t)~(sg * 32 + me)) : "memory");
          st_release_u64(&g_fl.key[st < NSEG ? 0 : 2][sg][me], (u64)ob << 32 | (uint32_t)~(sg * 32 + me));
        }
        __syncwarp();
        TR(0)
      }
    }
  }
}
#undef TRC

typedef CUresult (*EncodeFn)(CUtensorMap*, CUtensorMapDataType, cuuint32_t, void*, const cuuint64_t*, const cuuint64_t*,
                             const cuuint32_t*, const cuuint32_t*, CUtensorMapInterleave, CUtensorMapSwizzle,
                             CUtensorMapL2promotion, CUtensorMapFloatOOBfill);
void make_map(EncodeFn fn, CUtensorMap* m, const void* ptr, int rank, const cuuint64_t* dims, const cuuint64_t* strides, const cuuint32_t* box) {
  const cuuint32_t es[5] = {1, 1, 1, 1, 1};
  fn(m, CU_TENSOR_MAP_DATA_TYPE_BFLOAT16, rank, (void*)ptr, dims, strides, box, es, CU_TENSOR_MAP_INTERLEAVE_NONE,
     CU_TENSOR_MAP_SWIZZLE_128B, CU_TENSOR_MAP_L2_PROMOTION_L2_256B, CU_TENSOR_MAP_FLOAT_OOB_FILL_NONE);
}
struct HostState {
  const void* key[4];
  ChainMaps cm;
  CUtensorMap wo;
};
HostState g_hs;

}

extern "C" void kernel_launch(void* const* d_in, const int* in_sizes, int n_in, void* d_out, int out_size) {
  (void)in_sizes; (void)n_in; (void)out_size;
  HostState& hs = g_hs;
  if (hs.key[0] != d_in[2] || hs.key[1] != d_in[3] || hs.key[2] != d_in[4] || hs.key[3] != d_in[5]) {
    void* fnp = nullptr;
    cudaDriverEntryPointQueryResult qr;
    cudaGetDriverEntryPoint("cuTensorMapEncodeTiled", &fnp, cudaEnableDefault, &qr);
    const cuuint32_t box[2] = {64, 256}, box5[5] = {64, 2, 4, 4, 4};
    const cuuint64_t dw[2] = {HD, DM}, sw[1] = {HD * 2}, dwo[2] = {DM, HD}, swo[1] = {DM * 2};
    const cuuint64_t d5[5] = {DM, 2, 4, 4, HD / 32}, s5[4] = {DM * 2, 8 * DM * 2, 2 * DM * 2, 32 * DM * 2};
    for (int i = 0; i < 3; i++) make_map((EncodeFn)fnp, &hs.cm.w[i], d_in[2 + i], 2, dw, sw, box);
    make_map((EncodeFn)fnp, &hs.cm.wo, d_in[5], 5, d5, s5, box5);
    make_map((EncodeFn)fnp, &hs.wo, d_in[5], 2, dwo, swo, box);
    cudaFuncSetAttribute(worker_kernel, cudaFuncAttributeMaxDynamicSharedMemorySize, K_SMEM);
    cudaFuncSetAttribute(chain_kernel, cudaFuncAttributeMaxDynamicSharedMemorySize, C_SMEM);
    for (int i = 0; i < 4; i++) hs.key[i] = d_in[2 + i];
  }
  cudaStream_t st = cudaStreamPerThread;
  WorkerParams wp;
  wp.wo = hs.wo; wp.x0 = (const bf16*)d_in[0]; wp.w_r = (const bf16*)d_in[8]; wp.w_gate = (const bf16*)d_in[9];
  wp.w_up = (const bf16*)d_in[10]; wp.w_down = (const bf16*)d_in[11]; wp.out = (bf16*)d_out;
  chain_kernel<<<96, 512, C_SMEM, st>>>(hs.cm, (const bf16*)d_in[1], wp.x0);
  cudaLaunchAttribute pdl[1];
  pdl[0].id = cudaLaunchAttributeProgrammaticStreamSerialization;
  pdl[0].val.programmaticStreamSerializationAllowed = 1;
  cudaLaunchConfig_t cfg = {};
  cfg.gridDim = dim3(NWORK); cfg.blockDim = dim3(640); cfg.dynamicSmemBytes = K_SMEM; cfg.stream = st;
  cfg.attrs = pdl; cfg.numAttrs = 1;
  cudaLaunchKernelEx(&cfg, worker_kernel, wp);
}
```

```cpp
#include <cuda_runtime.h>
#include <cuda_bf16.h>
#include <cuda.h>
#include <stdint.h>

namespace {

typedef __nv_bfloat16 bf16;
typedef unsigned long long u64;

constexpr int NTOK = 2048, DM = 512, HD = 4096, NSEG = 64, FF = 1792;
#define DELTA 5
constexpr int NSTEP = NSEG + DELTA;
#define WLAG 1
constexpr int WD = DELTA + WLAG, WSTEP = NSEG + WD;
constexpr int SPIN_LIMIT = 40000;
constexpr int MBAR_LIMIT = 20000;
constexpr int NWORK = 36;
constexpr int OSLOTS = 8;
#define SLP_C 100
#define SLP_K 200
#define WEXP 0

__device__ __align__(1024) uint8_t g_xs[2][NSEG * 32768];
__device__ __align__(1024) uint8_t g_O[OSLOTS][3][32 * 8192];
__device__ __align__(1024) uint8_t g_part[3][2 * 32 * 8192];
__device__ __align__(1024) bf16 g_rows[NTOK][3][3][DM];
__device__ __align__(1024) bf16 g_x2p[NSEG][2][DM];
struct Flags {
  uint32_t pol[96];
  uint32_t stamp[96];
  uint32_t oflag[3][NSEG][8];
  uint32_t ffncnt[WSTEP][8];
  u64 key[3][NSEG][32];
  float upd[WSTEP][DM];
};
struct Exchange { uint32_t M[4 * 16384], P[96 * 4096]; Flags fl; uint32_t ready[32]; };
__device__ __align__(65536) Exchange g_ex;
#define g_M g_ex.M
#define g_P g_ex.P
#define g_fl g_ex.fl
#define TR(e)
#define TRV(e, v)
#define TG(i)
#define HD(e)
#define TRDUMP
#define TREXTRA 0

#define STAT(e, v)
#define STATC(n)
#define STATDUMP
__device__ __forceinline__ uint32_t smem_u32(const void* p) { return (uint32_t)__cvta_generic_to_shared(p); }
__device__ __forceinline__ uint32_t pack_bf16(float lo, float hi) {
  uint32_t r;
  asm("cvt.rn.bf16x2.f32 %0, %1, %2;" : "=r"(r) : "f"(hi), "f"(lo));
  return r;
}
__device__ __forceinline__ float bf_lo(uint32_t v) { return __uint_as_float(v << 16); }
__device__ __forceinline__ float bf_hi(uint32_t v) { return __uint_as_float(v & 0xffff0000u); }
__device__ __forceinline__ float ex2_fast(float x) { float y; asm("ex2.approx.ftz.f32 %0, %1;" : "=f"(y) : "f"(x)); return y; }
__device__ __forceinline__ float round_bf16(float x) { return __bfloat162float(__float2bfloat16_rn(x)); }
__device__ __forceinline__ uint32_t clk32() { uint32_t t; asm volatile("mov.u32 %0, %%clock;" : "=r"(t) :: "memory"); return t; }

__device__ __forceinline__ void mma16816(float (&d)[4], uint32_t a0, uint32_t a1, uint32_t a2, uint32_t a3,
                                         uint32_t b0, uint32_t b1) {
  asm("mma.sync.aligned.m16n8k16.row.col.f32.bf16.bf16.f32 {%0,%1,%2,%3}, {%4,%5,%6,%7}, {%8,%9}, {%0,%1,%2,%3};"
      : "+f"(d[0]), "+f"(d[1]), "+f"(d[2]), "+f"(d[3])
      : "r"(a0), "r"(a1), "r"(a2), "r"(a3), "r"(b0), "r"(b1));
}
__device__ __forceinline__ void ldsm4t(uint32_t (&r)[4], uint32_t addr) {
  asm volatile("ldmatrix.sync.aligned.m8n8.x4.trans.shared.b16 {%0,%1,%2,%3}, [%4];"
               : "=r"(r[0]), "=r"(r[1]), "=r"(r[2]), "=r"(r[3]) : "r"(addr) : "memory");
}
__device__ __forceinline__ void stsm4(uint32_t addr, uint32_t a, uint32_t b, uint32_t c, uint32_t d) {
  asm volatile("stmatrix.sync.aligned.m8n8.x4.shared.b16 [%0], {%1,%2,%3,%4};" ::"r"(addr), "r"(a), "r"(b), "r"(c), "r"(d) : "memory");
}
__device__ __forceinline__ void stsm4t(uint32_t addr, uint32_t a, uint32_t b, uint32_t c, uint32_t d) {
  asm volatile("stmatrix.sync.aligned.m8n8.x4.trans.shared.b16 [%0], {%1,%2,%3,%4};" ::"r"(addr), "r"(a), "r"(b), "r"(c), "r"(d) : "memory");
}
__device__ __forceinline__ uint4 lds128(uint32_t a) {
  uint4 v; asm volatile("ld.shared.v4.b32 {%0,%1,%2,%3}, [%4];" : "=r"(v.x), "=r"(v.y), "=r"(v.z), "=r"(v.w) : "r"(a) : "memory"); return v;
}
__device__ __forceinline__ uint32_t lds32(uint32_t a) { uint32_t v; asm volatile("ld.shared.b32 %0, [%1];" : "=r"(v) : "r"(a) : "memory"); return v; }
__device__ __forceinline__ uint32_t lds32_poll(uint32_t a) { uint32_t v; asm volatile("ld.volatile.shared.b32 %0, [%1];" : "=r"(v) : "r"(a) : "memory"); return v; }
__device__ __forceinline__ void sts32(uint32_t a, uint32_t x) { asm volatile("st.shared.b32 [%0], %1;" ::"r"(a), "r"(x) : "memory"); }
__device__ __forceinline__ void sts128(uint32_t a, uint4 v) {
  asm volatile("st.shared.v4.b32 [%0], {%1,%2,%3,%4};" ::"r"(a), "r"(v.x), "r"(v.y), "r"(v.z), "r"(v.w) : "memory");
}
__device__ __forceinline__ void cp16(uint32_t dst, const void* src) {
  asm volatile("cp.async.cg.shared.global [%0], [%1], 16;" ::"r"(dst), "l"(src) : "memory");
}
__device__ __forceinline__ void mbar_init(uint32_t mbar, uint32_t cnt) {
  asm volatile("mbarrier.init.shared.b64 [%0], %1;" ::"r"(mbar), "r"(cnt) : "memory");
}
__device__ __forceinline__ void mbar_expect_tx(uint32_t mbar, uint32_t bytes) {
  asm volatile("mbarrier.arrive.expect_tx.shared.b64 _, [%0], %1;" ::"r"(mbar), "r"(bytes) : "memory");
}
__device__ __forceinline__ void mbar_arrive_z(uint32_t mbar, uint32_t z) {
  asm volatile("{ .reg .pred p; setp.eq.u32 p, %1, 0; @p mbarrier.arrive.shared.b64 _, [%0]; }" ::"r"(mbar), "r"(z) : "memory");
}
__device__ __forceinline__ void mbar_expect_tx_z(uint32_t mbar, uint32_t bytes, uint32_t z) {
  asm volatile("{ .reg .pred p; setp.eq.u32 p, %2, 0; @p mbarrier.arrive.expect_tx.shared.b64 _, [%0], %1; }" ::"r"(mbar), "r"(bytes), "r"(z) : "memory");
}
__device__ __forceinline__ void mbar_arrive_remote_z(uint32_t mbar, uint32_t z) {
  asm volatile("{ .reg .pred p; setp.eq.u32 p, %1, 0; @p mbarrier.arrive.shared::cluster.b64 _, [%0]; }" ::"r"(mbar), "r"(z) : "memory");
}
__device__ __forceinline__ void warp_sleep(uint32_t ns) { __nanosleep(ns); __syncwarp(); }
__device__ __forceinline__ void fail(int) { __trap(); }
__device__ __forceinline__ void give_up(int it, int limit, int code) { if (it > limit) fail(code); }
__device__ __forceinline__ void mbar_wait(uint32_t mbar, uint32_t par, int code) {
  asm volatile("{ .reg .pred p; .reg .b32 n; mov.b32 n, %2;\n"
               "W: mbarrier.try_wait.parity.shared::cta.b64 p, [%0], %1; @p bra D;\n"
               "add.s32 n, n, -1; setp.eq.s32 p, n, 0; @p trap; bra W;\n"
               "D: }" ::"r"(mbar), "r"(par), "n"(MBAR_LIMIT) : "memory");
}
__device__ __forceinline__ void bulk_g2s(uint32_t dst, const void* src, uint32_t bytes, uint32_t mbar) {
  asm volatile("cp.async.bulk.shared::cluster.global.mbarrier::complete_tx::bytes [%0], [%1], %2, [%3];"
               ::"r"(dst), "l"(src), "r"(bytes), "r"(mbar) : "memory");
}
__device__ __forceinline__ void bulk_s2r(uint32_t dst, uint32_t src, uint32_t bytes, uint32_t mbar) {
  asm volatile("cp.async.bulk.shared::cluster.shared::cta.mbarrier::complete_tx::bytes [%0], [%1], %2, [%3];"
               ::"r"(dst), "r"(src), "r"(bytes), "r"(mbar) : "memory");
}
__device__ __forceinline__ void bulk_s2g(void* dst, uint32_t src, uint32_t bytes) {
  asm volatile("cp.async.bulk.global.shared::cta.bulk_group [%0], [%1], %2;" ::"l"(dst), "r"(src), "r"(bytes) : "memory");
}
__device__ __forceinline__ void fence_async_smem() { asm volatile("fence.proxy.async.shared::cta;" ::: "memory"); }
__device__ __forceinline__ void fence_async_glb() { asm volatile("fence.proxy.async.global;" ::: "memory"); }
__device__ __forceinline__ void bar_sync(int id, int n) { asm volatile("bar.sync %0, %1;" ::"r"(id), "r"(n) : "memory"); }
__device__ __forceinline__ void bar_arrive(int id, int n) { asm volatile("bar.arrive %0, %1;" ::"r"(id), "r"(n) : "memory"); }
__device__ __forceinline__ void cluster_sync() { asm volatile("barrier.cluster.arrive.release; barrier.cluster.wait.acquire;" ::: "memory"); }
__device__ __forceinline__ uint32_t mapa_u32(uint32_t a, uint32_t r) {
  uint32_t o;
  asm("mapa.shared::cluster.u32 %0, %1, %2;" : "=r"(o) : "r"(a), "r"(r));
  return o;
}
template <int OFF>
__device__ __forceinline__ void st_async32(uint32_t a, uint32_t x, uint32_t mbar) {
  asm volatile("st.async.weak.shared::cluster.mbarrier::complete_tx::bytes.b32 [%0 + %3], %1, [%2];" ::"r"(a), "r"(x), "r"(mbar), "n"(OFF) : "memory");
}
__device__ __forceinline__ uint4 ld_rlx128(const void* p) {
  uint4 v;
  asm volatile("ld.relaxed.gpu.global.v4.u32 {%0,%1,%2,%3}, [%4];" : "=r"(v.x), "=r"(v.y), "=r"(v.z), "=r"(v.w) : "l"(p) : "memory");
  return v;
}
__device__ __forceinline__ uint2 ld_rlx64(const void* p) {
  uint2 v; asm volatile("ld.relaxed.gpu.global.v2.u32 {%0,%1}, [%2];" : "=r"(v.x), "=r"(v.y) : "l"(p) : "memory"); return v;
}
__device__ __forceinline__ uint32_t ld_rlx32(const void* p) {
  uint32_t v; asm volatile("ld.relaxed.gpu.global.u32 %0, [%1];" : "=r"(v) : "l"(p) : "memory"); return v;
}
__device__ __forceinline__ void st_rlx32(void* p, uint32_t a) { asm volatile("st.relaxed.gpu.global.u32 [%0], %1;" ::"l"(p), "r"(a) : "memory"); }
__device__ __forceinline__ void red_release(uint32_t* p) { asm volatile("red.release.gpu.global.add.u32 [%0], 1;" ::"l"(p) : "memory"); }
__device__ __forceinline__ void st_release_u64(void* p, u64 a) { asm volatile("st.release.gpu.global.u64 [%0], %1;" ::"l"(p), "l"(a) : "memory"); }
__device__ __forceinline__ uint32_t poll32(const uint32_t* p) {
  uint32_t v = 0;
  asm volatile("{ .reg .pred p; setp.eq.u32 p, %2, 0; @p atom.relaxed.gpu.global.or.b32 %0, [%1], 0; }" : "+r"(v) : "l"(p), "r"(threadIdx.x & 31) : "memory");
  return __shfl_sync(~0u, v, 0);
}
__device__ __forceinline__ void wait_count(const uint32_t* p, uint32_t val, int code) {
  int it = 0;
  while (poll32(p) < val) {
    give_up(++it, SPIN_LIMIT, code);
    warp_sleep(SLP_C);
  }
}
template <bool ATOM>
__device__ __forceinline__ u64 wait_keys(const u64* keys, int lane, int code) {
  u64 k;
  int it = 0;
  while (true) {
    if (ATOM) asm volatile("atom.relaxed.gpu.global.or.b64 %0, [%1], 0;" : "=l"(k) : "l"(keys + lane) : "memory");
    else
    asm volatile("ld.relaxed.gpu.global.u64 %0, [%1];" : "=l"(k) : "l"(keys + lane) : "memory");
    if (__all_sync(~0u, k != 0)) break;
    give_up(++it, SPIN_LIMIT, code);
    warp_sleep(SLP_K);
  }
  const uint32_t hi = __reduce_max_sync(~0u, (uint32_t)(k >> 32));
  const uint32_t lo = __reduce_max_sync(~0u, (uint32_t)(k >> 32) == hi ? (uint32_t)k : 0u);
  return (u64)hi << 32 | lo;
}
__device__ __forceinline__ int key_token(u64 k) { return (int)(~(uint32_t)k) & (NTOK - 1); }
__device__ __forceinline__ float key_score(u64 k) {
  const uint32_t ob = (uint32_t)(k >> 32);
  return __uint_as_float((ob & 0x80000000u) ? (ob & 0x7fffffffu) : ~ob);
}

__device__ __forceinline__ uint64_t mk_desc(uint32_t saddr, uint32_t lbo, uint32_t sbo, uint32_t sw) {
  return (uint64_t)((saddr & 0x3FFFF) >> 4) | (uint64_t)(lbo >> 4) << 16 | (uint64_t)(sbo >> 4) << 32 | (uint64_t)sw << 62;
}
template <int N> __device__ __forceinline__ void reg_inc() { asm volatile("setmaxnreg.inc.sync.aligned.u32 %0;" ::"n"(N)); }
template <int N> __device__ __forceinline__ void reg_dec() { asm volatile("setmaxnreg.dec.sync.aligned.u32 %0;" ::"n"(N)); }
__device__ __forceinline__ void wg_fence() { asm volatile("wgmma.fence.sync.aligned;" ::: "memory"); }
__device__ __forceinline__ void wg_commit() { asm volatile("wgmma.commit_group.sync.aligned;" ::: "memory"); }
template <int N> __device__ __forceinline__ void wg_wait() { asm volatile("wgmma.wait_group.sync.aligned %0;" ::"n"(N) : "memory"); }
template <int N> __device__ __forceinline__ void acc_fence(float (&d)[N]) {
#pragma unroll
  for (int i = 0; i < N; i++) asm volatile("" : "+f"(d[i]) :: "memory");
}
#define O4(d, i) "+f"(d[i]), "+f"(d[i + 1]), "+f"(d[i + 2]), "+f"(d[i + 3])
template <int TB, int ACC>
__device__ __forceinline__ void wg_rs24(float (&d)[12], const uint32_t (&a)[4], uint64_t db) {
  asm volatile("wgmma.mma_async.sync.aligned.m64n24k16.f32.bf16.bf16 {%0,%1,%2,%3,%4,%5,%6,%7,%8,%9,%10,%11}, {%12,%13,%14,%15}, %16, %17, 1, 1, %18;"
               : O4(d, 0), O4(d, 4), O4(d, 8) : "r"(a[0]), "r"(a[1]), "r"(a[2]), "r"(a[3]), "l"(db), "n"(ACC), "n"(TB));
}
template <int TB, int ACC>
__device__ __forceinline__ void wg_rs32(float (&d)[16], const uint32_t (&a)[4], uint64_t db) {
  asm volatile("wgmma.mma_async.sync.aligned.m64n32k16.f32.bf16.bf16 {%0,%1,%2,%3,%4,%5,%6,%7,%8,%9,%10,%11,%12,%13,%14,%15}, {%16,%17,%18,%19}, %20, %21, 1, 1, %22;"
               : O4(d, 0), O4(d, 4), O4(d, 8), O4(d, 12) : "r"(a[0]), "r"(a[1]), "r"(a[2]), "r"(a[3]), "l"(db), "n"(ACC), "n"(TB));
}
template <int ACC>
__device__ __forceinline__ void wg_rs64(float (&d)[32], uint32_t a0, uint32_t a1, uint32_t a2, uint32_t a3, uint64_t db) {
  asm volatile("wgmma.mma_async.sync.aligned.m64n64k16.f32.bf16.bf16 {%0,%1,%2,%3,%4,%5,%6,%7,%8,%9,%10,%11,%12,%13,%14,%15,"
               "%16,%17,%18,%19,%20,%21,%22,%23,%24,%25,%26,%27,%28,%29,%30,%31}, {%32,%33,%34,%35}, %36, %37, 1, 1, 0;"
               : O4(d, 0), O4(d, 4), O4(d, 8), O4(d, 12), O4(d, 16), O4(d, 20), O4(d, 24), O4(d, 28)
               : "r"(a0), "r"(a1), "r"(a2), "r"(a3), "l"(db), "n"(ACC));
}
template <int ACC>
__device__ __forceinline__ void wg_ss24(float (&d)[12], uint64_t da, uint64_t db) {
  asm volatile("wgmma.mma_async.sync.aligned.m64n24k16.f32.bf16.bf16 {%0,%1,%2,%3,%4,%5,%6,%7,%8,%9,%10,%11}, %12, %13, %14, 1, 1, 1, 0;"
               : O4(d, 0), O4(d, 4), O4(d, 8) : "l"(da), "l"(db), "n"(ACC));
}
template <int ACC>
__device__ __forceinline__ void wg_rs40(float (&d)[20], const uint32_t (&a)[4], uint64_t db) {
  asm volatile("wgmma.mma_async.sync.aligned.m64n40k16.f32.bf16.bf16 {%0,%1,%2,%3,%4,%5,%6,%7,%8,%9,%10,%11,%12,%13,%14,%15,%16,%17,%18,%19}, {%20,%21,%22,%23}, %24, %25, 1, 1, 1;"
               : O4(d, 0), O4(d, 4), O4(d, 8), O4(d, 12), O4(d, 16) : "r"(a[0]), "r"(a[1]), "r"(a[2]), "r"(a[3]), "l"(db), "n"(ACC));
}

struct Row { uint32_t w[8]; };
__device__ __forceinline__ uint32_t add_bf16x2(uint32_t a, uint32_t b) {
  uint32_t d; asm("add.rn.bf16x2 %0, %1, %2;" : "=r"(d) : "r"(a), "r"(b)); return d;
}
__device__ __forceinline__ Row warp_ln(const Row& r, float& extra) {
  float x[16];
#pragma unroll
  for (int i = 0; i < 8; i++) { x[2 * i] = bf_lo(r.w[i]); x[2 * i + 1] = bf_hi(r.w[i]); }
  float m = (((x[0] + x[1]) + (x[2] + x[3])) + ((x[4] + x[5]) + (x[6] + x[7]))) + (((x[8] + x[9]) + (x[10] + x[11])) + ((x[12] + x[13]) + (x[14] + x[15])));
  m *= (1.f / 16);
  float v0 = 0.f, v1 = 0.f;
#pragma unroll
  for (int i = 0; i < 16; i += 2) { const float d0 = x[i] - m, d1 = x[i + 1] - m; v0 = fmaf(d0, d0, v0); v1 = fmaf(d1, d1, v1); }
  float v = v0 + v1;
#pragma unroll
  for (int o = 1; o <= 16; o <<= 1) {
    const float mo = __shfl_xor_sync(~0u, m, o), vo = __shfl_xor_sync(~0u, v, o);
    extra += __shfl_xor_sync(~0u, extra, o);
    const float d = mo - m;
    v = fmaf(d * d, 8.f * o, v + vo);
    m = 0.5f * (m + mo);
  }
  const float var = fmaf(v, 1.f / DM, 1e-5f);
  float rs = rsqrtf(var);
  rs = rs * fmaf(-0.5f * var * rs, rs, 1.5f);
  Row y;
#pragma unroll
  for (int i = 0; i < 8; i++) y.w[i] = pack_bf16((x[2 * i] - m) * rs, (x[2 * i + 1] - m) * rs);
  return y;
}
__device__ __forceinline__ Row warp_ln(const Row& r) { float e = 0.f; return warp_ln(r, e); }
__device__ __forceinline__ Row load_row(const bf16* p, int lane) {
  Row r;
#pragma unroll
  for (int q = 0; q < 4; q++) { const uint2 v = ld_rlx64(p + lane * 4 + q * 128); r.w[2 * q] = v.x; r.w[2 * q + 1] = v.y; }
  return r;
}
__device__ __forceinline__ void store_row_img(uint8_t* img, int rr, int lane, const Row& r) {
  uint8_t* p = img + (lane >> 4) * 4096 + rr * 128 + ((((lane & 15) >> 1) ^ (rr & 7)) << 4) + (lane & 1) * 8;
#pragma unroll
  for (int q = 0; q < 4; q++) *(uint2*)(p + q * 8192) = make_uint2(r.w[2 * q], r.w[2 * q + 1]);
}

constexpr int C_WO = 0;
constexpr int C_X = 49152;
constexpr int C_M = C_X + 65536;
constexpr int C_Q = C_M + 24576;
constexpr int C_K = C_Q + 10240, C_V = C_K + 10240;
constexpr int C_SA = C_V + 10240, C_SB = C_SA + 8192;
constexpr int C_O = C_SB + 8192;
constexpr int C_OT = C_O + 6144;
constexpr int C_PI = C_OT + 16384;
constexpr int C_BAR = C_PI + 8192;
constexpr int C_SMEM = C_BAR + 384 + 1024 + TREXTRA;
constexpr int C_STG = C_X + 32768;
static_assert(C_STG + 131072 <= C_BAR, "staging");
enum { B_M0 = 0, B_M1, B_M2, B_X, B_O, B_T, B_F, B_XL, B_U, B_P1, B_P2, B_OT, B_XF, B_XA, B_I, B_PI, B_J, B_W, B_WO, B_NUM };
static_assert(B_NUM <= 24, "barriers");
constexpr int C_POL = C_BAR + 192, C_INFO = C_BAR + 208;
enum { NB_ALL = 0, NB_M0, NB_PV, NB_W0, NB_TA, NB_M1, NB_M2, NB_RD, NB_SM, NB_C, NB_GO };
constexpr float SCALE_LOG2E = 0.08838834764831845f * 1.4426950408889634f;
#define N0STEPS 9
#define N2STEPS 12
#define FGATE 1
#define NSSTEPS 0
constexpr int KA = 32 - NSSTEPS - N2STEPS, K3 = KA - N0STEPS;
static_assert(KA % 4 == 0, "the rows of layer 1 are refilled in two parts");
#define BGATE 0
#define W0EARLY 0
#define PVEARLY 1
#define S1GATE 0
#define UPOLL 120
#define UGATE 1200
#define IGRP 0
#define SHIPLATE 7
#define SHIP 1024
#define GATE_P 2300
#define GATE_W 170
#define EXPF 0
#define GATE_G 170
#define GATE_M 3280
#define HOLE0 22
#define HOLE1 28
#define HOLE2 32
__device__ __forceinline__ uint32_t gtime() { uint32_t t; asm volatile("mov.u32 %0, %%globaltimer_lo;" : "=r"(t) :: "memory"); return t; }
__device__ __forceinline__ void wait_clock(uint32_t t) {
  asm volatile("{ .reg .pred p; .reg .b32 c; .reg .b64 cc;\nL: mov.u64 cc, %%clock64; cvt.u32.u64 c, cc; sub.u32 c, c, %0; setp.lt.s32 p, c, 0; @p bra L; }" ::"r"(t) : "memory");
}
__device__ __forceinline__ void bar_sync_z(int id, int n, uint32_t z) {
  asm volatile("{ .reg .pred p; setp.eq.u32 p, %2, 0; @p bar.sync %0, %1; }" ::"r"(id), "r"(n), "r"(z) : "memory");
}

__device__ __forceinline__ int probe_home(uint32_t* p, int lane) {
  uint32_t best[2] = {~0u, ~0u};
#pragma unroll 1
  for (int rep = 0; rep < 3; rep++) {
#pragma unroll
    for (int pg = 0; pg < 2; pg++) {
      uint32_t t0, t1, v = 0;
      asm volatile("mov.u32 %0, %%clock;" : "=r"(t0) :: "memory");
      asm volatile("{ .reg .pred p; setp.eq.u32 p, %2, 0; @p atom.relaxed.gpu.global.exch.b32 %0, [%1], %3; }" : "+r"(v) : "l"(p + pg * 1024), "r"(lane), "r"(rep) : "memory");
      asm volatile("{ .reg .pred p; setp.ne.u32 p, %1, 0x13572468; mov.u32 %0, 0; @p mov.u32 %0, %%clock; }" : "=r"(t1) : "r"(v) : "memory");
      best[pg] = min(best[pg], t1 - t0);
    }
  }
  return __shfl_sync(~0u, max(-150, min(150, (int)(best[1] - best[0]))), 0);
}
__device__ __forceinline__ uint32_t home_flip(const void* p) { const uint32_t a = (uint32_t)(size_t)p; return ((a >> 16) ^ (a >> 17) ^ (a >> 19)) & 1; }
__device__ __forceinline__ uint32_t ppage(uint32_t lp, uint32_t pol) { return lp ? 3 - pol : pol; }
__device__ __forceinline__ uint32_t and_x(uint32_t a, uint32_t b, uint32_t m) {
  uint32_t d; asm("lop3.b32 %0, %1, %2, %3, 0x42;" : "=r"(d) : "r"(a), "r"(b), "r"(m)); return d;
}
__device__ __forceinline__ uint32_t and3(uint32_t a, uint32_t b, uint32_t c) {
  uint32_t d; asm("lop3.b32 %0, %1, %2, %3, 0x80;" : "=r"(d) : "r"(a), "r"(b), "r"(c)); return d;
}

template <int N> struct IC { static constexpr int value = N; };
template <class F> __device__ __forceinline__ void static_for2(F f) { f(IC<0>()); f(IC<1>()); }
template <class F> __device__ __forceinline__ void static_for3(F f) { f(IC<0>()); f(IC<1>()); f(IC<2>()); }
__device__ __forceinline__ void stage_weights(uint32_t stage, const CUtensorMap* map, int col, int row, uint32_t mbar) {
  mbar_expect_tx(mbar, 131072);
#pragma unroll 1
  for (int i = 0; i < 4; i++)
    asm volatile("cp.async.bulk.tensor.2d.shared::cluster.global.mbarrier::complete_tx::bytes [%0], [%1, {%3, %4}], [%2];"
                 ::"r"(stage + (i & 1) * 65536 + (i >> 1) * 32768), "l"(map), "r"(mbar), "r"(col + (i & 1) * 64), "r"(row + (i >> 1) * 256) : "memory");
}
__device__ __forceinline__ void load_wfrags(uint32_t (&wA)[32][4], uint32_t stage, int w, int lane) {
  const int mi = lane >> 3, r = lane & 7;
  const uint32_t a = stage + (w >> 2) * 65536 + ((mi >> 1) * 8 + r) * 128 + ((((w & 3) * 2 + (mi & 1)) ^ r) << 4);
#pragma unroll
  for (int ks = 0; ks < 32; ks++) ldsm4t(wA[ks], a + ks * 2048);
}
template <int K0, int K1>
__device__ __forceinline__ void tok_seq(float (&d)[16], const uint32_t (&wA)[32][4], uint64_t desc, uint32_t wave) {
#pragma unroll
  for (int k = K0; k < K1; k++) {
    const int ks = k & 31;
    constexpr int HM0 = 1, HM1 = 2, HM2 = 4;
    const int hm = (k == HOLE0 ? HM0 : 0) | (k == HOLE1 ? HM1 : 0) | (k == HOLE2 ? HM2 : 0);
    if (hm) bar_sync_z(NB_RD, 384, ((hm >> wave) & 1) ^ 1);
    if (ks == 0) wg_rs32<0, 0>(d, wA[ks], desc);
    else wg_rs32<0, 1>(d, wA[ks], desc + (ks >> 2) * 256 + (ks & 3) * 2);
  }
}
template <int K0, int K1>
__device__ __forceinline__ void mem_part(float (&d)[12], const uint32_t (&wA)[32][4], uint64_t desc) {
#pragma unroll
  for (int ks = K0; ks < K1; ks++) {
    if (ks == 0) wg_rs24<1, 0>(d, wA[ks], desc);
    else wg_rs24<1, 1>(d, wA[ks], desc + ks * 48);
  }
}
__device__ __forceinline__ void out_tile(float (&d)[12], uint64_t da, uint64_t db) {
#pragma unroll
  for (int i = 0; i < 8; i++) { if (i == 0) wg_ss24<0>(d, da, db); else wg_ss24<1>(d, da + i * 128, db + (i >> 1) * 32 + (i & 1) * 2); }
}
__device__ __forceinline__ void tok_pack(uint32_t (&p)[8], const float (&d)[16]) {
#pragma unroll
  for (int i = 0; i < 8; i++) p[i] = pack_bf16(d[2 * i], d[2 * i + 1]);
}
__device__ __forceinline__ void tok_store(uint32_t dst, const uint32_t (&p)[8]) {
  stsm4(dst, p[0], p[1], p[2], p[3]);
  stsm4(dst + 4096, p[4], p[5], p[6], p[7]);
}
template <class T> __device__ __forceinline__ T keep(T v) { asm volatile("" : "+r"(v)); return v; }
__device__ __forceinline__ uint32_t pin(uint32_t v) { return __shfl_sync(~0u, v, threadIdx.x & 31); }

#define TRC blockIdx.x
#define TRS (C_BAR + 384)
__device__ __forceinline__ void chain_proj(const uint32_t sb, const int w, const int lane_, const uint32_t rank) {
  uint32_t wA[32][4];
  mbar_wait(sb + C_BAR + B_W * 8, 0, 30);
  if (w == 0) { HD(2) }
  load_wfrags(wA, sb + C_STG, w, lane_);
  bar_arrive(NB_ALL, 384);
  const int lane = pin(lane_);
  const uint32_t bars = sb + C_BAR;
  const uint32_t quad = pin(sb + (lane_ >> 4) * 2048 + (lane_ & 15) * 16);
  const uint32_t own = C_Q + rank * 10240;
  const uint64_t dX1 = mk_desc(sb + C_X, 16, 1024, 1), dX2 = dX1 + 2048;
  const uint64_t dM = mk_desc(sb + C_M, 128, 256, 0);
  const uint32_t r1 = rank == 0 ? 1 : 0, r2 = rank == 2 ? 1 : 2;
  const uint32_t xa = pin(sb + own + 8192 + w * 256 + lane_ * 4);
  const uint32_t a1x = pin(mapa_u32(xa, r1)), a2x = pin(mapa_u32(xa, r2));
  const uint32_t b1x = pin(mapa_u32(bars + B_X * 8, r1)), b2x = pin(mapa_u32(bars + B_X * 8, r2));
  const uint32_t wave = rank == 2 ? 0 : rank + 1;
  float a[16];
  wg_fence();
  tok_seq<32, 32 + KA>(a, wA, mk_desc(__shfl_sync(~0u, sb, 0) + C_X, 16, 1024, 1), 3);
  wg_commit();
  wg_wait<0>();
  mbar_arrive_z(bars + B_XA * 8, lane);
#pragma unroll 1
  for (int st = 0;; st++) {
    uint32_t pk[8];
    wg_fence();
    if (NSSTEPS) bar_sync(NB_SM, 416);
    tok_seq<32 + KA, 32 + KA + NSSTEPS>(a, wA, dX1, 3);
    bar_sync(NB_PV, NSSTEPS ? 384 : 416);
    tok_seq<32 + KA + NSSTEPS, 64>(a, wA, dX1, 3);
    wg_commit();
    wg_wait<0>();
    acc_fence(a);
    mbar_arrive_z(bars + B_XF * 8, lane);
    tok_pack(pk, a);
    TR(1)
    bar_sync(NB_W0, 416);
    tok_store(quad + w * 256 + (rank == 0 ? own : C_SA), pk);
    __syncwarp();
    mbar_arrive_z(bars + B_P1 * 8, lane);
    wg_fence();
    tok_seq<0, 32>(a, wA, dX2, wave);
    wg_commit();
    const uint32_t info = lds32(sb + C_INFO + (st & 1) * 4);
    TR(2)
    wg_wait<0>();
    acc_fence(a);
    TR(3)
    tok_pack(pk, a);
    tok_store(quad + w * 256 + (rank == 0 ? C_SA : own), pk);
    if (rank == 2) tok_store(quad + w * 256 + C_SB, pk);
    __syncwarp();
    mbar_arrive_z(bars + B_P2 * 8, lane);
    TR(4)
    wg_fence();
    tok_seq<32, 32 + K3>(a, wA, dX1, wave);
    TR(6)
    {
      float am[12];
      bar_sync(NB_M0, 384);
      mem_part<0, 10>(am, wA, dM);
      TR(7)
      bar_sync(NB_M1, 384);
      mem_part<10, 21>(am, wA, dM);
      bar_sync(NB_M2, 384);
      const uint32_t bad = lds32(sb + C_INFO + 16 + (lane & 3) * 32);
      mem_part<21, 32>(am, wA, dM);
      wg_commit();
      const bool redo = __any_sync(~0u, bad != 0);
      if (__builtin_expect(redo, 0)) {
        wg_wait<0>();
        int it = 0;
        while (__any_sync(~0u, lds32_poll(sb + C_INFO + 20 + (lane & 3) * 32) != st && bad)) give_up(++it, 50 * SPIN_LIMIT, 31);
        wg_fence();
        mem_part<0, 32>(am, wA, dM);
        wg_commit();
      }
      wg_wait<0>();
      acc_fence(am);
      TR(8)
      const uint32_t x00 = pack_bf16(am[0], am[1]), x01 = pack_bf16(am[2], am[3]), x10 = pack_bf16(am[4], am[5]), x11 = pack_bf16(am[6], am[7]);
      const uint32_t y0 = pack_bf16(am[8], am[9]), y1 = pack_bf16(am[10], am[11]), x20 = info ? x10 : y0, x21 = info ? x11 : y1;
      st_async32<0>(a1x, rank == 0 ? x10 : x00, b1x); st_async32<0>(a2x, rank == 2 ? x10 : x20, b2x);
      st_async32<128>(a1x, rank == 0 ? x11 : x01, b1x); st_async32<128>(a2x, rank == 2 ? x11 : x21, b2x);
      sts32(xa, rank == 0 ? x00 : rank == 2 ? x20 : x10); sts32(xa + 128, rank == 0 ? x01 : rank == 2 ? x21 : x11);
      if (__builtin_expect(info, 0)) {
        const uint32_t o = (info & 3) * 2048 - 8192;
        if (rank == 2) { sts32(xa + o, y0); sts32(xa + o + 128, y1); }
        else { st_async32<0>(a2x + o, y0, b2x + (B_T - B_X) * 8); st_async32<128>(a2x + o, y1, b2x + (B_T - B_X) * 8); }
      }
      __syncwarp();
      mbar_arrive_z(bars + B_X * 8, lane);
    }
    TR(9)
    wg_fence();
    tok_seq<32 + K3, 32 + KA>(a, wA, dX1, 3);
    wg_commit();
    TR(0)
    wg_wait<0>();
    if (st == NSTEP - 1) break;
    mbar_arrive_z(bars + B_XA * 8, lane);
  }
  if (NSSTEPS) bar_arrive(NB_SM, 416);
  bar_arrive(NB_PV, NSSTEPS ? 384 : 416);
}

__device__ __forceinline__ void chain_mem(const uint32_t sb, const int w, const int lane_, const uint32_t rank, const int h,
                                          const bf16* __restrict__ mem0) {
  const int lane = pin(lane_);
  const int wave = rank == 2 ? 0 : rank + 1;
  const int c = w - 8, t = c * 32 + lane, b = wave * 32 + h;
  const uint32_t bars = sb + C_BAR;
  const int wi = (lane & 1) * 2 + (lane >> 4), cq = (lane >> 2) & 3;
  mbar_expect_tx_z(bars + B_X * 8, 4096, t); mbar_expect_tx_z(bars + B_O * 8, 4096, t);
  if (NSSTEPS) bar_arrive(NB_SM, 416);
  bar_arrive(NB_PV, NSSTEPS ? 384 : 416); bar_arrive(NB_W0, 416); bar_arrive(NB_RD, 384);
  uint32_t m0[16];
#pragma unroll
  for (int i = 0; i < 16; i++) m0[i] = *(const uint32_t*)(mem0 + (lane >> 2) * DM + (c * 16 + i) * 8 + (lane & 3) * 2);
  uint32_t* pp = g_M + c * 16384 + 14 * 1024 + (blockIdx.x & 31) * 32;
  st_rlx32(pp + lane, 0); st_rlx32(pp + 1024 + lane, 0);
  mbar_wait(bars + B_W * 8, 0, 32);
  {
    uint32_t* p = pp;
    const int vote = probe_home(p, lane);
    sts32(sb + C_POL + c * 4, home_flip(p) ? -vote : vote);
    bar_sync(NB_C, 128);
    const uint4 v = lds128(sb + C_POL);
    const uint32_t side = (int)(v.x + v.y + v.z + v.w) > 0;
    bar_sync(NB_C, 128);
    sts32(sb + C_POL + c * 4, side ^ home_flip(p));
    sts32(sb + C_INFO + 8, side ^ home_flip(g_P + b * 4096));
    if (c == 0) { HD(0) }
    wait_count(g_ex.ready, 96, 35);
    if (c == 0) { HD(1) }
    st_rlx32(&g_fl.pol[b], (side ^ home_flip(g_P + b * 4096)) + 1);
  }
  bar_sync(NB_ALL, 384);
  if (c == 0) { HD(3) }
  mbar_arrive_remote_z(mapa_u32(bars + B_F * 8, (rank + 1 + (t & 1)) % 3), t >> 1);
#pragma unroll
  for (int i = 0; i < 16; i += 4) {
    const uint32_t a = sb + C_M + (c * 8 + i / 2 + (lane >> 4)) * 768 + (lane & 15) * 16;
    stsm4t(a, m0[i], m0[i + 1], m0[i + 2], m0[i + 3]); stsm4t(a + 256, m0[i], m0[i + 1], m0[i + 2], m0[i + 3]); stsm4t(a + 512, m0[i], m0[i + 1], m0[i + 2], m0[i + 3]);
  }
  sts32(sb + C_INFO + 16 + c * 32, 0); sts32(sb + C_INFO + 20 + c * 32, 0);
  fence_async_smem();
  bar_arrive(NB_M0, 384); bar_arrive(NB_M1, 384);
  mbar_wait(bars + B_F * 8, 0, 34);
  bar_arrive(NB_M2, 384);
  mbar_wait(bars + B_WO * 8, 0, 33);
  uint32_t pgbits, polP;
  {
    const int tl = lane / 3, u = ((tl * 3 + rank) * 4 + c) * 3 + (lane - tl * 3);
    uint32_t pol;
    int it = 0;
    do { pol = ld_rlx32(&g_fl.pol[lane < 9 && u < 96 ? u : b]); give_up(it++, SPIN_LIMIT, 40); } while (__any_sync(~0u, pol == 0));
    pgbits = __reduce_or_sync(~0u, lane < 9 ? ppage(h >> 4, (pol - 1) & 1) << (2 * lane) : 0u);
    polP = __shfl_sync(~0u, pol - 1, 9);
  }
  const int mi = lane >> 3;
  const uint32_t l16 = pin(sb + lane * 16);
  const uint32_t r1 = rank == 2 ? 0 : rank + 1, r2 = rank == 0 ? 2 : rank - 1;
  const uint32_t oa = pin(sb + C_O + rank * 2048 + (lane >> 2) * 64 + (((lane & 3) ^ (lane >> 3)) << 4));
  const uint32_t a1 = mapa_u32(oa, r1), b1 = mapa_u32(bars + B_O * 8, r1), a2 = mapa_u32(oa, r2), b2 = mapa_u32(bars + B_O * 8, r2);
  const uint64_t dWo = mk_desc(sb + C_WO, 8192, 1024, 1), dO = mk_desc(sb + C_O, 16, 2048, 2);
  const uint64_t dK = mk_desc(sb + C_K, 128, 2048, 0);
  const uint64_t dV = mk_desc(sb + C_V, 2048, 128, 0), dVm = mk_desc(sb + C_V + 8192, 0, 128, 0);
  const uint32_t qa = pin(sb + C_Q + (c ? c + 1 : mi & 1) * 2048 + (mi >> 1) * 128 + (lane & 7) * 16);
  const uint32_t dg = ((lane >> 2) < 2 * (lane & 3) ? 1 : 0) | ((lane >> 2) < 2 * (lane & 3) + 1 ? 2 : 0);
  const uint32_t msk = pin(c == 0 ? dg | dg << 4 : c == 1 ? dg << 2 | 3 << 4 : c == 2 ? dg << 4 : 0);
  uint8_t* Pw = (uint8_t*)g_P + (rank * 4 + c) * 3 * 16384 + (h & 15) * 256 + ((lane * 4) ^ ((h & 3) << 5));
  const uint32_t pia = pin(sb + C_PI + ((lane >> 4) * 4 + (lane & 3)) * 256 + ((c * 64 + cq * 16) ^ ((lane & 3) << 5)));
  uint8_t* Mw = (uint8_t*)g_M + (b >> 5) * 16384 + ((lane & 2) ? 4096 : 12288) + (b & 31) * 256 + c * 64 + cq * 16 + wi * 4;
  uint32_t nupd = 0;
  bar_arrive(NB_GO, 160);

  { const int st = 71; (void)st; STAT(0, lds32(sb + C_POL + c * 4)) STAT(1, polP) STAT(2, (uint32_t)(size_t)(g_M + c * 16384)) STAT(3, (uint32_t)(size_t)(g_P + b * 4096)) }
#pragma unroll 1
  for (int st = 0;; st++) {
    mbar_wait(bars + B_P1 * 8, st & 1, 38);
    mbar_wait(bars + B_T * 8, st & 1, 42);
    STAT(10, clk32())
    {
      float s[20];
      {
        uint32_t q[8][4];
        if (c == 3) mbar_wait(bars + B_X * 8, st & 1, 41);
#pragma unroll
        for (int i = 0; i < 8; i++) ldsm4t(q[i], qa + i * 256);
        if (c != 3) { mbar_wait(bars + B_X * 8, st & 1, 41); fence_async_smem(); }
        STAT(11, clk32())
        TR(0)
        wg_fence();
#pragma unroll
        for (int i = 0; i < 8; i++) { if (i == 0) wg_rs40<0>(s, q[i], dK); else wg_rs40<1>(s, q[i], dK + i * 16); }
        wg_commit();
        wg_wait<0>();
        if (NSSTEPS) bar_arrive(NB_SM, 416);
        acc_fence(s);
      }
      TR(1)
      const bool w0 = c == 0;
      float z[10] = {s[16], s[17], s[0], s[1], w0 ? s[18] : s[4], w0 ? s[19] : s[5], w0 ? s[2] : s[8], w0 ? s[3] : s[9], w0 ? s[6] : s[12], w0 ? s[7] : s[13]};
      if (msk & 1) z[2] = -INFINITY;
      if (msk & 2) z[3] = -INFINITY;
      if (msk & 4) z[6] = -INFINITY;
      if (msk & 8) z[7] = -INFINITY;
      if (msk & 16) z[8] = -INFINITY;
      if (msk & 32) z[9] = -INFINITY;
      float m0 = fmaxf(fmaxf(z[0], z[1]), fmaxf(z[2], z[3])), m1 = fmaxf(fmaxf(fmaxf(z[4], z[5]), fmaxf(z[6], z[7])), fmaxf(z[8], z[9]));
      m0 = fmaxf(m0, __shfl_xor_sync(~0u, m0, 1)); m1 = fmaxf(m1, __shfl_xor_sync(~0u, m1, 1));
      m0 = fmaxf(m0, __shfl_xor_sync(~0u, m0, 2)); m1 = fmaxf(m1, __shfl_xor_sync(~0u, m1, 2));
      if (!w0) m0 = m1 = fmaxf(m0, m1);
      m0 *= -SCALE_LOG2E; m1 *= -SCALE_LOG2E;
      uint32_t p[5];
#pragma unroll
      for (int k = 0; k < 5; k++) {
        z[2 * k] = ex2_fast(fmaf(z[2 * k], SCALE_LOG2E, k < 2 ? m0 : m1)); z[2 * k + 1] = ex2_fast(fmaf(z[2 * k + 1], SCALE_LOG2E, k < 2 ? m0 : m1));
        p[k] = pack_bf16(z[2 * k], z[2 * k + 1]);
      }
      const uint32_t p2 = w0 ? 0 : p[2], p3 = w0 ? 0 : p[3], p4 = w0 ? 0 : p[4];
      float oA[32], oB[32];
      wg_fence();
      wg_rs64<0>(oA, p[0], p[2], 0, 0, dVm); wg_rs64<1>(oA, p[1], p[3], p2, p[4], dV); wg_rs64<1>(oA, p3, 0, p4, 0, dV + 256);
      wg_commit();
      wg_rs64<0>(oB, p[0], p[2], 0, 0, dVm + 64); wg_rs64<1>(oB, p[1], p[3], p2, p[4], dV + 64); wg_rs64<1>(oB, p3, 0, p4, 0, dV + 320);
      wg_commit();
      float l0 = (z[0] + z[1]) + (z[2] + z[3]), l1 = ((z[4] + z[5]) + (z[6] + z[7])) + (z[8] + z[9]);
      if (!w0) l0 += l1;
      l0 += __shfl_xor_sync(~0u, l0, 1); l1 += __shfl_xor_sync(~0u, l1, 1);
      l0 += __shfl_xor_sync(~0u, l0, 2); l1 += __shfl_xor_sync(~0u, l1, 2);
      float i0, i1;
      asm volatile("rcp.approx.ftz.f32 %0, %2; rcp.approx.ftz.f32 %1, %3;" : "=f"(i0), "=f"(i1) : "f"(l0), "f"(l1));
      asm volatile("st.shared.v2.f32 [%0], {%1,%2};" ::"r"(sb + C_INFO + 24), "f"(i0), "f"(i1) : "memory");
      const uint32_t ta = l16 + C_OT + (st & 1) * 8192 + (c ? c + 1 : 0) * 2048;
      auto leave = [&](const float (&o)[32], auto hc) {
        constexpr int H = decltype(hc)::value;
        uint32_t e[8];
#pragma unroll
        for (int j = 0; j < 8; j++) e[j] = pack_bf16(o[4 * j] * i0, o[4 * j + 1] * i0);
        if (c == 3) {
          static_for2([&](auto bc) {
            constexpr int B = decltype(bc)::value;
            asm volatile("st.async.weak.shared::cluster.mbarrier::complete_tx::bytes.v4.b32 [%0 + %9], {%5,%6,%7,%8}, [%1];\n"
                         "st.async.weak.shared::cluster.mbarrier::complete_tx::bytes.v4.b32 [%2 + %9], {%5,%6,%7,%8}, [%3];\n"
                         "st.shared.v4.b32 [%4 + %9], {%5,%6,%7,%8};"
                         ::"r"(a1), "r"(b1), "r"(a2), "r"(b2), "r"(oa), "r"(e[4 * B]), "r"(e[4 * B + 1]), "r"(e[4 * B + 2]), "r"(e[4 * B + 3]),
                           "n"(H * 1024 + B * 512) : "memory");
          });
        } else {
          stsm4(ta + H * 1024, e[0], e[1], e[2], e[3]); stsm4(ta + H * 1024 + 512, e[4], e[5], e[6], e[7]);
          if (w0) {
#pragma unroll
            for (int j = 0; j < 8; j++) e[j] = pack_bf16(o[4 * j + 2] * i1, o[4 * j + 3] * i1);
            stsm4(ta + 2048 + H * 1024, e[0], e[1], e[2], e[3]); stsm4(ta + 2048 + H * 1024 + 512, e[4], e[5], e[6], e[7]);
          }
        }
      };
      wg_wait<1>();
      acc_fence(oA);
      leave(oA, IC<0>());
      wg_wait<0>();
      if (PVEARLY) bar_arrive(NB_PV, NSSTEPS ? 384 : 416);
      acc_fence(oB);
      leave(oB, IC<1>());
      if (!PVEARLY) bar_arrive(NB_PV, NSSTEPS ? 384 : 416);
      __syncwarp();
      mbar_arrive_z(bars + (c == 3 ? B_O : B_OT) * 8, lane);
      TR(2)
    }
    mbar_wait(bars + B_O * 8, st & 1, 43);
    if (st == NSTEP - 1) break;
    uint32_t info;
    {
      const uint32_t tag = (st & 1) ^ 1;
      float oc0[12], oc1[12], oc2[12];
      fence_async_smem();
      TR(3)
      wg_fence();
      out_tile(oc0, dWo, dO);
      wg_commit();
      out_tile(oc1, dWo + 1024, dO);
      wg_commit();
      asm volatile("" : "+r"(pgbits));
      auto put = [&](const float (&oc)[12], auto tlc) {
        constexpr int TL = decltype(tlc)::value;
        static_for3([&](auto jc) {
          constexpr int j = decltype(jc)::value;
          uint8_t* p = Pw + ((pgbits >> (2 * (TL * 3 + j))) & 3) * 4096;
          asm volatile("st.relaxed.gpu.global.u32 [%0 + %3], %1; st.relaxed.gpu.global.u32 [%0 + %3 + 128], %2;" ::"l"(p),
                       "r"((pack_bf16(oc[4 * j], oc[4 * j + 1]) & ~1u) | tag), "r"((pack_bf16(oc[4 * j + 2], oc[4 * j + 3]) & ~1u) | tag),
                       "n"((TL * 36 + j) * 16384) : "memory");
        });
      };
      wg_wait<1>();
      acc_fence(oc0);
      put(oc0, IC<0>());
      sts32(sb + C_INFO + 24, clk32());
      TR(4)
      out_tile(oc2, dWo + 2048, dO);
      wg_commit();
      wg_wait<1>();
      acc_fence(oc1);
      put(oc1, IC<1>());
      if (W0EARLY) bar_arrive(NB_W0, 416);
      bar_sync(NB_TA, 192);
      TR(5)
      wg_wait<0>();
      if (!W0EARLY) bar_arrive(NB_W0, 416);
      info = lds32(sb + C_INFO + ((st + 1) & 1) * 4);
      acc_fence(oc2);
      if (rank != 2) put(oc2, IC<2>());
      mbar_arrive_remote_z(((t & 1) ? b2 : b1) + (B_F - B_O) * 8, t >> 1);
      mbar_expect_tx_z(bars + ((t & 1) ? B_O : B_X) * 8, 4096, t >> 1);
      TR(6)
    }
    const int sn = (st + 1) & 3;
    uint8_t* mw = Mw + sn * 65536;
    asm volatile("" : "+l"(mw));
    if (__builtin_expect((st < DELTA && b % 3 != 0) || (info && b % 3 == 2), 0)) {
      bar_arrive(NB_RD, 384);
      const int col = b / 3 * 16 + c * 4 + ((lane >> 2) & 3), r0 = (lane & 1) * 4 + (lane >> 4) * 2;
      const bool upd = info && b % 3 == 2;
      if (upd) mbar_wait(bars + B_U * 8, nupd & 1, 39);
      uint32_t hv[2];
#pragma unroll
      for (int i = 0; i < 2; i++) {
        const int r = r0 + i, sg = st + 1 - DELTA;
        const void* p = !upd ? (const void*)(mem0 + r * DM + col) : r == (int)(info >> 4) ? (const void*)(g_x2p[sg][1] + col)
                      : (const void*)(g_xs[1] + sg * 32768 + (col >> 6) * 4096 + ((info & 3) * 8 + r) * 128 + ((((col >> 3) ^ r) & 7) << 4) + (col & 7) * 2);
        asm volatile("ld.relaxed.gpu.global.u16 %0, [%1];" : "=r"(hv[i]) : "l"(p) : "memory");
      }
      st_rlx32(mw, hv[0] | hv[1] << 16);
      STAT(1, 0) STAT(2, 0) STAT(4, 0)
    } else {
      const uint32_t flip = (st & 1) ? ~0u : 0u;
      const bool u16 = lane & 16;
      const uint32_t bs = (lane & 4) ? 0x3f800000u : 0x00003f80u, bs0 = (lane & 8) ? 0u : bs, bs1 = (lane & 8) ? bs : 0u;
      STATC(c_rdy)
      mbar_wait(bars + B_PI * 8, st & 1, 37);
      TR(7)
      uint4 q0 = lds128(pia), q1 = lds128(pia + 2048), q2 = lds128(pia + 4096), q3 = lds128(pia + 6144);
      int it = 0;
#pragma unroll 1
      while (true) {
        float d0[4] = {0.f, 0.f, 0.f, 0.f}, d1[4] = {0.f, 0.f, 0.f, 0.f};
        mma16816(d0, q0.x, q0.y, q0.z, q0.w, bs0, bs1);
        mma16816(d1, q1.x, q1.y, q1.z, q1.w, bs0, bs1);
        mma16816(d0, q2.x, q2.y, q2.z, q2.w, bs0, bs1);
        mma16816(d1, q3.x, q3.y, q3.z, q3.w, bs0, bs1);
        const bool all = __all_sync(~0u, (int)and3(and_x(q0.x, q1.x, flip), and_x(q2.x, q3.x, flip), 1u));
        const float a0 = d0[0] + d1[0], a1 = d0[1] + d1[1], a2 = d0[2] + d1[2], a3 = d0[3] + d1[3];
        asm volatile("{ .reg .pred p; setp.ne.u32 p, %0, 0; @p bar.arrive %1, 384; }" ::"r"((uint32_t)all), "n"((int)NB_RD) : "memory");
        const uint32_t mword = pack_bf16((u16 ? a2 : a0) + __shfl_xor_sync(~0u, u16 ? a0 : a2, 16), (u16 ? a3 : a1) + __shfl_xor_sync(~0u, u16 ? a1 : a3, 16));
        asm volatile("{ .reg .pred p; setp.ne.u32 p, %2, 0; @p st.relaxed.gpu.global.u32 [%0], %1; }" ::"l"(mw), "r"(mword), "r"((uint32_t)all) : "memory");
        if (__builtin_expect(all, 1)) break;
        give_up(++it, SPIN_LIMIT, 44);
        const uint8_t* Pr0 = (const uint8_t*)g_P + b * 16384 + (pia - sb - C_PI) + polP * 4096;
        const uint8_t* Pr1 = Pr0 + (3 - 2 * polP) * 4096;
        q0 = ld_rlx128(Pr0); q1 = ld_rlx128(Pr0 + 2048); q2 = ld_rlx128(Pr1); q3 = ld_rlx128(Pr1 + 2048);
      }
      STATC(c_mst)
      STAT(1, c_rdy - tref) STAT(2, c_mst - tref) STAT(4, it)
      TRV(14, it)
    }
    STAT(0, lds32(sb + C_INFO + 24) - tref) STAT(3, tref)
    nupd += info != 0;
    TR(9)
    {
      int it = 0;
      const uint32_t mchk = pin(keep(l16) + C_M + c * 2048 + lane * 16 + (lane & 28));
      auto missing = [&](int g) { return __any_sync(~0u, max(lds32(mchk + g * 8192), lds32(mchk + g * 8192 + 1024)) == ~0u); };
      auto complete = [&](int g) {
        const uint8_t* src = (const uint8_t*)g_M + sn * 65536 + (lds32(sb + C_POL + sn * 4) ? 4096 : 12288) + g * 16384 + c * 2048 + lane * 16;
        uint4 v0, v1, v2, v3;
#pragma unroll 1
        do {
          v0 = ld_rlx128(src); v1 = ld_rlx128(src + 512); v2 = ld_rlx128(src + 1024); v3 = ld_rlx128(src + 1536);
          give_up(++it, SPIN_LIMIT, 48);
        } while (__any_sync(~0u, max(__vimax3_u32(v0.x, v1.x, v2.x), v3.x) == ~0u));
        const uint32_t d = l16 + C_M + g * 8192 + c * 2048;
        sts128(d, v0); sts128(d + 512, v1); sts128(d + 1024, v2); sts128(d + 1536, v3);
        fence_async_smem();
      };
      mbar_wait(bars + B_M0 * 8, (st + 1) & 1, 45);
      bar_arrive(NB_M0, 384);
      STATC(c_g0)
      TR(10)
      const bool redo = missing(0);
      sts32(sb + C_INFO + 16 + c * 32, redo);
      static_for2([&](auto gc) {
        constexpr int g = 1 + decltype(gc)::value;
        mbar_wait(bars + (B_M0 + g) * 8, (st + 1) & 1, 46);
        TR(10 + g)
        const bool m = missing(g);
        asm volatile("{ .reg .pred p; setp.eq.u32 p, %0, 0; @p bar.arrive %1, 384; }" ::"r"((uint32_t)m), "n"(NB_M1 + g - 1) : "memory");
        if (__builtin_expect(m, 0)) { complete(g); bar_arrive(NB_M1 + g - 1, 384); }
        STAT(6 + g, clk32() - tref)
      });
      if (__builtin_expect(redo, 0)) { complete(0); __syncwarp(); sts32(sb + C_INFO + 20 + c * 32, st + 1); }
      STAT(5, c_g0 - tref)
      STAT(9, clk32() - tref) STAT(6, it + redo * 256)
      TR(13)
      TRV(15, it)
      st_rlx32(Mw + (st & 3) * 65536, ~0u);
    }
  }
}

__device__ __forceinline__ void chain_dma(const uint32_t sb, const int w, const int lane, const uint32_t rank, const int h) {
  const uint32_t bars = sb + C_BAR;
  const int expf_ = EXPF;
  if (w == 12) {
    u64 best = 0;
    uint32_t nx = 0;
    auto load = [&](uint32_t dst, const uint8_t* src, uint32_t bytes) {
      mbar_expect_tx_z(bars + B_XL * 8, bytes, lane >> 1);
      if (lane < 2 && bytes) {
        fence_async_glb();
        bulk_g2s(sb + dst, src, bytes, bars + B_XL * 8);
      }
      __syncwarp();
      mbar_wait(bars + B_XL * 8, nx++ & 1, 52);
    };
    bar_arrive(NSSTEPS ? NB_SM : NB_PV, 416);
    wait_count(g_ex.ready, 96, 59);
    HD(6)
#pragma unroll 1
    for (int st = 0; st < NSTEP; st++) {
      const int sg = st - DELTA;
      const bool more = st + 1 < NSEG && !(expf_ & 4);
      uint32_t info = 0;
      if (sg >= 0) {
        const u64 k = wait_keys<false>(g_fl.key[0][sg], lane, 50);
        if (k > best) { best = k; info = 4 | ((key_token(k) >> 3) & 3) | (key_token(k) & 7) << 4; }
      }
      TR(0)
      mbar_wait(bars + B_XA * 8, st & 1, 58);
      sts32(sb + C_INFO + (st & 1) * 4, info);
      if (st > 0) bar_arrive(NB_TA, 192);
      TR(1)
      load(lane ? C_X : C_X + 32768, lane ? g_xs[0] + (st + 1) * 32768 : g_xs[1] + sg * 32768, lane ? (more ? KA * 1024 : 0) : (sg >= 0 && !(expf_ & 8) ? 32768 : 0));
      bar_arrive(NB_W0, 416);
      TR(2)
      if (__builtin_expect(info, 0)) {
        int it = 0;
        while (__any_sync(~0u, max(ld_rlx32(g_x2p[sg][1] + lane * 16), ld_rlx32(g_x2p[sg][1] + lane * 16 + 8)) == ~0u)) { give_up(++it, SPIN_LIMIT, 56); warp_sleep(UPOLL); }
        sts32(sb + C_INFO + 40, clk32());
        __syncwarp();
        mbar_arrive_z(bars + B_U * 8, lane);
      }
      mbar_wait(bars + B_XF * 8, st & 1, 53);
      mbar_wait(bars + (B_M0 + BGATE) * 8, st & 1, 54);
      load(C_X + KA * 1024, g_xs[0] + (st + 1) * 32768 + KA * 1024, more && lane == 0 ? 32768 - KA * 1024 : 0);
      TR(3)
      bar_arrive(NSSTEPS ? NB_SM : NB_PV, 416);
    }
  } else if (w == 13) {
    constexpr uint32_t NP = 8192 / SHIP;
    const uint32_t o = (lane >> 1) * SHIP, own = sb + C_Q + rank * 10240, bt = bars + B_T * 8;
    const uint32_t d2 = 1 + (lane & 1);
    const uint32_t src2 = (rank == 0 ? sb + C_SA : rank == 1 ? own : sb + C_SB) + o;
    const uint32_t skip = (lane & 1) ? 4 | (o >> 11) : 8;
#pragma unroll 1
    for (int st = 0; st < NSTEP; st++) {
      mbar_wait(bars + B_P1 * 8, st & 1, 61);
      fence_async_smem();
      mbar_wait(bars + B_F * 8, st & 1, 60);
      if (st > 0) mbar_wait(bars + (S1GATE ? B_PI : B_J) * 8, (st - 1) & 1, 65);
      const uint32_t info = lds32(sb + C_INFO + (st & 1) * 4);
      TR(2)
      if (st < NSEG && rank != 0 && lane < 2 * NP && d2 == 1 && !(expf_ & 1)) bulk_s2r(mapa_u32(own + o, 0), sb + C_SA + o, SHIP, mapa_u32(bt, 0));
      __syncwarp();
      TR(3)
      mbar_wait(bars + B_P2 * 8, st & 1, 62);
      fence_async_smem();
      if (st > 0 && (SHIPLATE >> rank & 1)) mbar_wait(bars + B_I * 8, (st - 1) & 1, 64);
      TR(0)
      if (st >= DELTA && lane < 2 * NP && d2 != rank && (info & 7) != skip && !(expf_ & 2)) bulk_s2r(mapa_u32(own + o, d2), src2, SHIP, mapa_u32(bt, d2));
      __syncwarp();
      TR(1)
    }
  } else if (w == 14) {
    const int s0 = rank == 0 ? 0 : DELTA;
    const uint32_t tbytes = (expf_ & (rank ? 2 : 1)) ? 0 : 16384;
    mbar_expect_tx_z(bars + B_T * 8, s0 == 0 ? tbytes : 0, lane);
#pragma unroll 1
    for (int st = 0; st < NSTEP; st++) {
      const int sg = st - s0;
      const bool act = (unsigned)sg < (unsigned)NSEG;
      mbar_wait(bars + B_OT * 8, st & 1, 70);
      mbar_expect_tx_z(bars + B_T * 8, (unsigned)(sg + 1) < (unsigned)NSEG ? tbytes : 0, lane);
      fence_async_smem();
      const int s1 = rank && st < NSEG - 1 ? st + 1 : st;
      if (s1 != st) mbar_wait(bars + B_X * 8, s1 & 1, 71);
      TR(0)
      if (act && lane == 0 && !(expf_ & (rank ? 32 : 16))) {
        bulk_s2g(g_O[st & (OSLOTS - 1)][rank] + h * 8192, sb + C_OT + (st & 1) * 8192, 8192);
        asm volatile("cp.async.bulk.commit_group;" ::: "memory");
        asm volatile("cp.async.bulk.wait_group 0;" ::: "memory");
        asm volatile("fence.acq_rel.gpu;" ::: "memory");
      }
      __syncwarp();
      if (WLAG && s1 < NSTEP - 1) mbar_wait(bars + (FGATE ? B_M0 + FGATE - 1 : B_I) * 8, (s1 + (FGATE > 0)) & 1, 72);
      if (act && lane == 0) asm volatile("red.relaxed.gpu.global.add.u32 [%0], 1;" ::"l"(&g_fl.oflag[rank][sg][h >> 2]) : "memory");
      __syncwarp();
      TR(1)
    }
  } else {
    mbar_arrive_z(bars + B_M0 * 8, lane); mbar_arrive_z(bars + B_M1 * 8, lane); mbar_arrive_z(bars + B_M2 * 8, lane);
    const uint32_t wave = rank == 2 ? 0 : rank + 1, gate_p = GATE_P + wave * GATE_W, gate_g = GATE_G, gate_m = GATE_M;
    uint32_t nupd = 0, late = 128;
    bar_sync(NB_GO, 160);
#pragma unroll 1
    for (int st = 0; st < NSTEP - 1; st++) {
      mbar_wait(bars + B_X * 8, st & 1, 75);
      if (st < 4) { HD(8 + st) }
      if (st == NSTEP - 2) { HD(12) }
      mbar_wait(bars + B_T * 8, st & 1, 77);
      const uint32_t now = gtime() & ~31u, tag = (st + 1) & 31;
      if (lane == 0) st_rlx32(&g_fl.stamp[blockIdx.x], (now + late) | tag);
      late = 0;
      __syncwarp();
      wait_clock(clk32() + 550);
      uint32_t s0, s1, s2;
      int it = 0;
#pragma unroll 1
      do {
        s0 = ld_rlx32(&g_fl.stamp[lane]) ^ tag; s1 = ld_rlx32(&g_fl.stamp[32 + lane]) ^ tag; s2 = ld_rlx32(&g_fl.stamp[64 + lane]) ^ tag;
        give_up(it++, SPIN_LIMIT, 76);
      } while (__any_sync(~0u, ((s0 | s1 | s2) & 31) != 0));
      const uint32_t tref = now + __reduce_max_sync(~0u, __vimax3_s32((int)(s0 - now), (int)(s1 - now), (int)(s2 - now)));
      const uint32_t g0 = gtime();
      uint32_t g1, c1;
      it = 0;
      do { g1 = gtime(); c1 = clk32(); } while (g1 == g0 && ++it < 64);
      c1 -= (g1 - tref) * 7 / 4;
      sts32(sb + C_INFO + 12, c1);
      TR(0)
      bar_sync(NB_TA, 192);
      const int sn = (st + 1) & 3;
      const uint8_t* src = (const uint8_t*)g_M + sn * 65536 + (lds32(sb + C_POL + sn * 4) ? 4096 : 12288);
      {
        const uint32_t pol = lds32(sb + C_INFO + 8);
        const uint8_t* ps = (const uint8_t*)g_P + (wave * 32 + h) * 16384;
        if (lane == 0) {
          mbar_expect_tx(bars + B_PI * 8, 8192);
          wait_clock(c1 + gate_p);
          bulk_g2s(sb + C_PI, ps + pol * 4096, 4096, bars + B_PI * 8);
          bulk_g2s(sb + C_PI + 4096, ps + (3 - pol) * 4096, 4096, bars + B_PI * 8);
          mbar_arrive_z(bars + B_J * 8, 0);
        }
        __syncwarp();
      }
      c1 += gate_m;
      if (__builtin_expect(lds32(sb + C_INFO + ((st + 1) & 1) * 4), 0)) {
        late = rank == 2 ? 96 : 0;
        mbar_wait(bars + B_U * 8, nupd++ & 1, 78);
        const uint32_t c2 = lds32(sb + C_INFO + 40) + UGATE;
        if ((int)(c2 - c1) > 0) c1 = c2;
      }
      mbar_expect_tx_z(bars + (B_M0 + lane) * 8, 8192, lane / 3);
      if (lane == 0) {
#pragma unroll
        for (int g = 0; g < 3; g++) {
          wait_clock(c1 + g * gate_g);
          bulk_g2s(sb + C_M + g * 8192, src + g * 16384, 8192, bars + (B_M0 + g) * 8);
          if (g == IGRP) mbar_arrive_z(bars + B_I * 8, 0);
        }
      }
      __syncwarp();
      TR(3)
    }
  }
}

struct ChainMaps { CUtensorMap w[3], wo; };
__global__ void __cluster_dims__(3, 1, 1) __launch_bounds__(512, 1)
chain_kernel(const __grid_constant__ ChainMaps maps, const bf16* __restrict__ mem0, const bf16* __restrict__ x0) {
  extern __shared__ __align__(1024) uint8_t smem_raw[];
  const uint32_t sb = (smem_u32(smem_raw) + 1023) & ~1023u;
  const int tid = threadIdx.x, lane = tid & 31;
  const int w = __shfl_sync(~0u, tid >> 5, 0);
  uint32_t rank;
  asm volatile("mov.u32 %0, %%cluster_ctarank;" : "=r"(rank));
  const int h = blockIdx.x / 3;
  asm volatile("griddepcontrol.launch_dependents;" ::: "memory");
  TG(0)
  const int row2 = 32 + blockIdx.x * 16 + w, row3 = 1568 + min(w, 4) * 96 + blockIdx.x;
  Row xr[4] = {load_row(x0 + row2 * DM, lane), load_row(x0 + row3 * DM, lane), load_row(x0 + w * DM, lane), load_row(x0 + (w + 16) * DM, lane)};
  if (tid == 0) {
    const uint32_t bars = sb + C_BAR;
    mbar_init(bars + B_M0 * 8, 1); mbar_init(bars + B_M1 * 8, 1); mbar_init(bars + B_M2 * 8, 1);
    mbar_init(bars + B_X * 8, 9); mbar_init(bars + B_O * 8, 2); mbar_init(bars + B_T * 8, 1); mbar_init(bars + B_F * 8, 2);
    mbar_init(bars + B_XL * 8, 2); mbar_init(bars + B_U * 8, 1);
    mbar_init(bars + B_P1 * 8, 8); mbar_init(bars + B_P2 * 8, 8); mbar_init(bars + B_OT * 8, 3); mbar_init(bars + B_XF * 8, 8); mbar_init(bars + B_XA * 8, 8); mbar_init(bars + B_I * 8, 1); mbar_init(bars + B_PI * 8, 1); mbar_init(bars + B_J * 8, 1);
    mbar_init(bars + B_W * 8, 1); mbar_init(bars + B_WO * 8, 1);
    asm volatile("fence.mbarrier_init.release.cluster;" ::: "memory");
    fence_async_smem();
    stage_weights(sb + C_STG, &maps.w[rank], h * 128, 0, bars + B_W * 8);
    const int nt = rank == 2 ? 2 : 3;
    mbar_expect_tx(bars + B_WO * 8, nt * 16384);
    for (int tl = 0; tl < nt; tl++)
      asm volatile("cp.async.bulk.tensor.5d.shared::cluster.global.mbarrier::complete_tx::bytes [%0], [%1, {%3, 0, 0, 0, %4}], [%2];"
                   ::"r"(sb + C_WO + tl * 16384), "l"(&maps.wo), "r"(bars + B_WO * 8), "r"((tl * 3 + rank) * 64), "r"(h * 4) : "memory");
  }
  __syncwarp();
  asm volatile("barrier.cluster.arrive.relaxed.aligned;" ::: "memory");
  {
    const int gt = blockIdx.x * 512 + tid, g1 = gt - 12288, g2 = gt - 12288 - 16384, g3 = gt - 45056;
    static_assert(12288 + 16384 + sizeof(Flags) / 16 <= 45056, "reset");
    if (g1 < 0) ((uint4*)g_M)[gt / 3072 * 4096 + 256 + gt % 3072] = make_uint4(~0u, ~0u, ~0u, ~0u);
    else if (g2 < 0) ((uint4*)(g_part[1] + 32 * 8192))[g1] = make_uint4(0, 0, 0, 0);
    else if (g2 < (int)(sizeof(Flags) / 16)) ((uint4*)&g_fl)[g2] = make_uint4(0, 0, 0, 0);
    else if (g3 >= 0) ((uint4*)g_x2p[g3 >> 6][1])[g3 & 63] = make_uint4(~0u, ~0u, ~0u, ~0u);
    if ((NSTEP - 1) & 1) { ((uint4*)g_P)[gt] = make_uint4(0, 0, 0, 0); ((uint4*)g_P)[gt + 49152] = make_uint4(0, 0, 0, 0); }
#pragma unroll 1
    for (int i = 0; i < 4; i++) {
      if (i != 1 || w < 5) {
        const int row = i == 0 ? row2 : i == 1 ? row3 : (i - 2) * 16 + w;
        store_row_img(i < 2 ? g_xs[0] + (row >> 5) * 32768 : smem_raw + (sb - smem_u32(smem_raw)) + C_X, row & 31, lane, warp_ln(xr[0]));
      }
      xr[0] = xr[1]; xr[1] = xr[2]; xr[2] = xr[3];
    }
  }
  fence_async_smem();
  __syncthreads();
  asm volatile("barrier.cluster.wait.aligned;" ::: "memory");
  if (tid == 448) red_release(g_ex.ready);
  __syncwarp();
  if (w < 8) {
    reg_inc<184>();
    chain_proj(sb, w, lane, rank);
    TG(1)
    TRDUMP
    cluster_sync();
  } else if (w < 12) {
    reg_dec<120>();
    chain_mem(sb, w, lane, rank, h, mem0);
    STATDUMP
    TRDUMP
    cluster_sync();
  } else {
    reg_dec<24>();
    chain_dma(sb, w, lane, rank, h);
    TRDUMP
    cluster_sync();
  }
}
#undef TRC
#undef TRS

constexpr int K_BAR = 0, K_LN = 128, K_FH = 320, K_FS = 512, K_FY = 1536;
constexpr int K_W = 3072;
constexpr int K_O = K_W + 3 * 49152;
constexpr int K_ST = K_O + 65536;
constexpr int K_SMEM = K_ST + 16384;
static_assert(K_SMEM <= 232448, "shared memory");
enum { KB_FULL = 0, KB_EMPTY = 2, KB_OK = 4, KB_GO = 7, KB_ST = 10, KB_REL = 12, KB_W = 13 };
enum { KN_ST = 1, KN_ST1, KN_REL, KN_FFN, KN_INIT, KN_RES, KN_RES1, KN_CAND, KN_TAKEN, KN_FF2 };
#define GATE_R 850
struct WorkerParams {
  CUtensorMap wo;
  const bf16 *x0, *w_r, *w_gate, *w_up, *w_down;
  bf16* out;
};
#define TRC (96 + blockIdx.x)
#define FT(e)
#define NCOPY 4
#define QUIET 4500
__device__ __forceinline__ void quiet_until(uint32_t t) {
  int d;
  while ((d = (int)(t - clk32())) > 0) warp_sleep(min(d / 3 + 20, 1000));
}
#define FOR_UNITS _Pragma("unroll 1") for (int st = 0, n = 0; st < WSTEP; st++) \
                  _Pragma("unroll 1") for (int v = st < NSEG ? 0 : st < WSTEP - 1 ? 1 : 2, sg = v ? st - WD : st; v < (st >= WD ? 3 : 1); v++, n++, sg = st - WD)

template <int ACC>
__device__ __forceinline__ void wg_ss8(float (&d)[4], uint64_t da, uint64_t db) {
  asm volatile("wgmma.mma_async.sync.aligned.m64n8k16.f32.bf16.bf16 {%0,%1,%2,%3}, %4, %5, %6, 1, 1, 1, 0;" : O4(d, 0) : "l"(da), "l"(db), "n"(ACC));
}
template <int NU>
__device__ __forceinline__ void ffn_slice(uint32_t sb, int t, const bf16* yrow, int ev) {
  const int lane = t & 31, c = t >> 5;
  FT(1)
  {
    const uint2 r = ld_rlx64(yrow + t * 4);
    asm volatile("st.shared.v2.b32 [%0], {%1,%2};" ::"r"(sb + K_FY + ((t >> 1) & 31) * 32 + (t >> 6) * 16 + (t & 1) * 8), "r"(r.x), "r"(r.y) : "memory");
  }
  fence_async_smem();
  bar_sync(KN_FFN, 128);
  FT(2)
  {
    float g[NU][4];
    const uint64_t da = mk_desc(sb + K_W, 16384, 512, 2), db = mk_desc(sb + K_FY, 32, 0, 0);
    wg_fence();
#pragma unroll
    for (int i = 0; i < 16; i++)
#pragma unroll
      for (int u = 0; u < NU; u++) { if (i == 0) wg_ss8<0>(g[u], da + u * 3072, db); else wg_ss8<1>(g[u], da + u * 3072 + i * 64, db + i * 4); }
    wg_commit();
    wg_wait<0>();
#pragma unroll
    for (int u = 0; u < NU; u++) {
      acc_fence(g[u]);
      if ((lane & 3) == 0) {
        const uint32_t a = sb + K_FS + u * 256 + c * 64 + lane;
        sts32(a, __float_as_uint(c < 2 ? g[u][0] : g[u][1])); sts32(a + 32, __float_as_uint(c < 2 ? g[u][2] : g[u][3]));
      }
    }
  }
  FT(3)
  bar_sync(KN_FFN, 128);
  {
    const uint32_t pa = sb + K_FS + c * 256 + lane * 4;
    const float gt = round_bf16(__uint_as_float(lds32(pa)) + __uint_as_float(lds32(pa + 128)));
    const float up = __shfl_xor_sync(~0u, gt, 16);
    const uint32_t hv = pack_bf16(round_bf16(__fdividef(gt, 1.f + __expf(-gt))) * up, 0.f);
    if (lane < 16) asm volatile("st.shared.b16 [%0], %1;" ::"r"(sb + K_FH + (c * 16 + lane) * 2), "h"((unsigned short)hv) : "memory");
  }
  fence_async_smem();
  bar_sync(KN_FFN, 128);
  FT(4)
  float old[4];
#pragma unroll
  for (int hf = 0; hf < 2; hf++) {
    float o[4][4];
    const uint64_t da = mk_desc(sb + K_W + 32768 + hf * 8192, 16, 1024, 1), db = mk_desc(sb + K_FH, 16, 0, 0);
    wg_fence();
#pragma unroll
    for (int u = 0; u < NU; u++)
#pragma unroll
      for (int j = 0; j < 4; j++) { if (u == 0) wg_ss8<0>(o[j], da + j * 128, db); else wg_ss8<1>(o[j], da + u * 3072 + j * 128, db + u * 2); }
    wg_commit();
    wg_wait<0>();
    float lo = 0.f, hi = 0.f;
#pragma unroll
    for (int j = 0; j < 4; j++) {
      acc_fence(o[j]);
      const float a = __shfl_sync(~0u, o[j][0], lane & 28), b = __shfl_sync(~0u, o[j][2], lane & 28);
      if ((lane & 3) == j) { lo = a; hi = b; }
    }
    float* p = &g_fl.upd[ev][hf * 256 + (lane & 3) * 64 + c * 16 + (lane >> 2)];
    asm volatile("atom.relaxed.gpu.global.add.f32 %0, [%2], %3; atom.relaxed.gpu.global.add.f32 %1, [%2 + 32], %4;"
                 : "=f"(old[2 * hf]), "=f"(old[2 * hf + 1]) : "l"(p), "f"(lo), "f"(hi) : "memory");
  }
  sts32(sb + K_FY + t * 4, __float_as_uint((old[0] + old[1]) + (old[2] + old[3])));
  FT(5)
  bar_sync(KN_FFN, 128);
  if (t == 96) asm volatile("red.relaxed.gpu.global.add.u32 [%0], 1;" ::"l"(g_fl.ffncnt[ev]) : "memory");
  __syncwarp();
}
__device__ __forceinline__ uint4 pair_ln(uint4 r, float& e, uint32_t sl, int bar, int t) {
  const float x[8] = {bf_lo(r.x), bf_hi(r.x), bf_lo(r.y), bf_hi(r.y), bf_lo(r.z), bf_hi(r.z), bf_lo(r.w), bf_hi(r.w)};
  const float s = ((x[0] + x[1]) + (x[2] + x[3])) + ((x[4] + x[5]) + (x[6] + x[7]));
  const float q = (fmaf(x[0], x[0], x[1] * x[1]) + fmaf(x[2], x[2], x[3] * x[3])) + (fmaf(x[4], x[4], x[5] * x[5]) + fmaf(x[6], x[6], x[7] * x[7]));
  const bool u16 = t & 16, u8 = t & 8;
  const float a = (u16 ? q : s) + __shfl_xor_sync(~0u, u16 ? s : q, 16), b = e + __shfl_xor_sync(~0u, e, 16);
  float v = (u8 ? b : a) + __shfl_xor_sync(~0u, u8 ? a : b, 8);
  v += __shfl_xor_sync(~0u, v, 4); v += __shfl_xor_sync(~0u, v, 2); v += __shfl_xor_sync(~0u, v, 1);
  sts32(sl + (t >> 3) * 4, __float_as_uint(v));
  bar_sync(bar, 64);
  const uint4 s0 = lds128(sl), s1 = lds128(sl + 16);
  const float m = (__uint_as_float(s0.x) + __uint_as_float(s1.x)) * (1.f / DM), m2 = (__uint_as_float(s0.z) + __uint_as_float(s1.z)) * (1.f / DM);
  e = __uint_as_float(s0.y) + __uint_as_float(s1.y);
  float rs;
  asm("rsqrt.approx.ftz.f32 %0, %1;" : "=f"(rs) : "f"(fmaxf(fmaf(-m, m, m2), 0.f) + 1e-5f));
  return make_uint4(pack_bf16((x[0] - m) * rs, (x[1] - m) * rs), pack_bf16((x[2] - m) * rs, (x[3] - m) * rs),
                    pack_bf16((x[4] - m) * rs, (x[5] - m) * rs), pack_bf16((x[6] - m) * rs, (x[7] - m) * rs));
}
__device__ __forceinline__ uint32_t score_bits(float r) {
  const uint32_t b = pack_bf16(0.f, r);
  return (b & 0x80000000u) ? ~b : (b | 0x80000000u);
}

__global__ void __launch_bounds__(640, 1) worker_kernel(const __grid_constant__ WorkerParams prm) {
  extern __shared__ __align__(1024) uint8_t smem_raw[];
  const uint32_t sb = smem_u32(smem_raw);
  if (sb & 1023) __trap();
  const int tid = threadIdx.x, lane = tid & 31;
  const int w = __shfl_sync(~0u, tid >> 5, 0);
  const int me = blockIdx.x, kb = me >> 2, cb = me & 3;
  const bool full = me < 32;
  const uint32_t bars = sb + K_BAR;
  TG(0)
  if (tid == 0) {
    for (int i = 0; i < 2; i++) { mbar_init(bars + (KB_FULL + i) * 8, 1); mbar_init(bars + (KB_EMPTY + i) * 8, 1); }
    for (int i = 0; i < 10; i++) mbar_init(bars + (KB_OK + i) * 8, i < 3 ? 2 : 1);
    sts32(sb + K_LN + 144, 0);
    asm volatile("fence.mbarrier_init.release.cluster;" ::: "memory");
    fence_async_smem();
  }
  __syncwarp();
  if (w == 0) {
    wait_count(g_ex.ready, 96, 94);
    if (lane == 0 && full) stage_weights(sb + K_W, &prm.wo, cb * 128, kb * 512, bars + KB_W * 8);
  }
  __syncthreads();
  if (w < 8) {
    reg_inc<176>();
    if (full) {
      uint32_t wA[32][4];
      mbar_wait(bars + KB_W * 8, 0, 79);
      load_wfrags(wA, sb + K_W, w, lane);
      bar_arrive(KN_INIT, 384);
      const uint32_t sp = pin(sb + K_ST + ((lane >> 4) * 8 + (lane & 7)) * 256 + (((2 * w + ((lane >> 3) & 1)) ^ (lane & 7)) << 4));
      const uint32_t tm = pin(lane < 4 ? 0x00010001u : 0u);
      FOR_UNITS {
        float d[16];
        mbar_wait(bars + (KB_FULL + (n & 1)) * 8, (n >> 1) & 1, 81);
        TR(4 * v)
        const uint64_t db = mk_desc(sb + K_O + (n & 1) * 32768, 128, 2048, 0);
        wg_fence();
#pragma unroll
        for (int ks = 0; ks < 32; ks++) {
          if (ks == 0) wg_rs32<0, 0>(d, wA[ks], db);
          else wg_rs32<0, 1>(d, wA[ks], db + (ks >> 3) * 512 + (ks & 7) * 16);
        }
        wg_commit();
        mbar_wait(bars + (KB_ST + (n & 1)) * 8, ((n >> 1) & 1) ^ 1, 82);
        wg_wait<0>();
        acc_fence(d);
        TR(4 * v + 1)
        const uint32_t tag = (sg & 2) ? 0u : tm;
        uint32_t pk[8];
#pragma unroll
        for (int i = 0; i < 8; i++) pk[i] = (pack_bf16(d[2 * i], d[2 * i + 1]) & ~tm) | tag;
        stsm4t(sp + (n & 1) * 8192, pk[0], pk[1], pk[2], pk[3]);
        stsm4t(sp + (n & 1) * 8192 + 4096, pk[4], pk[5], pk[6], pk[7]);
        bar_arrive(KN_ST + (n & 1), 288);
        TR(4 * v + 2)
      }
    }
  } else if (w < 12) {
    reg_dec<56>();
    if (full) {
      const int ly = (w >> 1) & 1, t = pin(tid & 63);
      const uint32_t so = pin((t >> 4) * 8192 + me * 256 + (((t & 15) ^ (me & 7)) << 4));
      int sstar = -1;
      uint32_t sl = sb + K_LN + ly * 64;
      float rr = 0.f;
      int kprev = -1;
      auto records = [&](int sg, uint32_t off) {
        int it = 0;
        while (__any_sync(~0u, (int)lds32_poll(sb + K_LN + 144) <= sg)) { give_up(++it, SPIN_LIMIT, 86); warp_sleep(50); }
        return lds32_poll(sb + K_LN + off);
      };
#pragma unroll 1
      for (int n = ly ? 2 * WD : 0; n < 2 * WSTEP; n++) {
        const int st = n >> 1, v = (n & 1) ? 2 : ly, sg = v ? st - WD : st, tok = sg * 32 + me;
        if (n == 2 * NSEG) bar_sync(KN_INIT, 128);
        if (n == 2 * NSEG + 2) sstar = records(NSEG - 1, 156);
        if (v == 2 ? sg < 0 || (st < NSEG ? st & 1 : 0) != ly : sg >= NSEG - v) continue;
        const bf16* xin = v ? g_rows[tok][0][2] : prm.x0 + tok * DM;
        if (v == 2 && ((records(sg, 148 + (sg >> 5) * 4) >> (sg & 31)) & 1)) xin = g_x2p[sg][0];
        const uint8_t* src = g_part[v] + (sg & 1) * (32 * 8192) + so;
        const uint32_t flip = (sg & 2) ? ~0u : 0u;
        mbar_wait(bars + (KB_GO + v) * 8, sg & 1, 87);
        TR(4 * v)
        uint4 p[8], x;
        int it = 0;
#pragma unroll 1
        do {
#pragma unroll
          for (int k = 0; k < 8; k++) p[k] = ld_rlx128(src + k * 32768);
          x = ld_rlx128(((WEXP & 2) ? prm.x0 : xin) + t * 8);
          give_up(it++, SPIN_LIMIT, 85);
        } while (__builtin_expect(!__all_sync(~0u, (int)and3(and3(and_x(p[0].x, p[1].x, flip), and_x(p[2].x, p[3].x, flip), 1u),
                                                             and_x(p[4].x, p[5].x, flip), and_x(p[6].x, p[7].x, flip))), 0));
        mbar_arrive_z(bars + (KB_OK + v) * 8, t & 31);
#define P8(h, f) (((h(p[0].f) + h(p[1].f)) + (h(p[2].f) + h(p[3].f))) + ((h(p[4].f) + h(p[5].f)) + (h(p[6].f) + h(p[7].f))))
#define X8(f) x.f = add_bf16x2(x.f, pack_bf16(P8(bf_lo, f), P8(bf_hi, f)));
        X8(x) X8(y) X8(z) X8(w)
#undef X8
#undef P8
        TRV(12 + v, it - 1)
        TR(4 * v + 1)
        bf16* dst = g_rows[tok][v][0] + t * 8;
        *(uint4*)dst = x;
        const uint4 wr = ld_rlx128(prm.w_r + t * 8);
        sl ^= 32;
        uint4 y = pair_ln(x, rr, sl, KN_RES + ly, t);
        *(uint4*)(dst + DM) = y;
        x = make_uint4(add_bf16x2(x.x, y.x), add_bf16x2(x.y, y.y), add_bf16x2(x.z, y.z), add_bf16x2(x.w, y.w));
        *(uint4*)(v == (sg < sstar ? 1 : 2) ? prm.out + tok * DM + t * 8 : dst + 2 * DM) = x;
        asm volatile("{ .reg .pred p; setp.eq.u32 p, %2, 0; @p st.relaxed.gpu.global.u64 [%0], %1; }" ::"l"(&g_fl.key[0][0][0] + max(kprev, 0)),
                     "l"((u64)score_bits(rr) << 32 | (uint32_t)~(kprev & (NTOK - 1))), "r"(t | (kprev < 0)) : "memory");
        kprev = v * NTOK + tok;
        rr = (fmaf(bf_lo(y.x), bf_lo(wr.x), bf_hi(y.x) * bf_hi(wr.x)) + fmaf(bf_lo(y.y), bf_lo(wr.y), bf_hi(y.y) * bf_hi(wr.y))) +
             (fmaf(bf_lo(y.z), bf_lo(wr.z), bf_hi(y.z) * bf_hi(wr.z)) + fmaf(bf_lo(y.w), bf_lo(wr.w), bf_hi(y.w) * bf_hi(wr.w)));
        if (v == 0 || st >= NSEG) {
          sl ^= 32;
          y = pair_ln(x, rr, sl, KN_RES + ly, t);
          if (v == 0) *(uint4*)(g_xs[1] + sg * 32768 + (t >> 3) * 4096 + me * 128 + (((t ^ me) & 7) << 4)) = y;
          sts32(sb + K_LN + 128 + ly * 4, score_bits(rr));
          bar_arrive(KN_REL, v == 0 || st == WSTEP - 1 ? 96 : 160);
          kprev = -1;
        }
        TR(4 * v + 2)
      }
    }
  } else if (w < 16) {
    reg_dec<48>();
    const int t = tid - 384, nu = full ? 3 : 4;
    if (full) bar_sync(KN_INIT, 384);
    {
      const int j0 = (full ? me * 3 : 96 + (me - 32) * 4) * 16;
#pragma unroll 1
      for (int i = t; i < nu * 3072; i += 128) {
        const int u = i / 3072, r = i - u * 3072;
        const int q = (r ^ (r >> 3)) & 3, r2 = r - 2048;
        const bf16* src = r < 2048 ? ((q & 2) ? prm.w_up : prm.w_gate) + (size_t)(r >> 2) * FF + j0 + u * 16 + (q & 1) * 8
                                   : prm.w_down + (size_t)(j0 + u * 16 + ((r2 >> 3) & 15)) * DM + (r2 >> 7) * 64 + ((r2 ^ (r2 >> 3)) & 7) * 8;
        cp16(sb + K_W + i * 16, src);
      }
      asm volatile("cp.async.wait_all;" ::: "memory");
    }
    bar_arrive(KN_TAKEN, 160);
#pragma unroll 1
    while (true) {
      bar_sync(KN_CAND, 160);
      const uint4 cand = lds128(sb + K_LN + 160);
      const u64 k = (u64)cand.y << 32 | cand.x;
      const int ev = cand.z, ver = cand.w & 3, tok = key_token(k);
      const bool last = cand.w & 4;
      if (!last) {
        bar_arrive(KN_TAKEN, 160);
        FT(0)
        if (full) ffn_slice<3>(sb, t, g_rows[tok][ver][1], ev); else ffn_slice<4>(sb, t, g_rows[tok][ver][1], ev);
      }
      if ((tok & 31) == me && (ver == 0 || last)) {
        if (t < 64) {
          FT(6)
          uint4 x = ld_rlx128(g_rows[tok][ver][0] + t * 8);
          const uint4 y = ld_rlx128(g_rows[tok][ver][1] + t * 8);
          const float sig = round_bf16(__fdividef(1.f, 1.f + __expf(-key_score(k))));
          int it = 0;
          while (poll32(g_fl.ffncnt[ev]) < NWORK) { give_up(++it, SPIN_LIMIT, 80); warp_sleep(40); }
          uint4 u0, u1;
          asm volatile("atom.relaxed.gpu.global.add.v4.f32 {%0,%1,%2,%3}, [%8], {%9,%9,%9,%9}; atom.relaxed.gpu.global.add.v4.f32 {%4,%5,%6,%7}, [%8 + 16], {%9,%9,%9,%9};"
                       : "=r"(u0.x), "=r"(u0.y), "=r"(u0.z), "=r"(u0.w), "=r"(u1.x), "=r"(u1.y), "=r"(u1.z), "=r"(u1.w) : "l"(&g_fl.upd[ev][t * 8]), "r"(0) : "memory");
          auto upd = [&](uint32_t xw, uint32_t yw, uint32_t a, uint32_t b) {
            const uint32_t r = pack_bf16(__uint_as_float(a), __uint_as_float(b));
            return add_bf16x2(xw, add_bf16x2(yw, pack_bf16(bf_lo(r) * sig, bf_hi(r) * sig)));
          };
          x = make_uint4(upd(x.x, y.x, u0.x, u0.y), upd(x.y, y.y, u0.z, u0.w), upd(x.z, y.z, u1.x, u1.y), upd(x.w, y.w, u1.z, u1.w));
          FT(7)
          *(uint4*)((ver ? prm.out + tok * DM : g_x2p[ev][0]) + t * 8) = x;
          if (ver == 0) {
            float e = 0.f;
            *(uint4*)(g_x2p[ev][1] + t * 8) = pair_ln(x, e, sb + K_FS, KN_FF2, t);
          }
        }
      }
      FT(8)
      if (last) break;
    }
  } else {
    reg_dec<24>();
    if (w == 16) {
      u64 best = 0, mask = 0;
      int sstar = 0;
      uint32_t ver = 0, ev = 0;
      auto post = [&](uint32_t cmd) {
        bar_sync(KN_TAKEN, 160);
        sts128(sb + K_LN + 160, make_uint4((uint32_t)best, (uint32_t)(best >> 32), ev, ver | cmd));
        bar_arrive(KN_CAND, 160);
      };
      u64 accn = 0, acca = 0;
      uint32_t recs = 0;
      int j = 0, jc = 0;
      uint32_t tq = clk32();
#pragma unroll 1
      for (int st = 0; st < WSTEP; st++) {
        const u64* keys = st < NSEG ? g_fl.key[0][st] : g_fl.key[2][st - WD];
        if (st < NSEG) quiet_until(tq);
        const uint32_t t0 = clk32();
        u64 k = wait_keys<true>(keys, lane, 91);
        tq = (clk32() - t0 > 1100 ? clk32() : tq) + QUIET;
        if (st < NSEG) {
          const bool rec = k > best;
          recs &= ~(1u << (st & 31));
          if (rec) {
            best = k; ev = sstar = st;
            recs |= 1u << (st & 31);
            if ((key_token(k) & 31) == me) mask |= 1ull << st;
          }
          if (lane == 0) sts128(sb + K_LN + 144, make_uint4(st + 1, (uint32_t)mask, (uint32_t)(mask >> 32), sstar));
          __syncwarp();
          if (rec) post(0);
        }
#pragma unroll 1
        for (; j <= st - WD - (st < NSEG ? 2 : 0); j++) {
          u64 kn = 1, kc;
          int it = 0;
          do {
            if (j < NSEG - 1) asm volatile("ld.relaxed.gpu.global.u64 %0, [%1];" : "=l"(kn) : "l"(&g_fl.key[1][j][lane]) : "memory");
            asm volatile("ld.relaxed.gpu.global.u64 %0, [%1];" : "=l"(kc) : "l"(&g_fl.key[2][j][lane]) : "memory");
            give_up(it++, SPIN_LIMIT, 92);
          } while (__any_sync(~0u, kn == 0 || kc == 0));
          if ((recs >> (j & 31)) & 1) acca = accn;
          if (kc > acca) acca = kc;
          if (kn > accn) accn = kn;
        }
        if (st >= NSEG) {
          const u64 m = j <= sstar ? accn : acca;
          const uint32_t hi = __reduce_max_sync(~0u, (uint32_t)(m >> 32));
          k = (u64)hi << 32 | __reduce_max_sync(~0u, (uint32_t)(m >> 32) == hi ? (uint32_t)m : 0u);
          if (st == NSEG || k != best) {
            best = k; ev = st;
            ver = (key_token(k) >> 5) < sstar ? 1 : 2;
            post(0);
          }
        }
        const int nc = min(min(min(sstar, j), NSEG + 1 - WD), st < NSEG ? jc + NCOPY : st < WSTEP - 2 ? jc + 2 * NCOPY : NSEG);
#pragma unroll 1
        for (; jc < nc && full; jc++) {
          const bf16* src = g_rows[jc * 32 + me][1][2] + lane * 8;
          bf16* dst = prm.out + (jc * 32 + me) * DM + lane * 8;
          const uint4 a = ld_rlx128(src), b = ld_rlx128(src + 256);
          *(uint4*)dst = a; *(uint4*)(dst + 256) = b;
        }
      }
      HD(6)
      post(4);
      if (me == 0 && lane == 0) st_rlx32(g_ex.ready, 0);
    } else if (!full) {
    } else if (w == 17) {
      uint32_t tq = clk32();
      FOR_UNITS {
        const bool first = v == (st < NSEG ? 0 : 1) && st < WSTEP - 3;
        if (first) { quiet_until(tq); tq += QUIET; }
        if (poll32(&g_fl.oflag[v][sg][kb]) < 4) {
          wait_count(&g_fl.oflag[v][sg][kb], 4, 84);
          if (first) tq = clk32() + QUIET;
        }
        mbar_wait(bars + (KB_EMPTY + (n & 1)) * 8, ((n >> 1) & 1) ^ 1, 83);
        TR(v)
        if (st == WSTEP - 1) { HD(v) }
        if (lane == 0) {
          fence_async_glb();
          mbar_expect_tx(bars + (KB_FULL + (n & 1)) * 8, (WEXP & 4) ? 4096 : 32768);
          bulk_g2s(sb + K_O + (n & 1) * 32768, g_O[(v ? sg + DELTA : sg) & (OSLOTS - 1)][v] + kb * 32768, (WEXP & 4) ? 4096 : 32768, bars + (KB_FULL + (n & 1)) * 8);
        }
        __syncwarp();
      }
    } else if (w == 18) {
      FOR_UNITS {
        if (sg > 0) mbar_wait(bars + (KB_OK + v) * 8, (sg - 1) & 1, 90);
        bar_sync(KN_ST + (n & 1), 288);
        fence_async_smem();
        const uint32_t tg = clk32() + GATE_R;
        if (lane == 0) {
          bulk_s2g(g_part[v] + ((sg & 1) * 32 + me) * 8192, sb + K_ST + (n & 1) * 8192, 8192);
          asm volatile("cp.async.bulk.commit_group;" ::: "memory");
          mbar_arrive_z(bars + (KB_EMPTY + (n & 1)) * 8, 0);
          asm volatile("cp.async.bulk.wait_group.read 0;" ::: "memory");
        }
        __syncwarp();
        mbar_arrive_z(bars + (KB_ST + (n & 1)) * 8, lane);
        TR(v)
        if (v == (st < NSEG ? 0 : st < WSTEP - 1 ? 1 : 2) && st > 0) mbar_wait(bars + KB_REL * 8, (st - 1) & 1, 93);
        wait_clock(tg);
        if (st == WSTEP - 1) { HD(2 + v) }
        mbar_arrive_z(bars + (KB_GO + v) * 8, lane);
      }
    } else {
#pragma unroll 1
      for (int st = 0; st < WSTEP; st++) {
        const int sg = st < NSEG ? st : st - WD;
        const bool both = st >= NSEG && st < WSTEP - 1;
        bar_sync(KN_REL, both ? 160 : 96);
        const uint32_t ob = __shfl_sync(~0u, lds32(sb + K_LN + 128), 0), obn = __shfl_sync(~0u, lds32(sb + K_LN + 132), 0);
        mbar_arrive_z(bars + KB_REL * 8, lane);
        if (st == WSTEP - 1) { HD(5) }
        if (lane == 0) {
          if (both) asm volatile("st.relaxed.gpu.global.u64 [%0], %1;" ::"l"(&g_fl.key[1][sg][me]), "l"((u64)obn << 32 | (uint32_t)~(sg * 32 + me)) : "memory");
          st_release_u64(&g_fl.key[st < NSEG ? 0 : 2][sg][me], (u64)ob << 32 | (uint32_t)~(sg * 32 + me));
        }
        __syncwarp();
        TR(0)
      }
    }
  }
}
#undef TRC

typedef CUresult (*EncodeFn)(CUtensorMap*, CUtensorMapDataType, cuuint32_t, void*, const cuuint64_t*, const cuuint64_t*,
                             const cuuint32_t*, const cuuint32_t*, CUtensorMapInterleave, CUtensorMapSwizzle,
                             CUtensorMapL2promotion, CUtensorMapFloatOOBfill);
void make_map(EncodeFn fn, CUtensorMap* m, const void* ptr, int rank, const cuuint64_t* dims, const cuuint64_t* strides, const cuuint32_t* box) {
  const cuuint32_t es[5] = {1, 1, 1, 1, 1};
  fn(m, CU_TENSOR_MAP_DATA_TYPE_BFLOAT16, rank, (void*)ptr, dims, strides, box, es, CU_TENSOR_MAP_INTERLEAVE_NONE,
     CU_TENSOR_MAP_SWIZZLE_128B, CU_TENSOR_MAP_L2_PROMOTION_L2_256B, CU_TENSOR_MAP_FLOAT_OOB_FILL_NONE);
}
struct HostState {
  const void* key[4];
  ChainMaps cm;
  CUtensorMap wo;
};
HostState g_hs;

}

extern "C" void kernel_launch(void* const* d_in, const int* in_sizes, int n_in, void* d_out, int out_size) {
  (void)in_sizes; (void)n_in; (void)out_size;
  HostState& hs = g_hs;
  if (hs.key[0] != d_in[2] || hs.key[1] != d_in[3] || hs.key[2] != d_in[4] || hs.key[3] != d_in[5]) {
    void* fnp = nullptr;
    cudaDriverEntryPointQueryResult qr;
    cudaGetDriverEntryPoint("cuTensorMapEncodeTiled", &fnp, cudaEnableDefault, &qr);
    const cuuint32_t box[2] = {64, 256}, box5[5] = {64, 2, 4, 4, 4};
    const cuuint64_t dw[2] = {HD, DM}, sw[1] = {HD * 2}, dwo[2] = {DM, HD}, swo[1] = {DM * 2};
    const cuuint64_t d5[5] = {DM, 2, 4, 4, HD / 32}, s5[4] = {DM * 2, 8 * DM * 2, 2 * DM * 2, 32 * DM * 2};
    for (int i = 0; i < 3; i++) make_map((EncodeFn)fnp, &hs.cm.w[i], d_in[2 + i], 2, dw, sw, box);
    make_map((EncodeFn)fnp, &hs.cm.wo, d_in[5], 5, d5, s5, box5);
    make_map((EncodeFn)fnp, &hs.wo, d_in[5], 2, dwo, swo, box);
    cudaFuncSetAttribute(worker_kernel, cudaFuncAttributeMaxDynamicSharedMemorySize, K_SMEM);
    cudaFuncSetAttribute(chain_kernel, cudaFuncAttributeMaxDynamicSharedMemorySize, C_SMEM);
    for (int i = 0; i < 4; i++) hs.key[i] = d_in[2 + i];
  }
  cudaStream_t st = cudaStreamPerThread;
  WorkerParams wp;
  wp.wo = hs.wo; wp.x0 = (const bf16*)d_in[0]; wp.w_r = (const bf16*)d_in[8]; wp.w_gate = (const bf16*)d_in[9];
  wp.w_up = (const bf16*)d_in[10]; wp.w_down = (const bf16*)d_in[11]; wp.out = (bf16*)d_out;
  chain_kernel<<<96, 512, C_SMEM, st>>>(hs.cm, (const bf16*)d_in[1], wp.x0);
  cudaLaunchAttribute pdl[1];
  pdl[0].id = cudaLaunchAttributeProgrammaticStreamSerialization;
  pdl[0].val.programmaticStreamSerializationAllowed = 1;
  cudaLaunchConfig_t cfg = {};
  cfg.gridDim = dim3(NWORK); cfg.blockDim = dim3(640); cfg.dynamicSmemBytes = K_SMEM; cfg.stream = st;
  cfg.attrs = pdl; cfg.numAttrs = 1;
  cudaLaunchKernelEx(&cfg, worker_kernel, wp);
}
```
